```python
import torch

def _softmax(x, axis=-1):
    return torch.softmax(x, dim=axis)
def _gelu(x):
    return torch.nn.functional.gelu(x, approximate="tanh")
def _silu(x):
    return torch.nn.functional.silu(x)
def _sigmoid(x):
    return torch.sigmoid(x)
def _layernorm(x, axis=-1, eps=1e-5):
    m = x.mean(dim=axis, keepdim=True)
    v = x.var(dim=axis, keepdim=True, unbiased=False)
    return (x - m) / torch.sqrt(v + eps)
def _scatter_add(tgt, idx, src, axis=0):
    return tgt.clone().index_add_(axis, idx, src)
def _segment_sum(src, seg, n):
    out = torch.zeros((n,) + src.shape[1:], dtype=src.dtype)
    return out.index_add_(0, seg, src)
def _pad(x, pw):
    flat = tuple(v for pair in reversed(pw) for v in pair)
    return torch.nn.functional.pad(x, flat)

kernel_name = 'standalone__deep_cross_fibinet__recsys'

def setup_inputs():

    _w = (lambda a: (lambda t: t.to(torch.bfloat16) if t.is_floating_point() else t)(torch.as_tensor(a)))
    B, F, D = 4096, 26, 64
    V = min(100000, 100000)
    Fr = max(F // 2, 1)
    H = min(F * D, 256)
    return {
        "idx": _w((lambda lo, hi, *s: torch.randint(lo, hi, s))(0, V, B, F).to(torch.int64)),
        "table": _w((lambda *s: torch.randn(*s, dtype=torch.bfloat16) * 1.6)(V, D)),
        "se_w1": _w((lambda *s: torch.randn(*s, dtype=torch.bfloat16) * 1.6)(F, Fr)),
        "se_w2": _w((lambda *s: torch.randn(*s, dtype=torch.bfloat16) * 1.6)(Fr, F)),
        "w_bi": _w((lambda *s: torch.randn(*s, dtype=torch.bfloat16) * 0.05)(D, D) * (D ** -0.5)),
        "w_cross": _w((lambda *s: torch.randn(*s, dtype=torch.bfloat16) * 0.05)(2 * F * F * D) * 0.01),
        "w_deep1": _w((lambda *s: torch.randn(*s, dtype=torch.bfloat16) * 0.8)(F * D, H) * ((F * D) ** -0.5)),
        "w_deep2": _w((lambda *s: torch.randn(*s, dtype=torch.bfloat16) * 0.05)(H) * 0.01),
    }

def reference(idx, table, se_w1, se_w2, w_bi, w_cross, w_deep1, w_deep2):
    emb = table[idx]
    B = emb.shape[0]
    z = emb.mean(axis=-1)
    a = _sigmoid(_gelu(z @ se_w1) @ se_w2)
    v = a[:, :, None] * emb
    eW = torch.einsum('bfd,de->bfe', emb, w_bi)
    vW = torch.einsum('bfd,de->bfe', v, w_bi)
    p = torch.einsum('bie,bje->bije', eW, emb).reshape(B, -1)
    q = torch.einsum('bie,bje->bije', vW, v).reshape(B, -1)
    cross_feat = torch.concatenate([p, q], axis=-1)
    logit_cross = cross_feat @ w_cross
    h = _gelu(emb.reshape(B, -1) @ w_deep1)
    logit_deep = h @ w_deep2
    return logit_cross + logit_deep
```

```cpp
#include <cuda_runtime.h>
#include <cuda_bf16.h>
#include <cuda.h>
#include <stdint.h>

namespace {

constexpr int NB = 4096, NF = 26, ND = 64, NH = 256, NR = 13;
constexpr int NPREP = 4;
constexpr int NMAIN = 128;

constexpr int SLOT = 8192;
constexpr int ZOFF = 14 * SLOT;
__host__ __device__ constexpr int slot(int s) { return ZOFF - s * SLOT; }
constexpr int BOFF = ZOFF + SLOT;
constexpr int AOFF = BOFF + 32768 + 128;
constexpr int COFF = AOFF + 65536 + 128;
constexpr int MOFF = COFF + 8192;
constexpr int BAR_FULL = MOFF, BAR_DONE = MOFF + 208, BAR_WC = MOFF + 416, BAR_TD1 = MOFF + 464,
              BAR_TD2 = MOFF + 472, BAR_FIN = MOFF + 480;
constexpr int W2OFF = MOFF + 512, PARTOFF = MOFF + 1024, TSOFF = MOFF + 1536;
constexpr int SMEM_BYTES = MOFF + 2816;
constexpr int XDELTA = 2 * SLOT;
__host__ __device__ constexpr int xpair(int i) {
    return (i % 5) == 0 ? slot(14) : (i % 5) == 1 ? slot(13) : (i % 5) == 2 ? slot(9)
         : (i % 5) == 3 ? BOFF : BOFF + SLOT;
}
__host__ __device__ constexpr int wl(int st) { return st == 0 ? 1 : st + 2; }
__host__ __device__ constexpr int wcslot(int c) {
    return c == 0 ? slot(12) : c == 1 ? slot(8) : c == 2 ? slot(4) : c == 3 ? slot(10) : c == 4 ? slot(5)
         : c == 5 ? slot(13) : c == 6 ? slot(11) : c == 7 ? slot(9) : c == 8 ? slot(7)
         : c == 9 ? slot(2) : c == 10 ? slot(1) : c == 11 ? slot(6) : c == 12 ? slot(3)
         : c == 13 ? slot(14) : c == 14 ? ZOFF : slot(12);
}
constexpr int SEOFF = slot(14);
constexpr int ZQOFF = SEOFF + 4096;

__device__ uint4 g_wc[2 * 16 * 8192 / 16];
__device__ uint4 g_se[3072 / 16];
__device__ unsigned g_ready;
__device__ unsigned g_seen;

__device__ __forceinline__ int jmap(int n) {
    int t = (n >> 1) & 3, m = 2 * (n >> 3) + (n & 1);
    return m < 6 ? 2 + 4 * m + t : (m == 6 && t < 2) ? t : -1;
}
__device__ __forceinline__ int imap(int c, int t, int u) {
    int p = 4 * c + t;
    return c < 3 ? 2 + 4 * (p >> 1) + (p & 1) + 2 * u : (t == 0 ? u : -1);
}

__device__ __forceinline__ uint64_t mkdesc(uint32_t addr, uint32_t lbo, uint32_t sbo, int sw) {
    return (uint64_t)((addr & 0x3ffff) >> 4) | ((uint64_t)(lbo >> 4) << 16) | ((uint64_t)(sbo >> 4) << 32) |
           ((uint64_t)sw << 62);
}
__device__ __forceinline__ void mbar_init(uint32_t b, uint32_t n) {
    asm volatile("mbarrier.init.shared.b64 [%0], %1;" ::"r"(b), "r"(n) : "memory");
}
__device__ __forceinline__ void mbar_wait(uint32_t b) {
    asm volatile(
        "{\n.reg .pred p, q;\n.reg .u32 n;\n"
        "mbarrier.try_wait.parity.shared.b64 p, [%0], 0;\n@p bra.uni WD%=;\nmov.u32 n, 0;\n"
        "WL%=:\nmbarrier.try_wait.parity.shared.b64 p, [%0], 0;\n@p bra.uni WD%=;\n"
        "add.u32 n, n, 1;\nsetp.lt.u32 q, n, 4000000;\n@q bra.uni WL%=;\nWD%=:\n}\n" ::"r"(b)
        : "memory");
}
__device__ __forceinline__ void mbar_arrive(uint32_t b) {
    asm volatile("mbarrier.arrive.shared.b64 _, [%0];" ::"r"(b) : "memory");
}
__device__ __forceinline__ void mbar_expect(uint32_t b, uint32_t bytes) {
    asm volatile("mbarrier.arrive.expect_tx.shared.b64 _, [%0], %1;" ::"r"(b), "r"(bytes) : "memory");
}
__device__ __forceinline__ bool elect() {
    uint32_t p;
    asm volatile("{.reg .pred q; elect.sync _|q, 0xffffffff; selp.u32 %0, 1, 0, q;}" : "=r"(p));
    return p;
}
__device__ __forceinline__ void tma2d(uint32_t dst, const CUtensorMap* m, uint32_t bar, int x, int y) {
    asm volatile(
        "cp.async.bulk.tensor.2d.shared::cluster.global.mbarrier::complete_tx::bytes [%0], [%1, {%3, %4}], [%2];" ::"r"(dst),
        "l"(m), "r"(bar), "r"(x), "r"(y)
        : "memory");
}
__device__ __forceinline__ void bulk(uint32_t dst, const void* src, uint32_t bytes, uint32_t bar) {
    asm volatile("cp.async.bulk.shared::cluster.global.mbarrier::complete_tx::bytes [%0], [%1], %2, [%3];" ::"r"(dst),
                 "l"(src), "r"(bytes), "r"(bar)
                 : "memory");
}
__device__ __forceinline__ void cp16(uint32_t dst, const void* src) {
    asm volatile("cp.async.cg.shared.global [%0], [%1], 16;" ::"r"(dst), "l"(src) : "memory");
}
__device__ __forceinline__ void lds128(uint32_t (&v)[4], uint32_t a) {
    asm volatile("ld.shared.v4.u32 {%0,%1,%2,%3}, [%4];" : "=r"(v[0]), "=r"(v[1]), "=r"(v[2]), "=r"(v[3]) : "r"(a) : "memory");
}
__device__ __forceinline__ void lds128_if(uint32_t (&v)[4], uint32_t a, uint32_t p) {
    asm volatile("{.reg .pred q; setp.ne.u32 q, %5, 0; @q ld.shared.v4.u32 {%0,%1,%2,%3}, [%4];}"
                 : "+r"(v[0]), "+r"(v[1]), "+r"(v[2]), "+r"(v[3])
                 : "r"(a), "r"(p)
                 : "memory");
}
__device__ __forceinline__ void lds64(uint32_t& x, uint32_t& y, uint32_t a) {
    asm volatile("ld.shared.v2.u32 {%0,%1}, [%2];" : "=r"(x), "=r"(y) : "r"(a) : "memory");
}
__device__ __forceinline__ void sts128(uint32_t a, uint32_t x, uint32_t y, uint32_t z, uint32_t w) {
    asm volatile("st.shared.v4.u32 [%0], {%1,%2,%3,%4};" ::"r"(a), "r"(x), "r"(y), "r"(z), "r"(w) : "memory");
}
__device__ __forceinline__ void sts64(uint32_t a, uint32_t x, uint32_t y) {
    asm volatile("st.shared.v2.u32 [%0], {%1,%2};" ::"r"(a), "r"(x), "r"(y) : "memory");
}
__device__ __forceinline__ uint32_t pack(float lo, float hi) {
    uint32_t r;
    asm volatile("cvt.rn.bf16x2.f32 %0, %1, %2;" : "=r"(r) : "f"(hi), "f"(lo));
    return r;
}
__device__ __forceinline__ uint32_t hmul2(uint32_t a, uint32_t b) {
    uint32_t r;
    asm volatile("mul.rn.bf16x2 %0, %1, %2;" : "=r"(r) : "r"(a), "r"(b));
    return r;
}
__device__ __forceinline__ uint32_t hfma2(uint32_t a, uint32_t b, uint32_t c) {
    uint32_t r;
    asm volatile("fma.rn.bf16x2 %0, %1, %2, %3;" : "=r"(r) : "r"(a), "r"(b), "r"(c));
    return r;
}
__device__ __forceinline__ float ffma(float a, float b, float c) {
    float r;
    asm volatile("fma.rn.f32 %0, %1, %2, %3;" : "=f"(r) : "f"(a), "f"(b), "f"(c));
    return r;
}
__device__ __forceinline__ float tanh_fast(float x) {
    float r;
    asm("tanh.approx.f32 %0, %1;" : "=f"(r) : "f"(x));
    return r;
}
__device__ __forceinline__ float gelu_tanh(float x) {
    return tanh_fast(x * fmaf(x * x, 0.7978845608028654f * 0.044715f, 0.7978845608028654f));
}
#define WG_FENCE() asm volatile("wgmma.fence.sync.aligned;" ::: "memory")
#define WG_COMMIT() asm volatile("wgmma.commit_group.sync.aligned;" ::: "memory")
#define WG_WAIT0() asm volatile("wgmma.wait_group.sync.aligned 0;" ::: "memory")
#define PROXY_FENCE() asm volatile("fence.proxy.async.shared::cta;" ::: "memory")
template <int N>
__device__ __forceinline__ void pin(float (&d)[N]) {
#pragma unroll
    for (int i = 0; i < N; i++) asm volatile("" : "+f"(d[i])::"memory");
}
#define TS(k)

__device__ __forceinline__ void wgmma_ss_n168_acc(float (&d)[84], uint64_t da, uint64_t db) {
    asm volatile(
        "wgmma.mma_async.sync.aligned.m64n168k16.f32.bf16.bf16 "
        "{%0,%1,%2,%3,%4,%5,%6,%7,%8,%9,%10,%11,%12,%13,%14,%15,"
        "%16,%17,%18,%19,%20,%21,%22,%23,%24,%25,%26,%27,%28,%29,%30,%31,"
        "%32,%33,%34,%35,%36,%37,%38,%39,%40,%41,%42,%43,%44,%45,%46,%47,"
        "%48,%49,%50,%51,%52,%53,%54,%55,%56,%57,%58,%59,%60,%61,%62,%63,"
        "%64,%65,%66,%67,%68,%69,%70,%71,%72,%73,%74,%75,%76,%77,%78,%79,"
        "%80,%81,%82,%83}, "
        "%84, %85, 1, 1, 1, 0, 1;"
        : "+f"(d[0]), "+f"(d[1]), "+f"(d[2]), "+f"(d[3]), "+f"(d[4]), "+f"(d[5]), "+f"(d[6]), "+f"(d[7]),
          "+f"(d[8]), "+f"(d[9]), "+f"(d[10]), "+f"(d[11]), "+f"(d[12]), "+f"(d[13]), "+f"(d[14]), "+f"(d[15]),
          "+f"(d[16]), "+f"(d[17]), "+f"(d[18]), "+f"(d[19]), "+f"(d[20]), "+f"(d[21]), "+f"(d[22]), "+f"(d[23]),
          "+f"(d[24]), "+f"(d[25]), "+f"(d[26]), "+f"(d[27]), "+f"(d[28]), "+f"(d[29]), "+f"(d[30]), "+f"(d[31]),
          "+f"(d[32]), "+f"(d[33]), "+f"(d[34]), "+f"(d[35]), "+f"(d[36]), "+f"(d[37]), "+f"(d[38]), "+f"(d[39]),
          "+f"(d[40]), "+f"(d[41]), "+f"(d[42]), "+f"(d[43]), "+f"(d[44]), "+f"(d[45]), "+f"(d[46]), "+f"(d[47]),
          "+f"(d[48]), "+f"(d[49]), "+f"(d[50]), "+f"(d[51]), "+f"(d[52]), "+f"(d[53]), "+f"(d[54]), "+f"(d[55]),
          "+f"(d[56]), "+f"(d[57]), "+f"(d[58]), "+f"(d[59]), "+f"(d[60]), "+f"(d[61]), "+f"(d[62]), "+f"(d[63]),
          "+f"(d[64]), "+f"(d[65]), "+f"(d[66]), "+f"(d[67]), "+f"(d[68]), "+f"(d[69]), "+f"(d[70]), "+f"(d[71]),
          "+f"(d[72]), "+f"(d[73]), "+f"(d[74]), "+f"(d[75]), "+f"(d[76]), "+f"(d[77]), "+f"(d[78]), "+f"(d[79]),
          "+f"(d[80]), "+f"(d[81]), "+f"(d[82]), "+f"(d[83])
        : "l"(da), "l"(db));
}

__device__ __forceinline__ void wgmma_rs_n32_set(float (&d)[16], const uint32_t (&a)[4], uint64_t db) {
    asm volatile(
        "wgmma.mma_async.sync.aligned.m64n32k16.f32.bf16.bf16 "
        "{%0,%1,%2,%3,%4,%5,%6,%7,%8,%9,%10,%11,%12,%13,%14,%15}, "
        "{%16,%17,%18,%19}, %20, 0, 1, 1, 0;"
        : "=f"(d[0]), "=f"(d[1]), "=f"(d[2]), "=f"(d[3]), "=f"(d[4]), "=f"(d[5]), "=f"(d[6]), "=f"(d[7]),
          "=f"(d[8]), "=f"(d[9]), "=f"(d[10]), "=f"(d[11]), "=f"(d[12]), "=f"(d[13]), "=f"(d[14]), "=f"(d[15])
        : "r"(a[0]), "r"(a[1]), "r"(a[2]), "r"(a[3]), "l"(db));
}

__device__ __forceinline__ void wgmma_rs_n32_acc(float (&d)[16], const uint32_t (&a)[4], uint64_t db) {
    asm volatile(
        "wgmma.mma_async.sync.aligned.m64n32k16.f32.bf16.bf16 "
        "{%0,%1,%2,%3,%4,%5,%6,%7,%8,%9,%10,%11,%12,%13,%14,%15}, "
        "{%16,%17,%18,%19}, %20, 1, 1, 1, 0;"
        : "+f"(d[0]), "+f"(d[1]), "+f"(d[2]), "+f"(d[3]), "+f"(d[4]), "+f"(d[5]), "+f"(d[6]), "+f"(d[7]),
          "+f"(d[8]), "+f"(d[9]), "+f"(d[10]), "+f"(d[11]), "+f"(d[12]), "+f"(d[13]), "+f"(d[14]), "+f"(d[15])
        : "r"(a[0]), "r"(a[1]), "r"(a[2]), "r"(a[3]), "l"(db));
}

__device__ __forceinline__ void wgmma_rs_n16_set(float (&d)[8], const uint32_t (&a)[4], uint64_t db) {
    asm volatile(
        "wgmma.mma_async.sync.aligned.m64n16k16.f32.bf16.bf16 "
        "{%0,%1,%2,%3,%4,%5,%6,%7}, "
        "{%8,%9,%10,%11}, %12, 0, 1, 1, 0;"
        : "=f"(d[0]), "=f"(d[1]), "=f"(d[2]), "=f"(d[3]), "=f"(d[4]), "=f"(d[5]), "=f"(d[6]), "=f"(d[7])
        : "r"(a[0]), "r"(a[1]), "r"(a[2]), "r"(a[3]), "l"(db));
}

__device__ __forceinline__ void wgmma_rs_n16_acc(float (&d)[8], const uint32_t (&a)[4], uint64_t db) {
    asm volatile(
        "wgmma.mma_async.sync.aligned.m64n16k16.f32.bf16.bf16 "
        "{%0,%1,%2,%3,%4,%5,%6,%7}, "
        "{%8,%9,%10,%11}, %12, 1, 1, 1, 0;"
        : "+f"(d[0]), "+f"(d[1]), "+f"(d[2]), "+f"(d[3]), "+f"(d[4]), "+f"(d[5]), "+f"(d[6]), "+f"(d[7])
        : "r"(a[0]), "r"(a[1]), "r"(a[2]), "r"(a[3]), "l"(db));
}

__device__ __forceinline__ void wgmma_rs_n32_pred(float (&d)[16], const uint32_t (&a)[4], uint64_t db, uint32_t scale_d) {
    asm volatile(
        "{.reg .pred p; setp.ne.u32 p, %21, 0; wgmma.mma_async.sync.aligned.m64n32k16.f32.bf16.bf16 "
        "{%0,%1,%2,%3,%4,%5,%6,%7,%8,%9,%10,%11,%12,%13,%14,%15}, "
        "{%16,%17,%18,%19}, %20, p, 1, 1, 0;}"
        : "+f"(d[0]), "+f"(d[1]), "+f"(d[2]), "+f"(d[3]), "+f"(d[4]), "+f"(d[5]), "+f"(d[6]), "+f"(d[7]),
          "+f"(d[8]), "+f"(d[9]), "+f"(d[10]), "+f"(d[11]), "+f"(d[12]), "+f"(d[13]), "+f"(d[14]), "+f"(d[15])
        : "r"(a[0]), "r"(a[1]), "r"(a[2]), "r"(a[3]), "l"(db), "r"(scale_d));
}

__device__ __forceinline__ void prep_cta(uint32_t sb, int c, const __nv_bfloat16* __restrict__ wc,
                                         const __nv_bfloat16* __restrict__ se1, const __nv_bfloat16* __restrict__ se2) {
    const int tid = threadIdx.x, lane = tid & 31, warp = tid >> 5;
    constexpr int NROW = 2 * NF * NF;
    for (int q = tid; q < NROW * 2; q += 384) cp16(sb + q * 16, wc + (q >> 1) * ND + c * 16 + (q & 1) * 8);
    if (tid == 0) sts128(sb + NROW * 32, 0, 0, 0, 0);
    if (c == 0) {
        unsigned short* dst = reinterpret_cast<unsigned short*>(g_se);
        for (int q = tid; q < 1536; q += 384) {
            const int n = (q >> 5) - (q < 512 ? 0 : 16), k = q & 31, kk = k & 15;
            float v = 0.f;
            if (q < 512) {
                const int mm = kk >> 1, u = kk & 1, ww = k >> 4;
                const int f = mm < 6 ? 2 + 4 * mm + ww + 2 * u : (mm == 6 && u == 0) ? ww : -1;
                if (f >= 0 && n < NR) v = __bfloat162float(se1[f * NR + n]);
            } else {
                const int f = k < 16 ? jmap(n) : imap(n >> 3, (n >> 1) & 3, n & 1);
                if (f >= 0 && kk < NR) v = 0.5f * __bfloat162float(se2[kk * NF + f]);
            }
            dst[(q >> 5) * 32 + (((k >> 3) ^ ((n >> 1) & 3)) << 3) + (k & 7)] = __bfloat16_as_ushort(__float2bfloat16(v));
        }
    }
    asm volatile("cp.async.wait_all;" ::: "memory");
    __syncthreads();
    const int i = imap((lane & 7) >> 1, lane >> 3, lane & 1);
    const int g = lane >> 2, t = lane & 3;
    for (int task = warp; task < 128; task += 12) {
        const int eg = task & 1, n = (task >> 1) & 31, s = task >> 6;
        const int j = jmap(n);
        const uint32_t a = (i >= 0 && j >= 0) ? sb + ((s * NF + i) * NF + j) * 32 + eg * 16 : sb + NROW * 32;
        uint4 v;
        asm volatile("ldmatrix.sync.aligned.m8n8.x4.trans.shared.b16 {%0,%1,%2,%3}, [%4];"
                     : "=r"(v.x), "=r"(v.y), "=r"(v.z), "=r"(v.w)
                     : "r"(a));
        const int e = eg * 8 + g;
        const int ch = (t < 2 ? t ^ ((e >> 1) & 1) : t) ^ ((n >> 1) & 3);
        g_wc[(c >> 1) * 8192 + e * 512 + (c & 1) * 256 + s * 128 + n * 4 + ch] = v;
    }
    __threadfence();
    __syncthreads();
    if (tid == 0) atomicAdd(&g_ready, 1u);
}

#define PACE 250

__global__ void __cluster_dims__(2, 1, 1) __launch_bounds__(384, 1)
fibinet_kernel(const __grid_constant__ CUtensorMap tm_w1, const int* __restrict__ idx, const uint4* __restrict__ table,
               const __nv_bfloat16* __restrict__ se1, const __nv_bfloat16* __restrict__ se2,
               const __nv_bfloat16* __restrict__ wbi, const __nv_bfloat16* __restrict__ wc,
               const __nv_bfloat16* __restrict__ w2, __nv_bfloat16* __restrict__ out) {
    extern __shared__ __align__(1024) unsigned char smem[];
    const int tid = threadIdx.x;
    const uint32_t sb = (uint32_t)__cvta_generic_to_shared(smem);
    if (blockIdx.x < NPREP) {
        prep_cta(sb, blockIdx.x, wc, se1, se2);
        return;
    }
    const int grp = (blockIdx.x - NPREP) >> 1, rank = blockIdx.x & 1;
    const int warp = __shfl_sync(0xffffffffu, tid >> 5, 0);
    const int w = warp >> 2;

    int myidx[13];
    if (w == 2) {
        const int* ip = idx + (grp * 64 + ((tid & 127) >> 3) + 16 * (tid & 3)) * NF + ((tid >> 2) & 1);
#pragma unroll
        for (int k = 0; k < 13; k++) myidx[k] = __ldg(ip + 2 * k);
    } else if (elect()) {
#pragma unroll
        for (int k = 0; k < 8; k++) {
            const int b = warp * 8 + k;
            const uint32_t cnt = b < 26 ? 129u : b < 52 ? 4u : (b == 58 || b == 59) ? 8u : 1u;
            mbar_init(sb + MOFF + b * 8, cnt);
        }
        asm volatile("fence.mbarrier_init.release.cluster;" ::: "memory");
    }
    __syncthreads();
    asm volatile("barrier.cluster.arrive.relaxed.aligned;" ::: "memory");

    if (w == 2) {
        asm volatile("setmaxnreg.dec.sync.aligned.u32 40;");
        const int q = (tid & 127) >> 3, sub = tid & 7;
        const uint32_t dst0 = sb + q * 128 + ((sub ^ (q & 7)) << 4);
        const uint32_t dst1 = (dst0 ^ 64) + XDELTA;
        const uint4* tp = table + sub;
        auto gather = [&](int f) {
#pragma unroll
            for (int u = 0; u < 4; u++) {
                const uint32_t id = __shfl_sync(0xffffffffu, myidx[f >> 1], ((f & 1) << 2) + u, 8);
                asm volatile("{.reg .u64 a; mad.wide.u32 a, %2, 128, %1; cp.async.cg.shared.global [%0], [a], 16;}" ::"r"(
                                 ((f & 1) ? dst1 : dst0) + xpair(f >> 1) + u * 2048),
                             "l"(tp), "r"(id)
                             : "memory");
            }
            asm volatile("cp.async.mbarrier.arrive.noinc.shared.b64 [%0];" ::"r"(sb + BAR_FULL + f * 8) : "memory");
        };
        gather(0);
        TS(60);
        gather(1);
        {
            uint32_t c0;
            asm volatile("mov.u32 %0, %%clock;" : "=r"(c0)::"memory");
#pragma unroll
            for (int f = 2; f < 10; f++) {
                uint32_t c;
                do {
                    asm volatile("mov.u32 %0, %%clock;" : "=r"(c)::"memory");
                } while (c - c0 < (uint32_t)((f - 1) * PACE));
                gather(f);
            }
        }
        const bool lead = warp == 8;
#pragma unroll
        for (int f = 0; f < 22; f++) {
            if (f < 16 || lead) mbar_wait(sb + BAR_DONE + f * 8);
            if (lead && elect()) {
                const int fn = f + 4, L = wl(fn & 3);
                mbar_expect(sb + BAR_FULL + fn * 8, 16384);
                tma2d(sb + slot(2 * L), &tm_w1, sb + BAR_FULL + fn * 8, 128 * rank + 64 * (fn & 1), fn * 64);
                tma2d(sb + slot(L), &tm_w1, sb + BAR_FULL + fn * 8, 128 * rank + 64 - 64 * (fn & 1), fn * 64);
            }
            if ((f & 1) && f < 16) {
                gather(f + 9);
                gather(f + 10);
            }
            if (f == 16 && lead && elect()) {
                unsigned v, it = 0;
                do {
                    asm volatile("ld.acquire.gpu.global.u32 %0, [%1];" : "=r"(v) : "l"(&g_ready) : "memory");
                    if (++it > 4000000u) __trap();
                } while (v < NPREP);
                asm volatile("fence.proxy.async.global;" ::: "memory");
                if (atomicAdd(&g_seen, 1u) == NMAIN - 1) {
                    g_seen = 0;
                    g_ready = 0;
                }
            }
        }
        asm volatile("cp.async.wait_all;" ::: "memory");
        asm volatile("barrier.cluster.wait.aligned;" ::: "memory");
        if (lead) {
            const unsigned char* src = reinterpret_cast<const unsigned char*>(g_wc) + rank * 131072;
            if (elect()) {
                mbar_expect(sb + BAR_FIN, 512);
                mbar_expect(sb + BAR_WC, 3072 + 8192);
                bulk(sb + SEOFF, g_se, 3072, sb + BAR_WC);
                bulk(sb + wcslot(0), src, 8192, sb + BAR_WC);
            }
#pragma unroll
            for (int gi = 1; gi < 6; gi++) {
                const int c0 = gi == 1 ? 1 : gi == 2 ? 3 : gi == 3 ? 5 : gi == 4 ? 9 : 13;
                const int c1 = gi == 1 ? 3 : gi == 2 ? 5 : gi == 3 ? 9 : gi == 4 ? 13 : 16;
                if (gi < 5) mbar_wait(sb + (gi == 1 ? BAR_DONE + 22 * 8 : gi == 2 ? BAR_DONE + 23 * 8 : gi == 3 ? BAR_TD1 : BAR_TD2));
                if (elect()) {
                    mbar_expect(sb + BAR_WC + gi * 8, (c1 - c0) * 8192);
#pragma unroll
                    for (int c = c0; c < c1; c++) bulk(sb + wcslot(c), src + c * 8192, 8192, sb + BAR_WC + gi * 8);
                }
            }
            mbar_wait(sb + BAR_FIN);
            const float* part = reinterpret_cast<const float*>(smem + PARTOFF) + (tid & 31);
            out[grp * 64 + rank * 32 + (tid & 31)] = __float2bfloat16(part[0] + part[32] + part[64] + part[96]);
        }
    } else {
        asm volatile("setmaxnreg.inc.sync.aligned.u32 232;");
        const int lane = tid & 31, g = lane >> 2, t = lane & 3, wq = warp & 3, t128 = tid & 127;
        if (elect()) {
            const int f = warp >> 1, at = warp & 1, L = f == 0 ? 1 : f + 2;
            if (at == 0) mbar_expect(sb + BAR_FULL + f * 8, 16384);
            tma2d(sb + ZOFF - (2 - at) * L * SLOT, &tm_w1, sb + BAR_FULL + f * 8, 128 * rank + 64 * ((f ^ at) & 1), f * 64);
        }
        {
            const int d = tid >> 2;
            cp16(sb + ZOFF + d * 128 + ((t ^ (d & 7)) << 4), wbi + d * ND + 32 * rank + 8 * t);
            if (t == 0) sts128(sb + ZOFF + d * 128 + ((4 ^ (d & 7)) << 4), 0x3c803c80u, 0x3c803c80u, 0x3c803c80u, 0x3c803c80u);
            if (tid < 128) {
                const int h = 128 * rank + (tid & 64) + 8 * ((tid >> 1) & 7) + 2 * ((tid >> 4) & 3) + (tid & 1);
                reinterpret_cast<float*>(smem + W2OFF)[tid] = 0.5f * __bfloat162float(w2[h]);
            }
            asm volatile("cp.async.wait_all;" ::: "memory");
            PROXY_FENCE();
            asm volatile("bar.sync 1, 256;" ::: "memory");
        }

        float acc[84];
#pragma unroll
        for (int k = 0; k < 84; k++) asm volatile("mov.b32 %0, 0;" : "=f"(acc[k]));
        float sv[18];
        uint32_t X[14][2][4];
        uint32_t zq[4] = {0, 0, 0, 0};
        const uint64_t dA = mkdesc(sb + w * XDELTA, 16, 1024, 1);
        const uint64_t dB0 = mkdesc(sb + ZOFF - 2 * (w ? 3 : 1) * SLOT, (w ? 3 : 1) * SLOT, 1024, 1);
        const uint64_t dB1 = mkdesc(sb + ZOFF - 2 * (4 + w) * SLOT, (4 + w) * SLOT, 1024, 1);
        const uint32_t xl0 = sb + (t & 1) * XDELTA + (16 * wq + g) * 128 + (((4 * rank + 2 * w) ^ (4 * (t & 1)) ^ g) << 4);
        const uint32_t xl1 = xl0 ^ 16;
        const uint32_t hi_half = t >> 1;
        auto lift = [&](int i) {
            const int m = i == 0 ? 6 : (i - 1) >> 1;
#pragma unroll
            for (int r = 0; r < 2; r++)
#pragma unroll
                for (int cc = 0; cc < 2; cc++) {
                    const uint32_t a = (cc ? xl1 : xl0) + xpair(i) + r * 1024;
                    if (i == 0) lds128(X[2 * m + r][cc], a);
                    else lds128_if(X[2 * m + r][cc], a, (i & 1) ? hi_half ^ 1 : hi_half);
                }
        };
        auto store_pair = [&](int m) {
            uint32_t a;
            if (m < 4)
                a = sb + AOFF + t * 4096 + (t >> 1) * 16 + (wq * 32 + g * 4 + w) * 16 +
                    ((((g & 2) << 4) | ((t & 1) << 3)) ^ (((m & 1) << 5) | ((m >> 1) << 3)));
            else
                a = sb + BOFF + t * 2048 + t * 8 + (wq * 32 + g * 4 + 2 * (m & 1) + w) * 8;
#pragma unroll
            for (int n = 0; n < 4; n++)
#pragma unroll
                for (int u = 0; u < 2; u++)
                    sts64(a + (m < 4 ? (8 * n + u) * 2048 + n * 32 : (8 * n + u) * 1024 + n * 32),
                          pack(sv[4 * n + u], acc[64 + 4 * n + u]), pack(sv[4 * n + 2 + u], acc[64 + 4 * n + 2 + u]));
        };
        auto z_pair = [&](int m, float a0, float a1, float b0, float b1) {
            if (t == (m & 3)) {
                zq[2 * (m >> 2)] = pack(a0, b0);
                zq[2 * (m >> 2) + 1] = pack(a1, b1);
            }
        };

#pragma unroll
        for (int i = 0; i < 13; i++) {
            mbar_wait(sb + BAR_FULL + (2 * i + w) * 8);
            PROXY_FENCE();
            TS(2 * i + w);
            const uint64_t da = dA + (xpair(i) >> 4), db = ((i & 1) ? dB1 : dB0);
            WG_FENCE();
            wgmma_ss_n168_acc(acc, da, db + w * 256);
            wgmma_ss_n168_acc(acc, da + 2, db + w * 256 + 128);
            wgmma_ss_n168_acc(acc, da + 4, db + (w ^ 1) * 256);
            wgmma_ss_n168_acc(acc, da + 6, db + (w ^ 1) * 256 + 128);
            WG_COMMIT();
            mbar_wait(sb + BAR_FULL + (2 * i + (w ^ 1)) * 8);
            if (i < 11) {
                if (i & 1) {
#pragma unroll
                    for (int k = 0; k < 16; k++) X[(i - 1) + (k >> 3)][(k >> 2) & 1][k & 3] = 0;
                }
                lift(i);
            }
            if (i == 10 || i == 12) {
                mbar_wait(sb + BAR_DONE + (i == 10 ? 18 : 20) * 8);
                mbar_wait(sb + BAR_DONE + (i == 10 ? 19 : 21) * 8);
            }
            WG_WAIT0();
            pin(acc);
            if (lane == 0) mbar_arrive(sb + BAR_DONE + (2 * i + w) * 8);
            if (i == 0) {
                const uint32_t a = sb + COFF + t * 512 + (wq * 8 + g) * 8 + w * 2;
#pragma unroll
                for (int k = 0; k < 16; k++) {
                    const uint32_t v = pack(acc[64 + k], 0.f);
                    asm volatile("st.shared.u16 [%0], %1;" ::"r"(a + ((k >> 2) * 8 + (k & 1)) * 256 + ((k >> 1) & 1) * 4),
                                 "h"((unsigned short)v)
                                 : "memory");
                }
                z_pair(6, acc[80], acc[82], 0.f, 0.f);
            } else if (i & 1) {
#pragma unroll
                for (int k = 0; k < 18; k++)
                    asm volatile("mov.b32 %0, %1;" : "=f"(sv[k]) : "f"(acc[k < 17 ? 64 + k : 82]));
            } else {
                z_pair((i - 1) >> 1, sv[16], sv[17], acc[80], acc[82]);
                if (i < 12) store_pair((i - 1) >> 1);
            }
            if (i < 12) {
#pragma unroll
                for (int k = 64; k < 84; k++) asm volatile("mov.b32 %0, 0;" : "+f"(acc[k]));
            }
        }
        TS(26 + w);

        sts128(sb + ZQOFF + w * 2048 + t128 * 16, zq[0], zq[1], zq[2], zq[3]);
        mbar_wait(sb + BAR_DONE + (24 + w) * 8);
        {
            const uint32_t L = (w ? 3 : 1) * SLOT, a = sb + ZOFF - 2 * L + t128 * 16;
#pragma unroll
            for (int k = 0; k < 8; k++)
                sts128(a + (k >> 2) * L + (k & 3) * 2048, __float_as_uint(acc[32 + 4 * k]), __float_as_uint(acc[33 + 4 * k]),
                       __float_as_uint(acc[34 + 4 * k]), __float_as_uint(acc[35 + 4 * k]));
        }
        mbar_wait(sb + BAR_WC);
        asm volatile("bar.sync 1, 256;" ::: "memory");
        TS(28 + w);
        float aj[14];
        uint32_t ai[8];
        float sum0 = 0.f, sum1 = 0.f;
        {
            const uint64_t dS = mkdesc(sb + SEOFF, 16, 512, 2);
            uint32_t zo[4];
            lds128(zo, sb + ZQOFF + (w ^ 1) * 2048 + t128 * 16);
            float s1[8];
            WG_FENCE();
            wgmma_rs_n16_set(s1, zq, dS + w * 2);
            wgmma_rs_n16_acc(s1, zo, dS + (w ^ 1) * 2);
            WG_COMMIT();
            store_pair(5);
#pragma unroll
            for (int k = 0; k < 16; k++) X[10 + (k >> 3)][(k >> 2) & 1][k & 3] = 0;
            lift(11);
            lift(12);
            __syncwarp();
            if (lane == 0) mbar_arrive(sb + BAR_TD1);
            WG_WAIT0();
            pin(s1);
            uint32_t gq[4];
#pragma unroll
            for (int k = 0; k < 4; k++) {
                const float x0 = s1[2 * k], x1 = s1[2 * k + 1];
                gq[k] = pack(x0 * fmaf(gelu_tanh(x0), 0.5f, 0.5f), x1 * fmaf(gelu_tanh(x1), 0.5f, 0.5f));
            }
            float sj[16], si[16];
            WG_FENCE();
            wgmma_rs_n32_set(sj, gq, dS + 64);
            wgmma_rs_n32_set(si, gq, dS + 66);
            WG_COMMIT();
            const uint32_t L = (w ? 1 : 3) * SLOT, a = sb + ZOFF - 2 * L + t128 * 16;
#pragma unroll
            for (int k2 = 0; k2 < 4; k2++) {
                uint32_t hw[4], o0[4], o1[4];
                lds128(hw, sb + W2OFF + (w * 64 + t * 16 + k2 * 4) * 4);
                lds128(o0, a + (k2 >> 1) * L + ((2 * k2) & 3) * 2048);
                lds128(o1, a + (k2 >> 1) * L + ((2 * k2 + 1) & 3) * 2048);
#pragma unroll
                for (int k = 0; k < 8; k++) {
                    const float x = acc[8 * k2 + k] + __uint_as_float(k < 4 ? o0[k & 3] : o1[k & 3]);
                    const float h = __uint_as_float(hw[2 * (k >> 2) + (k & 1)]);
                    const float y = fmaf(gelu_tanh(x), h, h);
                    if (k & 2) sum1 = fmaf(x, y, sum1);
                    else sum0 = fmaf(x, y, sum0);
                }
            }
            WG_WAIT0();
            pin(sj);
            pin(si);
#pragma unroll
            for (int q = 0; q < 14; q++) aj[q] = fmaf(tanh_fast(sj[4 * (q >> 2) + 2 * (q & 1) + ((q >> 1) & 1)]), 0.5f, 0.5f);
#pragma unroll
            for (int k = 0; k < 8; k++)
                ai[k] = pack(fmaf(tanh_fast(si[2 * k]), 0.5f, 0.5f), fmaf(tanh_fast(si[2 * k + 1]), 0.5f, 0.5f));
        }
        asm volatile("bar.sync 1, 256;" ::: "memory");
        TS(30 + w);

        {
            const uint32_t la = sb + AOFF + w * (16 * 2048 + 64) + (wq * 32 + g * 4 + (t ^ (g & 2))) * 16;
            const uint32_t lb = sb + BOFF + w * (16 * 1024 + 64) + t128 * 8;
            const uint32_t lc = sb + COFF + w * (16 * 256) + (wq * 8 + g) * 8;
            const uint64_t dW = mkdesc(sb + w * 4096, 16, 512, 2);
            uint32_t Ap[2][2][4], Aq[2][4], hacc[4];
            float Sp[16], Sq[16], U[14];
            auto load_a = [&](int e) {
                lds128(Ap[e & 1][0], la + e * 2048 + (e >> 2) * 16);
                lds64(Ap[e & 1][1][0], Ap[e & 1][1][1], lb + e * 1024 + (e >> 1) * 8);
                lds64(Ap[e & 1][1][2], Ap[e & 1][1][3], lc + e * 256);
            };
            load_a(0);
#pragma unroll
            for (int e = 0; e < 16; e++) {
                if (e & 1) mbar_wait(sb + BAR_WC + (e == 1 ? 1 : e == 3 ? 2 : e < 9 ? 3 : e < 13 ? 4 : 5) * 8);
#pragma unroll
                for (int k = 0; k < 8; k++) Aq[k >> 2][k & 3] = hmul2(Ap[e & 1][k >> 2][k & 3], ai[k < 4 ? k ^ (e & 2) : k]);
                const uint64_t d = dW + (wcslot(e) >> 4);
                WG_FENCE();
                if (e == 0) wgmma_rs_n32_set(Sp, Ap[e & 1][0], d);
                else wgmma_rs_n32_pred(Sp, Ap[e & 1][0], d, blockIdx.y);
                wgmma_rs_n32_acc(Sp, Ap[e & 1][1], d + 2);
                if (e == 0) wgmma_rs_n32_set(Sq, Aq[0], d + 128);
                else wgmma_rs_n32_pred(Sq, Aq[0], d + 128, blockIdx.y);
                wgmma_rs_n32_acc(Sq, Aq[1], d + 130);
                WG_COMMIT();
                if (e + 1 < 16) load_a(e + 1);
                WG_WAIT0();
                pin(Sp);
                pin(Sq);
                if (e == 0 && lane == 0) mbar_arrive(sb + BAR_TD2);
#pragma unroll
                for (int q = 0; q < 14; q++) {
                    const int ix = 4 * (q >> 2) + 2 * (q & 1) + ((q >> 1) & 1);
                    const float u = ffma(aj[q], Sq[ix], Sp[ix]);
                    if (!(e & 1)) {
                        U[q] = u;
                    } else {
                        const uint32_t x = X[q][e >> 3][(e & 7) >> 1];
                        if ((e & 7) == 1 && q < 4) hacc[q] = hmul2(pack(U[q], u), x);
                        else hacc[q & 3] = hfma2(pack(U[q], u), x, hacc[q & 3]);
                    }
                }
                if ((e & 7) == 7) {
                    sum0 += (__uint_as_float(hacc[0] << 16) + __uint_as_float(hacc[0] & 0xffff0000u)) +
                            (__uint_as_float(hacc[2] << 16) + __uint_as_float(hacc[2] & 0xffff0000u));
                    sum1 += (__uint_as_float(hacc[1] << 16) + __uint_as_float(hacc[1] & 0xffff0000u)) +
                            (__uint_as_float(hacc[3] << 16) + __uint_as_float(hacc[3] & 0xffff0000u));
                }
                if (e == 7) TS(32 + w);
            }
        }
        TS(34 + w);
        {
            float v = (t & 1) ? sum1 : sum0;
            v += __shfl_xor_sync(0xffffffffu, (t & 1) ? sum0 : sum1, 1);
            v += __shfl_xor_sync(0xffffffffu, v, 2);
            asm volatile("barrier.cluster.wait.aligned;" ::: "memory");
            if (t < 2) {
                uint32_t ra, rb;
                asm("mapa.shared::cluster.u32 %0, %1, %2;"
                    : "=r"(ra)
                    : "r"(sb + PARTOFF + ((2 * rank + w) * 32 + (wq & 1) * 16 + t * 8 + g) * 4), "r"(wq >> 1));
                asm("mapa.shared::cluster.u32 %0, %1, %2;" : "=r"(rb) : "r"(sb + BAR_FIN), "r"(wq >> 1));
                asm volatile("st.async.shared::cluster.mbarrier::complete_tx::bytes.f32 [%0], %1, [%2];" ::"r"(ra), "f"(v), "r"(rb)
                             : "memory");
            }
        }
    }
}

typedef CUresult (*EncodeFn)(CUtensorMap*, CUtensorMapDataType, cuuint32_t, void*, const cuuint64_t*, const cuuint64_t*,
                             const cuuint32_t*, const cuuint32_t*, CUtensorMapInterleave, CUtensorMapSwizzle,
                             CUtensorMapL2promotion, CUtensorMapFloatOOBfill);

}

extern "C" void kernel_launch(void* const* d_in, const int* in_sizes, int n_in, void* d_out, int out_size) {
    static EncodeFn encode = nullptr;
    if (!encode) {
        void* fn = nullptr;
        cudaDriverEntryPointQueryResult qr;
        cudaGetDriverEntryPoint("cuTensorMapEncodeTiled", &fn, cudaEnableDefault, &qr);
        encode = (EncodeFn)fn;
        cudaFuncSetAttribute(fibinet_kernel, cudaFuncAttributeMaxDynamicSharedMemorySize, SMEM_BYTES);
    }
    CUtensorMap tm;
    const cuuint64_t gd[2] = {NH, NF * ND};
    const cuuint64_t gs[1] = {NH * 2};
    const cuuint32_t bd[2] = {64, 64}, es[2] = {1, 1};
    encode(&tm, CU_TENSOR_MAP_DATA_TYPE_BFLOAT16, 2, d_in[6], gd, gs, bd, es, CU_TENSOR_MAP_INTERLEAVE_NONE,
           CU_TENSOR_MAP_SWIZZLE_128B, CU_TENSOR_MAP_L2_PROMOTION_L2_256B, CU_TENSOR_MAP_FLOAT_OOB_FILL_NONE);
    fibinet_kernel<<<NPREP + NMAIN, 384, SMEM_BYTES>>>(
        tm, (const int*)d_in[0], (const uint4*)d_in[1], (const __nv_bfloat16*)d_in[2], (const __nv_bfloat16*)d_in[3],
        (const __nv_bfloat16*)d_in[4], (const __nv_bfloat16*)d_in[5], (const __nv_bfloat16*)d_in[7], (__nv_bfloat16*)d_out);
}
```

```cpp
#include <cuda_runtime.h>
#include <cuda_bf16.h>
#include <cuda.h>
#include <stdint.h>

namespace {

constexpr int NB = 4096, NF = 26, ND = 64, NH = 256, NR = 13;
constexpr int NPREP = 4;
constexpr int NMAIN = 128;

constexpr int SLOT = 8192;
constexpr int ZOFF = 15 * SLOT;
__host__ __device__ constexpr int slot(int s) { return ZOFF - s * SLOT; }
constexpr int BOFF = ZOFF + SLOT;
constexpr int AOFF = BOFF + 32768 + 128;
constexpr int COFF = slot(12);
constexpr int MOFF = AOFF + 65536 + 128;
constexpr int BAR_FULL = MOFF, BAR_DONE = MOFF + 64, BAR_WC = MOFF + 128, BAR_FIN = MOFF + 176,
              BAR_TD1 = MOFF + 184, BAR_TD2 = MOFF + 192;
__host__ __device__ constexpr int bfull(int f) { return BAR_FULL + (f & 7) * 8; }
__host__ __device__ constexpr int bdone(int f) { return BAR_DONE + (f & 7) * 8; }
__host__ __device__ constexpr int bpar(int f) { return (f >> 3) & 1; }
constexpr int W2OFF = MOFF + 512, PARTOFF = MOFF + 1024, TSOFF = MOFF + 1536;
constexpr int SMEM_BYTES = MOFF + 2816;
constexpr int XDELTA = 2 * SLOT;
__host__ __device__ constexpr int xpair(int i) {
    return (i & 3) == 0 ? slot(11) : (i & 3) == 1 ? BOFF : (i & 3) == 2 ? BOFF + SLOT : slot(15);
}
__host__ __device__ constexpr int wl(int f) { return f % 5 == 0 ? 1 : f % 5 == 4 ? 7 : f % 5 + 2; }
__host__ __device__ constexpr int wcslot(int c) {
    return c == 0 ? slot(3) : c == 1 ? slot(8) : c == 2 ? slot(4) : c == 3 ? slot(10) : c == 4 ? slot(5)
         : c == 5 ? slot(15) : c == 6 ? slot(13) : c == 7 ? slot(11) : c == 8 ? slot(9)
         : c == 9 ? slot(14) : c == 10 ? slot(7) : c == 11 ? slot(2) : c == 12 ? slot(1)
         : c == 13 ? slot(6) : c == 14 ? ZOFF : slot(3);
}
constexpr int SEOFF = slot(6);
constexpr int ZQOFF = SEOFF + 4096;

__device__ uint4 g_wc[2 * 16 * 8192 / 16];
__device__ uint4 g_se[3072 / 16];
__device__ unsigned g_ready;
__device__ unsigned g_seen;

__host__ __device__ constexpr int fieldof(int f) {
    return f < 2 ? 24 + f : 4 * ((f - 2) >> 2) + 2 * (f & 1) + (((f - 2) >> 1) & 1);
}
__device__ __forceinline__ int jmap(int n) {
    int t = (n >> 1) & 3, m = 2 * (n >> 3) + (n & 1);
    return m < 6 ? 4 * m + 2 * (t & 1) + (t >> 1) : (m == 6 && t < 2) ? 24 + t : -1;
}
__device__ __forceinline__ int imap(int c, int t, int u) {
    return c < 3 ? 8 * c + 2 * t + u : (t < 2 ? 24 + t : -1);
}

__device__ __forceinline__ uint64_t mkdesc(uint32_t addr, uint32_t lbo, uint32_t sbo, int sw) {
    return (uint64_t)((addr & 0x3ffff) >> 4) | ((uint64_t)(lbo >> 4) << 16) | ((uint64_t)(sbo >> 4) << 32) |
           ((uint64_t)sw << 62);
}
__device__ __forceinline__ void mbar_init(uint32_t b, uint32_t n) {
    asm volatile("mbarrier.init.shared.b64 [%0], %1;" ::"r"(b), "r"(n) : "memory");
}
__device__ __forceinline__ void mbar_wait(uint32_t b, uint32_t par = 0) {
    asm volatile(
        "{\n.reg .pred p, q;\n.reg .u32 n;\n"
        "mbarrier.try_wait.parity.shared.b64 p, [%0], %1;\n@p bra.uni WD%=;\nmov.u32 n, 0;\n"
        "WL%=:\nmbarrier.try_wait.parity.shared.b64 p, [%0], %1;\n@p bra.uni WD%=;\n"
        "add.u32 n, n, 1;\nsetp.lt.u32 q, n, 4000000;\n@q bra.uni WL%=;\nWD%=:\n}\n" ::"r"(b), "r"(par)
        : "memory");
}
__device__ __forceinline__ uint32_t mbar_test(uint32_t b, uint32_t par) {
    uint32_t ok;
    asm volatile("{.reg .pred p; mbarrier.test_wait.parity.shared.b64 p, [%1], %2; selp.u32 %0, 1, 0, p;}"
                 : "=r"(ok)
                 : "r"(b), "r"(par)
                 : "memory");
    return ok;
}
__device__ __forceinline__ void mbar_wait_unless(uint32_t ok, uint32_t b, uint32_t par) {
    asm volatile(
        "{\n.reg .pred p, q;\n.reg .u32 n;\n"
        "setp.ne.u32 p, %1, 0;\n@p bra.uni WD%=;\nmov.u32 n, 0;\n"
        "WL%=:\nmbarrier.try_wait.parity.shared.b64 p, [%0], %2;\n@p bra.uni WD%=;\n"
        "add.u32 n, n, 1;\nsetp.lt.u32 q, n, 4000000;\n@q bra.uni WL%=;\nWD%=:\n}\n" ::"r"(b), "r"(ok), "r"(par)
        : "memory");
}
__device__ __forceinline__ void mbar_arrive(uint32_t b) {
    asm volatile("mbarrier.arrive.shared.b64 _, [%0];" ::"r"(b) : "memory");
}
__device__ __forceinline__ void mbar_expect(uint32_t b, uint32_t bytes) {
    asm volatile("mbarrier.arrive.expect_tx.shared.b64 _, [%0], %1;" ::"r"(b), "r"(bytes) : "memory");
}
__device__ __forceinline__ uint32_t opaque(uint32_t v) { return __shfl_sync(0xffffffffu, v, threadIdx.x); }
__device__ __forceinline__ bool elect() {
    uint32_t p;
    asm volatile("{.reg .pred q; elect.sync _|q, 0xffffffff; selp.u32 %0, 1, 0, q;}" : "=r"(p));
    return p;
}
__device__ __forceinline__ void tma2d(uint32_t dst, const CUtensorMap* m, uint32_t bar, int x, int y) {
    asm volatile(
        "cp.async.bulk.tensor.2d.shared::cluster.global.mbarrier::complete_tx::bytes [%0], [%1, {%3, %4}], [%2];" ::"r"(dst),
        "l"(m), "r"(bar), "r"(x), "r"(y)
        : "memory");
}
__device__ __forceinline__ void bulk(uint32_t dst, const void* src, uint32_t bytes, uint32_t bar) {
    asm volatile("cp.async.bulk.shared::cluster.global.mbarrier::complete_tx::bytes [%0], [%1], %2, [%3];" ::"r"(dst),
                 "l"(src), "r"(bytes), "r"(bar)
                 : "memory");
}
__device__ __forceinline__ void cp16(uint32_t dst, const void* src) {
    asm volatile("cp.async.cg.shared.global [%0], [%1], 16;" ::"r"(dst), "l"(src) : "memory");
}
__device__ __forceinline__ void lds128(uint32_t (&v)[4], uint32_t a) {
    asm volatile("ld.shared.v4.u32 {%0,%1,%2,%3}, [%4];" : "=r"(v[0]), "=r"(v[1]), "=r"(v[2]), "=r"(v[3]) : "r"(a) : "memory");
}
__device__ __forceinline__ void lds128_if(uint32_t (&v)[4], uint32_t a, uint32_t p) {
    asm volatile("{.reg .pred q; setp.ne.u32 q, %5, 0; @q ld.shared.v4.u32 {%0,%1,%2,%3}, [%4];}"
                 : "+r"(v[0]), "+r"(v[1]), "+r"(v[2]), "+r"(v[3])
                 : "r"(a), "r"(p)
                 : "memory");
}
__device__ __forceinline__ void lds64(uint32_t& x, uint32_t& y, uint32_t a) {
    asm volatile("ld.shared.v2.u32 {%0,%1}, [%2];" : "=r"(x), "=r"(y) : "r"(a) : "memory");
}
__device__ __forceinline__ void sts128(uint32_t a, uint32_t x, uint32_t y, uint32_t z, uint32_t w) {
    asm volatile("st.shared.v4.u32 [%0], {%1,%2,%3,%4};" ::"r"(a), "r"(x), "r"(y), "r"(z), "r"(w) : "memory");
}
__device__ __forceinline__ void sts64(uint32_t a, uint32_t x, uint32_t y) {
    asm volatile("st.shared.v2.u32 [%0], {%1,%2};" ::"r"(a), "r"(x), "r"(y) : "memory");
}
__device__ __forceinline__ uint32_t pack(float lo, float hi) {
    uint32_t r;
    asm volatile("cvt.rn.bf16x2.f32 %0, %1, %2;" : "=r"(r) : "f"(hi), "f"(lo));
    return r;
}
__device__ __forceinline__ uint32_t hmul2(uint32_t a, uint32_t b) {
    uint32_t r;
    asm volatile("mul.rn.bf16x2 %0, %1, %2;" : "=r"(r) : "r"(a), "r"(b));
    return r;
}
__device__ __forceinline__ uint32_t hfma2(uint32_t a, uint32_t b, uint32_t c) {
    uint32_t r;
    asm volatile("fma.rn.bf16x2 %0, %1, %2, %3;" : "=r"(r) : "r"(a), "r"(b), "r"(c));
    return r;
}
__device__ __forceinline__ float ffma(float a, float b, float c) {
    float r;
    asm volatile("fma.rn.f32 %0, %1, %2, %3;" : "=f"(r) : "f"(a), "f"(b), "f"(c));
    return r;
}
__device__ __forceinline__ float tanh_fast(float x) {
    float r;
    asm volatile("tanh.approx.f32 %0, %1;" : "=f"(r) : "f"(x));
    return r;
}
__device__ __forceinline__ float gelu_tanh(float x) {
    float r;
    asm volatile(
        "{.reg .f32 a; mul.f32 a, %1, %1; fma.rn.f32 a, a, 0f3D122279, 0f3F4C422A; mul.f32 a, a, %1; tanh.approx.f32 %0, a;}"
        : "=f"(r)
        : "f"(x));
    return r;
}
__device__ __forceinline__ uint32_t clock32() {
    uint32_t c;
    asm volatile("mov.u32 %0, %%clock;" : "=r"(c)::"memory");
    return c;
}
#define WG_FENCE() asm volatile("wgmma.fence.sync.aligned;" ::: "memory")
#define WG_COMMIT() asm volatile("wgmma.commit_group.sync.aligned;" ::: "memory")
#define WG_WAIT0() asm volatile("wgmma.wait_group.sync.aligned 0;" ::: "memory")
#define CP_COMMIT() asm volatile("cp.async.commit_group;" ::: "memory")
#define CP_WAIT(n) asm volatile("cp.async.wait_group %0;" ::"n"(n) : "memory")
#define SCHED_FENCE() mbar_wait_unless(gridDim.y, sb + BAR_FULL, 0)
#define PROXY_FENCE() asm volatile("fence.proxy.async.shared::cta;" ::: "memory")
template <int N>
__device__ __forceinline__ void pin(float (&d)[N]) {
#pragma unroll
    for (int i = 0; i < N; i++) asm volatile("" : "+f"(d[i])::"memory");
}
#define TS(k)

__device__ __forceinline__ void wgmma_ss_n168_acc(float (&d)[84], uint64_t da, uint64_t db) {
    asm volatile(
        "wgmma.mma_async.sync.aligned.m64n168k16.f32.bf16.bf16 "
        "{%0,%1,%2,%3,%4,%5,%6,%7,%8,%9,%10,%11,%12,%13,%14,%15,"
        "%16,%17,%18,%19,%20,%21,%22,%23,%24,%25,%26,%27,%28,%29,%30,%31,"
        "%32,%33,%34,%35,%36,%37,%38,%39,%40,%41,%42,%43,%44,%45,%46,%47,"
        "%48,%49,%50,%51,%52,%53,%54,%55,%56,%57,%58,%59,%60,%61,%62,%63,"
        "%64,%65,%66,%67,%68,%69,%70,%71,%72,%73,%74,%75,%76,%77,%78,%79,"
        "%80,%81,%82,%83}, "
        "%84, %85, 1, 1, 1, 0, 1;"
        : "+f"(d[0]), "+f"(d[1]), "+f"(d[2]), "+f"(d[3]), "+f"(d[4]), "+f"(d[5]), "+f"(d[6]), "+f"(d[7]),
          "+f"(d[8]), "+f"(d[9]), "+f"(d[10]), "+f"(d[11]), "+f"(d[12]), "+f"(d[13]), "+f"(d[14]), "+f"(d[15]),
          "+f"(d[16]), "+f"(d[17]), "+f"(d[18]), "+f"(d[19]), "+f"(d[20]), "+f"(d[21]), "+f"(d[22]), "+f"(d[23]),
          "+f"(d[24]), "+f"(d[25]), "+f"(d[26]), "+f"(d[27]), "+f"(d[28]), "+f"(d[29]), "+f"(d[30]), "+f"(d[31]),
          "+f"(d[32]), "+f"(d[33]), "+f"(d[34]), "+f"(d[35]), "+f"(d[36]), "+f"(d[37]), "+f"(d[38]), "+f"(d[39]),
          "+f"(d[40]), "+f"(d[41]), "+f"(d[42]), "+f"(d[43]), "+f"(d[44]), "+f"(d[45]), "+f"(d[46]), "+f"(d[47]),
          "+f"(d[48]), "+f"(d[49]), "+f"(d[50]), "+f"(d[51]), "+f"(d[52]), "+f"(d[53]), "+f"(d[54]), "+f"(d[55]),
          "+f"(d[56]), "+f"(d[57]), "+f"(d[58]), "+f"(d[59]), "+f"(d[60]), "+f"(d[61]), "+f"(d[62]), "+f"(d[63]),
          "+f"(d[64]), "+f"(d[65]), "+f"(d[66]), "+f"(d[67]), "+f"(d[68]), "+f"(d[69]), "+f"(d[70]), "+f"(d[71]),
          "+f"(d[72]), "+f"(d[73]), "+f"(d[74]), "+f"(d[75]), "+f"(d[76]), "+f"(d[77]), "+f"(d[78]), "+f"(d[79]),
          "+f"(d[80]), "+f"(d[81]), "+f"(d[82]), "+f"(d[83])
        : "l"(da), "l"(db));
}

__device__ __forceinline__ void wgmma_rs_n32_set(float (&d)[16], const uint32_t (&a)[4], uint64_t db) {
    asm volatile(
        "wgmma.mma_async.sync.aligned.m64n32k16.f32.bf16.bf16 "
        "{%0,%1,%2,%3,%4,%5,%6,%7,%8,%9,%10,%11,%12,%13,%14,%15}, "
        "{%16,%17,%18,%19}, %20, 0, 1, 1, 0;"
        : "=f"(d[0]), "=f"(d[1]), "=f"(d[2]), "=f"(d[3]), "=f"(d[4]), "=f"(d[5]), "=f"(d[6]), "=f"(d[7]),
          "=f"(d[8]), "=f"(d[9]), "=f"(d[10]), "=f"(d[11]), "=f"(d[12]), "=f"(d[13]), "=f"(d[14]), "=f"(d[15])
        : "r"(a[0]), "r"(a[1]), "r"(a[2]), "r"(a[3]), "l"(db));
}

__device__ __forceinline__ void wgmma_rs_n32_acc(float (&d)[16], const uint32_t (&a)[4], uint64_t db) {
    asm volatile(
        "wgmma.mma_async.sync.aligned.m64n32k16.f32.bf16.bf16 "
        "{%0,%1,%2,%3,%4,%5,%6,%7,%8,%9,%10,%11,%12,%13,%14,%15}, "
        "{%16,%17,%18,%19}, %20, 1, 1, 1, 0;"
        : "+f"(d[0]), "+f"(d[1]), "+f"(d[2]), "+f"(d[3]), "+f"(d[4]), "+f"(d[5]), "+f"(d[6]), "+f"(d[7]),
          "+f"(d[8]), "+f"(d[9]), "+f"(d[10]), "+f"(d[11]), "+f"(d[12]), "+f"(d[13]), "+f"(d[14]), "+f"(d[15])
        : "r"(a[0]), "r"(a[1]), "r"(a[2]), "r"(a[3]), "l"(db));
}

__device__ __forceinline__ void wgmma_rs_n16_set(float (&d)[8], const uint32_t (&a)[4], uint64_t db) {
    asm volatile(
        "wgmma.mma_async.sync.aligned.m64n16k16.f32.bf16.bf16 "
        "{%0,%1,%2,%3,%4,%5,%6,%7}, "
        "{%8,%9,%10,%11}, %12, 0, 1, 1, 0;"
        : "=f"(d[0]), "=f"(d[1]), "=f"(d[2]), "=f"(d[3]), "=f"(d[4]), "=f"(d[5]), "=f"(d[6]), "=f"(d[7])
        : "r"(a[0]), "r"(a[1]), "r"(a[2]), "r"(a[3]), "l"(db));
}

__device__ __forceinline__ void wgmma_rs_n16_acc(float (&d)[8], const uint32_t (&a)[4], uint64_t db) {
    asm volatile(
        "wgmma.mma_async.sync.aligned.m64n16k16.f32.bf16.bf16 "
        "{%0,%1,%2,%3,%4,%5,%6,%7}, "
        "{%8,%9,%10,%11}, %12, 1, 1, 1, 0;"
        : "+f"(d[0]), "+f"(d[1]), "+f"(d[2]), "+f"(d[3]), "+f"(d[4]), "+f"(d[5]), "+f"(d[6]), "+f"(d[7])
        : "r"(a[0]), "r"(a[1]), "r"(a[2]), "r"(a[3]), "l"(db));
}

__device__ __forceinline__ void wgmma_rs_n32_pred(float (&d)[16], const uint32_t (&a)[4], uint64_t db, uint32_t scale_d) {
    asm volatile(
        "{.reg .pred p; setp.ne.u32 p, %21, 0; wgmma.mma_async.sync.aligned.m64n32k16.f32.bf16.bf16 "
        "{%0,%1,%2,%3,%4,%5,%6,%7,%8,%9,%10,%11,%12,%13,%14,%15}, "
        "{%16,%17,%18,%19}, %20, p, 1, 1, 0;}"
        : "+f"(d[0]), "+f"(d[1]), "+f"(d[2]), "+f"(d[3]), "+f"(d[4]), "+f"(d[5]), "+f"(d[6]), "+f"(d[7]),
          "+f"(d[8]), "+f"(d[9]), "+f"(d[10]), "+f"(d[11]), "+f"(d[12]), "+f"(d[13]), "+f"(d[14]), "+f"(d[15])
        : "r"(a[0]), "r"(a[1]), "r"(a[2]), "r"(a[3]), "l"(db), "r"(scale_d));
}

__device__ __forceinline__ void prep_cta(uint32_t sb, int c, const __nv_bfloat16* __restrict__ wc,
                                         const __nv_bfloat16* __restrict__ se1, const __nv_bfloat16* __restrict__ se2) {
    const int tid = threadIdx.x, lane = tid & 31, warp = tid >> 5;
    constexpr int NROW = 2 * NF * NF;
    for (int q = tid; q < NROW * 2; q += 384) cp16(sb + q * 16, wc + (q >> 1) * ND + c * 16 + (q & 1) * 8);
    if (tid == 0) sts128(sb + NROW * 32, 0, 0, 0, 0);
    if (c == 0) {
        unsigned short* dst = reinterpret_cast<unsigned short*>(g_se);
        for (int q = tid; q < 1536; q += 384) {
            const int n = (q >> 5) - (q < 512 ? 0 : 16), k = q & 31, kk = k & 15;
            float v = 0.f;
            if (q < 512) {
                const int mm = kk >> 1, u = kk & 1, ww = k >> 4;
                const int f = mm < 6 ? 4 * mm + 2 * ww + u : (mm == 6 && u == 0) ? 24 + ww : -1;
                if (f >= 0 && n < NR) v = __bfloat162float(se1[f * NR + n]);
            } else {
                const int f = k < 16 ? jmap(n) : imap(n >> 3, (n >> 1) & 3, n & 1);
                if (f >= 0 && kk < NR) v = 0.5f * __bfloat162float(se2[kk * NF + f]);
            }
            dst[(q >> 5) * 32 + (((k >> 3) ^ ((n >> 1) & 3)) << 3) + (k & 7)] = __bfloat16_as_ushort(__float2bfloat16(v));
        }
    }
    asm volatile("cp.async.wait_all;" ::: "memory");
    __syncthreads();
    const int i = imap((lane & 7) >> 1, lane >> 3, lane & 1);
    const int g = lane >> 2, t = lane & 3;
    for (int task = warp; task < 128; task += 12) {
        const int eg = task & 1, n = (task >> 1) & 31, s = task >> 6;
        const int j = jmap(n);
        const uint32_t a = (i >= 0 && j >= 0) ? sb + ((s * NF + i) * NF + j) * 32 + eg * 16 : sb + NROW * 32;
        uint4 v;
        asm volatile("ldmatrix.sync.aligned.m8n8.x4.trans.shared.b16 {%0,%1,%2,%3}, [%4];"
                     : "=r"(v.x), "=r"(v.y), "=r"(v.z), "=r"(v.w)
                     : "r"(a));
        const int e = eg * 8 + g;
        if (t == 3) {
            const uint32_t mask = (e & 1) ? 0xffff0000u : 0xffffu;
            v.x &= mask;
            v.y &= mask;
        }
        const int ch = (t < 2 ? t ^ ((e >> 1) & 1) : t) ^ ((n >> 1) & 3);
        g_wc[(c >> 1) * 8192 + e * 512 + (c & 1) * 256 + s * 128 + n * 4 + ch] = v;
    }
    __threadfence();
    __syncthreads();
    if (tid == 0) atomicAdd(&g_ready, 1u);
}

#define PACE1 500
#define PACE2 1000
#define PF_START 2600
#define PF_PACE 550
#define WPF_AT 800

__global__ void __cluster_dims__(2, 1, 1) __launch_bounds__(384, 1)
fibinet_kernel(const int* __restrict__ idx, const uint4* __restrict__ table,
               const __nv_bfloat16* __restrict__ se1, const __nv_bfloat16* __restrict__ se2,
               const __nv_bfloat16* __restrict__ wbi, const __nv_bfloat16* __restrict__ wc,
               const unsigned char* __restrict__ w1, const __nv_bfloat16* __restrict__ w2, __nv_bfloat16* __restrict__ out,
               const __grid_constant__ CUtensorMap tm_w1) {
    extern __shared__ __align__(1024) unsigned char smem[];
    const uint32_t t_start = clock32();
    const int tid = threadIdx.x;
    const uint32_t sb = (uint32_t)__cvta_generic_to_shared(smem);
    const int cta = blockIdx.x < NPREP ? 0 : blockIdx.x - NPREP;
    const int grp = cta >> 1, rank = cta & 1;
    uint32_t ids[13][4];
    if (tid < 256) {
        const int* ip = idx + (grp * 64 + ((tid >> 5) & 3) * 16 + ((tid >> 3) & 3)) * NF + (tid >> 7);
#pragma unroll
        for (int u = 0; u < 4; u++) asm volatile("ld.global.nc.u32 %0, [%1];" : "=r"(ids[0][u]) : "l"(ip + 4 * NF * u + 24));
        ip += tid >> 7;
#pragma unroll
        for (int m = 0; m < 6; m++)
#pragma unroll
            for (int u = 0; u < 4; u++)
                asm volatile("ld.global.nc.v2.u32 {%0,%1}, [%2];"
                             : "=r"(ids[2 * m + 1][u]), "=r"(ids[2 * m + 2][u])
                             : "l"(ip + 4 * NF * u + 4 * m));
    }
    if (blockIdx.x < NPREP) {
        prep_cta(sb, blockIdx.x, wc, se1, se2);
        return;
    }
    const int warp = __shfl_sync(0xffffffffu, tid >> 5, 0);
    const int w = warp >> 2, lane = tid & 31;

    if (w == 2) {
        asm volatile("setmaxnreg.dec.sync.aligned.u32 40;");
        if (warp == 8) {
            if (elect()) {
#pragma unroll
                for (int k = 0; k < 8; k++) mbar_init(sb + BAR_FULL + k * 8, 1);
                asm volatile("fence.mbarrier_init.release.cluster;" ::: "memory");
            }
            __syncwarp();
            asm volatile("barrier.cluster.arrive.relaxed.aligned;" ::: "memory");
#pragma unroll
            for (int f = 0; f < 26; f++) {
                if (f == 5) asm volatile("bar.sync 0, 384;" ::: "memory");
                if (f >= 5) mbar_wait(sb + bdone(f - 5), bpar(f - 5));
                if (elect()) {
                    mbar_expect(sb + bfull(f), 16384);
                    tma2d(sb + slot(2 * wl(f)), &tm_w1, sb + bfull(f), 128 * rank + 64 * (f & 1), fieldof(f) * 64);
                    tma2d(sb + slot(wl(f)), &tm_w1, sb + bfull(f), 128 * rank + 64 - 64 * (f & 1), fieldof(f) * 64);
                }
                TS(64 + f);
            }
        } else if (warp == 9) {
            if (elect()) {
#pragma unroll
                for (int k = 0; k < 9; k++) mbar_init(sb + BAR_WC + k * 8, k < 7 ? 1 : 8);
                asm volatile("fence.mbarrier_init.release.cluster;" ::: "memory");
                mbar_expect(sb + BAR_FIN, 512);
            }
            __syncwarp();
            asm volatile("barrier.cluster.arrive.relaxed.aligned;" ::: "memory");
            asm volatile("bar.sync 0, 384;" ::: "memory");
            mbar_wait(sb + bdone(7), bpar(7));
            mbar_wait(sb + bdone(14), bpar(14));
            mbar_wait(sb + bdone(15), bpar(15));
            const unsigned char* src = reinterpret_cast<const unsigned char*>(g_wc) + rank * 131072;
            if (elect()) {
                unsigned v, it = 0;
                do {
                    asm volatile("ld.acquire.gpu.global.u32 %0, [%1];" : "=r"(v) : "l"(&g_ready) : "memory");
                } while (v < NPREP && ++it < 4000000u);
                asm volatile("fence.proxy.async.global;" ::: "memory");
            }
            __syncwarp();
#pragma unroll
            for (int gi = 0; gi < 6; gi++) {
                const int c0 = gi == 0 ? 0 : gi == 1 ? 1 : gi == 2 ? 3 : gi == 3 ? 5 : gi == 4 ? 9 : 13;
                const int c1 = gi == 0 ? 1 : gi == 1 ? 3 : gi == 2 ? 5 : gi == 3 ? 9 : gi == 4 ? 13 : 16;
                if (gi < 5) mbar_wait(sb + (gi < 3 ? bdone(21 + gi) : gi == 3 ? BAR_TD1 : BAR_TD2));
                if (elect()) {
                    mbar_expect(sb + BAR_WC + gi * 8, (c1 - c0) * 8192 + (gi == 0 ? 3072 : 0));
                    if (gi == 0) bulk(sb + SEOFF, g_se, 3072, sb + BAR_WC);
#pragma unroll
                    for (int c = c0; c < c1; c++) bulk(sb + wcslot(c), src + c * 8192, 8192, sb + BAR_WC + gi * 8);
                }
            }
            __syncwarp();
            if (elect() && atomicAdd(&g_seen, 1u) == NMAIN - 1) {
                g_seen = 0;
                g_ready = 0;
            }
            __syncwarp();
            mbar_wait(sb + BAR_FIN);
            const float* part = reinterpret_cast<const float*>(smem + PARTOFF) + lane;
            out[grp * 64 + rank * 32 + lane] = __float2bfloat16(part[0] + part[32] + part[64] + part[96]);
        } else if (warp == 10) {
            if (elect()) {
#pragma unroll
                for (int k = 0; k < 8; k++) mbar_init(sb + BAR_DONE + k * 8, 4);
                asm volatile("fence.mbarrier_init.release.cluster;" ::: "memory");
            }
            __syncwarp();
            asm volatile("barrier.cluster.arrive.relaxed.aligned;" ::: "memory");
            asm volatile("bar.arrive 0, 384;" ::: "memory");
            while (clock32() - t_start < WPF_AT) {
            }
#pragma unroll
            for (int k = 0; k < 2; k++)
                if (k * 32 + lane < 48)
                    asm volatile("prefetch.global.L2 [%0];" ::"l"(w1 + (k * 16 + (lane >> 1)) * 32768 + cta * 256 + (lane & 1) * 128));
            uint32_t pid[20];
            const uint2* ip = reinterpret_cast<const uint2*>(idx) + (grp * 64 + rank * 32 + lane) * 13 + 2;
#pragma unroll
            for (int k = 0; k < 10; k++)
                asm volatile("ld.global.nc.v2.u32 {%0,%1}, [%2];" : "=r"(pid[2 * k]), "=r"(pid[2 * k + 1]) : "l"(ip + k));
#pragma unroll
            for (int i = 3; i < 13; i++) {
                while (clock32() - t_start < (uint32_t)(PF_START + (i - 3) * PF_PACE)) {
                }
#pragma unroll
                for (int k = 0; k < 2; k++)
                    asm volatile("{.reg .u64 a; mad.wide.u32 a, %1, 128, %0; prefetch.global.L2 [a];}" ::"l"(table),
                                 "r"(pid[fieldof(2 * i + k) - 4]));
            }
        } else {
#pragma unroll
            for (int k = 0; k < 8; k++) {
                const int d = k * 8 + (lane >> 2), c = lane & 3;
                cp16(sb + ZOFF + d * 128 + ((c ^ (d & 7)) << 4), wbi + d * ND + 32 * rank + 8 * c);
            }
            const uint2 v = __ldg(reinterpret_cast<const uint2*>(w2 + 128 * rank) + lane);
#pragma unroll
            for (int k = 0; k < 2; k++) {
                const int d = k * 32 + lane;
                sts128(sb + ZOFF + d * 128 + ((4 ^ (d & 7)) << 4), 0x3c803c80u, 0x3c803c80u, 0x3c803c80u, 0x3c803c80u);
                const uint32_t x = k ? v.y : v.x;
                sts64(sb + W2OFF + ((lane >> 4) * 64 + (2 * (lane & 1) + k) * 16 + ((lane >> 1) & 7) * 2) * 4,
                      __float_as_uint(0.5f * __uint_as_float(x << 16)), __float_as_uint(0.5f * __uint_as_float(x & 0xffff0000u)));
            }
            asm volatile("cp.async.wait_all;" ::: "memory");
            PROXY_FENCE();
            asm volatile("barrier.cluster.arrive.relaxed.aligned;" ::: "memory");
            asm volatile("bar.arrive 0, 384;" ::: "memory");
        }
        asm volatile("barrier.cluster.wait.aligned;" ::: "memory");
    } else {
        asm volatile("setmaxnreg.inc.sync.aligned.u32 232;");
        asm volatile("barrier.cluster.arrive.relaxed.aligned;" ::: "memory");
        const int g = lane >> 2, t = lane & 3, wq = warp & 3, t128 = tid & 127;
        const uint32_t gd0 = opaque(sb + w * XDELTA + (wq * 16 + (lane >> 3)) * 128 + (((lane & 7) ^ (lane >> 3) ^ (4 * w)) << 4));
        const uint4* tp = table + (lane & 7);
        auto gather = [&](int i) {
#pragma unroll
            for (int u = 0; u < 4; u++)
                asm volatile("{.reg .u64 a; mad.wide.u32 a, %2, 128, %1; cp.async.cg.shared.global [%0], [a], 16;}" ::"r"(
                                 (gd0 ^ ((u & 1) * 64)) + xpair(i) + u * 512),
                             "l"(tp), "r"(ids[i][u])
                             : "memory");
            CP_COMMIT();
        };
        gather(0);
        TS(56 + w);
        float acc[84];
#pragma unroll
        for (int k = 0; k < 84; k++) asm volatile("mov.b32 %0, 0;" : "=f"(acc[k]));
        uint32_t e0[9], e1[9], e2[4];
        uint32_t X[14][2][4];
        uint32_t zq[4] = {0, 0, 0, 0};
        const uint64_t dA = mkdesc(sb + w * XDELTA, 16, 1024, 1);
        const uint64_t dB = mkdesc(sb + ZOFF, 0, 1024, 1);
        const uint32_t xl0 = opaque(sb + (t & 1) * XDELTA + (16 * wq + g) * 128 + (((4 * rank + 2 * w) ^ (4 * (t & 1)) ^ g) << 4));
        const uint32_t hi_half = t >> 1;
        const uint32_t sa0 = opaque(sb + AOFF + t * 4096 + (t >> 1) * 16 + (wq * 32 + g * 4 + w) * 16);
        const uint32_t sa1 = opaque(((g & 2) << 4) | ((t & 1) << 3));
        const uint32_t zero = blockIdx.y;
        {
            const uint32_t c0 = clock32();
            asm volatile("bar.sync 0, 384;" ::: "memory");
            while (clock32() - c0 < PACE1) {
            }
            gather(1);
            while (clock32() - c0 < PACE2) {
            }
            gather(2);
        }
        auto lift = [&](int i) {
            const int m = i == 0 ? 6 : (i - 1) >> 1;
            if (i & 1) {
#pragma unroll
                for (int k = 0; k < 16; k++) X[2 * m + (k >> 3)][(k >> 2) & 1][k & 3] = 0;
            }
#pragma unroll
            for (int r = 0; r < 2; r++)
#pragma unroll
                for (int cc = 0; cc < 2; cc++) {
                    const uint32_t a = (xl0 ^ (cc * 16)) + xpair(i) + r * 1024;
                    if (i == 0) lds128(X[2 * m + r][cc], a);
                    else lds128_if(X[2 * m + r][cc], a, (i & 1) ? hi_half ^ 1 : hi_half);
                }
        };
        auto store_pair = [&](int m, int n0, int n1) {
            uint32_t a;
            if (m < 4) a = sa0 + (sa1 ^ (((m & 1) << 5) | ((m >> 1) << 3)));
            else a = sb + BOFF + t * 2048 + t * 8 + (wq * 32 + g * 4 + 2 * (m & 1) + w) * 8;
#pragma unroll
            for (int n = n0; n < n1; n++)
#pragma unroll
                for (int u = 0; u < 2; u++)
                    sts64(a + (m < 4 ? (8 * n + u) * 2048 + n * 32 : (8 * n + u) * 1024 + n * 32),
                          __byte_perm(n0 == 2 ? e2[2 * n - 4] : e0[2 * n], e1[2 * n], u ? 0x7632 : 0x5410),
                          __byte_perm(n0 == 2 ? e2[2 * n - 3] : e0[2 * n + 1], e1[2 * n + 1], u ? 0x7632 : 0x5410));
        };
        auto z_pair = [&](int m, uint32_t a, uint32_t b) {
            asm volatile("{.reg .pred p; setp.eq.u32 p, %4, %5; @p prmt.b32 %0, %2, %3, 0x5410; @p prmt.b32 %1, %2, %3, 0x7632;}"
                         : "+r"(zq[2 * (m >> 2)]), "+r"(zq[2 * (m >> 2) + 1])
                         : "r"(a), "r"(b), "r"(t), "r"(m & 3));
        };

        TS(58 + w);
        mbar_wait(sb + BAR_FULL + w * 8);
        CP_WAIT(2);
        if (w == 1) {
            asm volatile("bar.arrive 3, 256;" ::: "memory");
            asm volatile("bar.sync 2, 256;" ::: "memory");
        }
#pragma unroll
        for (int i = 0; i < 13; i++) {
            const uint64_t da = dA + (xpair(i) >> 4) + ((uint64_t)i << 16),
                           db = dB + (uint32_t)((w ? wl(2 * i + 1) : wl(2 * i)) * ((SLOT << 12) - (SLOT >> 3)));
            TS(2 * i + w);
            WG_FENCE();
            wgmma_ss_n168_acc(acc, da, db + w * 256);
            wgmma_ss_n168_acc(acc, da + 2, db + w * 256 + 128);
            wgmma_ss_n168_acc(acc, da + 4, db + (w ^ 1) * 256);
            wgmma_ss_n168_acc(acc, da + 6, db + (w ^ 1) * 256 + 128);
            WG_COMMIT();
            if (i == 0) {
                if (w == 0) {
                    asm volatile("bar.arrive 2, 256;" ::: "memory");
                    asm volatile("bar.sync 3, 256;" ::: "memory");
                }
            } else {
                mbar_wait(sb + bdone(2 * i - 2) + (w ^ 1) * 8, bpar(2 * i - 2));
            }
            if (i < 10) gather(i + 3);
            if (i < 11) lift(i);
            if (i == 1) {
#pragma unroll
                for (int n = 0; n < 4; n++) sts64(sb + COFF + w * 4096 + n * 1024 + (t128 ^ w) * 8, e1[2 * n], e1[2 * n + 1]);
                z_pair(6, e1[8], 0);
            } else if (i & 1) {
                if (i == 11) {
                    mbar_wait(sb + bdone(20) + w * 8, bpar(20));
                }
                z_pair((i - 2) >> 1, e0[8], e1[8]);
                store_pair((i - 2) >> 1, 0, 2);
#pragma unroll
                for (int k = 0; k < 4; k++) e2[k] = e0[4 + k];
            } else if (i >= 4) {
                store_pair((i - 3) >> 1, 2, 4);
            }
            const uint32_t rdy = i < 12 ? mbar_test(sb + bfull(2 * i + 2) + w * 8, bpar(2 * i + 2)) : mbar_test(sb + BAR_WC, 0);
            WG_WAIT0();
            pin(acc);
            if (i < 10) CP_WAIT(2);
            else if (i == 10) CP_WAIT(1);
            else if (i == 11) CP_WAIT(0);
            if (lane == 0) mbar_arrive(sb + bdone(2 * i) + w * 8);
#pragma unroll
            for (int k = 0; k < 9; k++) {
                const uint32_t v = k < 8 ? pack(acc[64 + 2 * k], acc[65 + 2 * k]) : pack(acc[80], acc[82]);
                if (i & 1) e0[k] = v;
                else e1[k] = v;
            }
            if (i < 12) {
#pragma unroll
                for (int k = 64; k < 83; k++)
                    if (k != 81) asm volatile("mov.b32 %0, %1;" : "+f"(acc[k]) : "r"(zero));
                mbar_wait_unless(rdy, sb + bfull(2 * i + 2) + w * 8, bpar(2 * i + 2));
            } else {
                z_pair(5, e0[8], e1[8]);
                sts128(sb + ZQOFF + w * 2048 + t128 * 16, zq[0], zq[1], zq[2], zq[3]);
                mbar_wait_unless(rdy, sb + BAR_WC, 0);
            }
        }
        TS(26 + w);

        mbar_wait(sb + bdone(24) + w * 8, bpar(24));
        {
            const uint32_t L = (w ? wl(25) : wl(24)) * SLOT, a = sb + ZOFF - 2 * L + t128 * 16;
#pragma unroll
            for (int k = 0; k < 8; k++)
                sts128(a + (k >> 2) * L + (k & 3) * 2048, __float_as_uint(acc[32 + 4 * k]), __float_as_uint(acc[33 + 4 * k]),
                       __float_as_uint(acc[34 + 4 * k]), __float_as_uint(acc[35 + 4 * k]));
        }
        asm volatile("bar.sync 1, 256;" ::: "memory");
        TS(28 + w);
        float aj[14];
        uint32_t ai[8];
        float sum0 = 0.f, sum1 = 0.f;
        float th[32];
        auto deep_issue = [&](int k0, int k1) {
#pragma unroll
            for (int k = k0; k < k1; k++) th[k] = gelu_tanh(acc[k]);
        };
        auto deep_use = [&](int k0, int k1) {
#pragma unroll
            for (int n = k0 >> 2; n < k1 >> 2; n++) {
                uint32_t h0, h1;
                lds64(h0, h1, sb + W2OFF + (w * 64 + t * 16 + n * 2) * 4);
#pragma unroll
                for (int k = 4 * n; k < 4 * n + 4; k++) {
                    const float h = __uint_as_float((k & 1) ? h1 : h0);
                    const float y = ffma(th[k], h, h);
                    if (k & 2) sum1 = ffma(acc[k], y, sum1);
                    else sum0 = ffma(acc[k], y, sum0);
                }
            }
        };
        {
            const uint64_t dS = mkdesc(sb + SEOFF, 16, 512, 2);
            uint32_t zo[4];
            lds128(zo, sb + ZQOFF + (w ^ 1) * 2048 + t128 * 16);
            const uint32_t L = (w ? wl(24) : wl(25)) * SLOT, a = sb + ZOFF - 2 * L + t128 * 16;
            uint32_t o[8][4];
#pragma unroll
            for (int k = 0; k < 8; k++) lds128(o[k], a + (k >> 2) * L + (k & 3) * 2048);
            float s1[8];
            WG_FENCE();
            wgmma_rs_n16_set(s1, zq, dS + w * 2);
            wgmma_rs_n16_acc(s1, zo, dS + (w ^ 1) * 2);
            WG_COMMIT();
#pragma unroll
            for (int k = 0; k < 32; k++) asm volatile("add.f32 %0, %0, %1;" : "+f"(acc[k]) : "r"(o[k >> 2][k & 3]));
            deep_issue(0, 12);
            store_pair(5, 0, 4);
            SCHED_FENCE();
            TS(36 + w);
            WG_WAIT0();
            pin(s1);
            float t1[8];
#pragma unroll
            for (int k = 0; k < 8; k++) t1[k] = gelu_tanh(s1[k]);
            deep_use(0, 12);
            SCHED_FENCE();
            TS(38 + w);
            uint32_t gq[4];
#pragma unroll
            for (int k = 0; k < 4; k++)
                gq[k] = pack(s1[2 * k] * ffma(t1[2 * k], 0.5f, 0.5f), s1[2 * k + 1] * ffma(t1[2 * k + 1], 0.5f, 0.5f));
            float s2[16];
            WG_FENCE();
            wgmma_rs_n32_set(s2, gq, dS + 64 + w * 2);
            WG_COMMIT();
            deep_issue(12, 20);
            lift(11);
            lift(12);
            __syncwarp();
            if (lane == 0) mbar_arrive(sb + BAR_TD1);
            SCHED_FENCE();
            TS(40 + w);
            WG_WAIT0();
            pin(s2);
#pragma unroll
            for (int k = 0; k < 16; k++) s2[k] = tanh_fast(s2[k]);
            deep_use(12, 20);
            SCHED_FENCE();
            TS(42 + w);
            uint32_t ap[8];
#pragma unroll
            for (int k = 0; k < 8; k++) ap[k] = pack(ffma(s2[2 * k], 0.5f, 0.5f), ffma(s2[2 * k + 1], 0.5f, 0.5f));
            sts128(sb + ZOFF + w * 4096 + t128 * 16, ap[0], ap[1], ap[2], ap[3]);
            sts128(sb + ZOFF + w * 4096 + 2048 + t128 * 16, ap[4], ap[5], ap[6], ap[7]);
            deep_issue(20, 32);
            asm volatile("bar.sync 1, 256;" ::: "memory");
            uint32_t v[4][4];
#pragma unroll
            for (int k = 0; k < 4; k++) lds128(v[k], sb + ZOFF + (k ^ 2) * 2048 + t128 * 16);
#pragma unroll
            for (int k = 0; k < 8; k++) ai[k] = v[k >> 2][k & 3];
#pragma unroll
            for (int q = 0; q < 14; q++) {
                const int k = 2 * (q >> 2) + (q & 1);
                const uint32_t x = v[2 + (k >> 2)][k & 3];
                aj[q] = __uint_as_float((q & 2) ? x & 0xffff0000u : x << 16);
            }
        }
        TS(30 + w);

        {
            const uint32_t la = sb + AOFF + w * (16 * 2048 + 64) + (wq * 32 + g * 4 + (t ^ (g & 2))) * 16;
            const uint32_t lb = sb + BOFF + w * (16 * 1024 + 64) + t128 * 8;
            const uint32_t lc0 = sb + COFF + (t & 1) * (4096 + 8) + w * 2048 + (wq * 8 + g) * 32, lc1 = lc0 ^ 8;
            const uint64_t dW = mkdesc(sb + w * 4096, 16, 512, 2);
            uint32_t Ap[2][2][4], Aq[2][4], hacc[4];
            float Sp[16], Sq[16], U[14];
            auto load_a = [&](int e) {
                lds128(Ap[e & 1][0], la + e * 2048 + (e >> 2) * 16);
                lds64(Ap[e & 1][1][0], Ap[e & 1][1][1], lb + e * 1024 + (e >> 1) * 8);
                lds64(Ap[e & 1][1][2], Ap[e & 1][1][3], ((e & 2) ? lc1 : lc0) + (e >> 3) * 1024 + (e & 4) * 4);
            };
            load_a(0);
#pragma unroll
            for (int e = 0; e < 16; e++) {
                if (e & 1) mbar_wait(sb + BAR_WC + (e == 1 ? 1 : e == 3 ? 2 : e < 9 ? 3 : e < 13 ? 4 : 5) * 8);
#pragma unroll
                for (int k = 0; k < 8; k++) Aq[k >> 2][k & 3] = hmul2(Ap[e & 1][k >> 2][k & 3], ai[k < 4 ? k ^ (e & 2) : k]);
                const uint64_t d = dW + (wcslot(e) >> 4);
                WG_FENCE();
                if (e == 0) wgmma_rs_n32_set(Sp, Ap[e & 1][0], d);
                else wgmma_rs_n32_pred(Sp, Ap[e & 1][0], d, blockIdx.y);
                wgmma_rs_n32_acc(Sp, Ap[e & 1][1], d + 2);
                if (e == 0) wgmma_rs_n32_set(Sq, Aq[0], d + 128);
                else wgmma_rs_n32_pred(Sq, Aq[0], d + 128, blockIdx.y);
                wgmma_rs_n32_acc(Sq, Aq[1], d + 130);
                WG_COMMIT();
                if (e + 1 < 16) load_a(e + 1);
                if (e == 0) {
                    SCHED_FENCE();
                    deep_use(20, 32);
                    SCHED_FENCE();
                }
                WG_WAIT0();
                pin(Sp);
                pin(Sq);
                if (e == 0 && lane == 0) mbar_arrive(sb + BAR_TD2);
#pragma unroll
                for (int q = 0; q < 14; q++) {
                    const int ix = 4 * (q >> 2) + 2 * (q & 1) + ((q >> 1) & 1);
                    const float u = ffma(aj[q], Sq[ix], Sp[ix]);
                    if (!(e & 1)) {
                        U[q] = u;
                    } else {
                        const uint32_t x = X[q][e >> 3][(e & 7) >> 1];
                        if ((e & 7) == 1 && q < 4) hacc[q] = hmul2(pack(U[q], u), x);
                        else hacc[q & 3] = hfma2(pack(U[q], u), x, hacc[q & 3]);
                    }
                }
                if ((e & 7) == 7) {
                    sum0 += (__uint_as_float(hacc[0] << 16) + __uint_as_float(hacc[0] & 0xffff0000u)) +
                            (__uint_as_float(hacc[2] << 16) + __uint_as_float(hacc[2] & 0xffff0000u));
                    sum1 += (__uint_as_float(hacc[1] << 16) + __uint_as_float(hacc[1] & 0xffff0000u)) +
                            (__uint_as_float(hacc[3] << 16) + __uint_as_float(hacc[3] & 0xffff0000u));
                }
                if (e == 7) TS(32 + w);
            }
        }
        TS(34 + w);
        {
            float v = (t & 1) ? sum1 : sum0;
            v += __shfl_xor_sync(0xffffffffu, (t & 1) ? sum0 : sum1, 1);
            v += __shfl_xor_sync(0xffffffffu, v, 2);
            asm volatile("barrier.cluster.wait.aligned;" ::: "memory");
            if (t < 2) {
                uint32_t ra, rb;
                asm("mapa.shared::cluster.u32 %0, %1, %2;"
                    : "=r"(ra)
                    : "r"(sb + PARTOFF + ((2 * rank + w) * 32 + (wq & 1) * 16 + t * 8 + g) * 4), "r"(wq >> 1));
                asm("mapa.shared::cluster.u32 %0, %1, %2;" : "=r"(rb) : "r"(sb + BAR_FIN), "r"(wq >> 1));
                asm volatile("st.async.shared::cluster.mbarrier::complete_tx::bytes.f32 [%0], %1, [%2];" ::"r"(ra), "f"(v), "r"(rb)
                             : "memory");
            }
        }
    }
}

typedef CUresult (*EncodeFn)(CUtensorMap*, CUtensorMapDataType, cuuint32_t, void*, const cuuint64_t*, const cuuint64_t*,
                             const cuuint32_t*, const cuuint32_t*, CUtensorMapInterleave, CUtensorMapSwizzle,
                             CUtensorMapL2promotion, CUtensorMapFloatOOBfill);

}

extern "C" void kernel_launch(void* const* d_in, const int* in_sizes, int n_in, void* d_out, int out_size) {
    static EncodeFn encode = nullptr;
    if (!encode) {
        void* fn = nullptr;
        cudaDriverEntryPointQueryResult qr;
        cudaGetDriverEntryPoint("cuTensorMapEncodeTiled", &fn, cudaEnableDefault, &qr);
        encode = (EncodeFn)fn;
        cudaFuncSetAttribute(fibinet_kernel, cudaFuncAttributeMaxDynamicSharedMemorySize, SMEM_BYTES);
    }
    CUtensorMap tm;
    const cuuint64_t gd[2] = {NH, NF * ND};
    const cuuint64_t gs[1] = {NH * 2};
    const cuuint32_t bd[2] = {64, 64}, es[2] = {1, 1};
    encode(&tm, CU_TENSOR_MAP_DATA_TYPE_BFLOAT16, 2, d_in[6], gd, gs, bd, es, CU_TENSOR_MAP_INTERLEAVE_NONE,
           CU_TENSOR_MAP_SWIZZLE_128B, CU_TENSOR_MAP_L2_PROMOTION_L2_256B, CU_TENSOR_MAP_FLOAT_OOB_FILL_NONE);
    fibinet_kernel<<<NPREP + NMAIN, 384, SMEM_BYTES>>>(
        (const int*)d_in[0], (const uint4*)d_in[1], (const __nv_bfloat16*)d_in[2], (const __nv_bfloat16*)d_in[3],
        (const __nv_bfloat16*)d_in[4], (const __nv_bfloat16*)d_in[5], (const unsigned char*)d_in[6], (const __nv_bfloat16*)d_in[7], (__nv_bfloat16*)d_out, tm);
}
```

```cpp
#include <cuda_runtime.h>
#include <cuda_bf16.h>
#include <cuda.h>
#include <stdint.h>

namespace {

constexpr int NB = 4096, NF = 26, ND = 64, NH = 256, NR = 13;
constexpr int NPREP = 4;
constexpr int NMAIN = 128;

constexpr int SLOT = 8192;
constexpr int ZOFF = 15 * SLOT;
__host__ __device__ constexpr int slot(int s) { return ZOFF - s * SLOT; }
constexpr int BOFF = ZOFF + SLOT;
constexpr int AOFF = BOFF + 32768;
constexpr int COFF = slot(12);
constexpr int MOFF = AOFF + 65536 + 128;
constexpr int BAR_FULL = MOFF, BAR_DONE = MOFF + 64, BAR_WC = MOFF + 128, BAR_FIN = MOFF + 176,
              BAR_GO = MOFF + 184, BAR_SE = MOFF + 192, BAR_TD = MOFF + 200, BAR_Z = MOFF + 208;
__host__ __device__ constexpr int bfull(int f) { return BAR_FULL + (f & 7) * 8; }
__host__ __device__ constexpr int bdone(int f) { return BAR_DONE + (f & 7) * 8; }
__host__ __device__ constexpr int bpar(int f) { return (f >> 3) & 1; }
constexpr int PARTOFF = MOFF + 256, SEOFF = MOFF + 768;
constexpr int SMEM_BYTES = MOFF + 2944;
constexpr int XDELTA = 2 * SLOT;
__host__ __device__ constexpr int xpair(int i) {
    return (i & 3) == 0 ? slot(11) : (i & 3) == 1 ? BOFF : (i & 3) == 2 ? BOFF + SLOT : slot(15);
}
__host__ __device__ constexpr int wl(int f) { return f % 5 == 0 ? 1 : f % 5 == 4 ? 7 : f % 5 + 2; }
__host__ __device__ constexpr int wcslot(int c) {
    return c == 0 ? slot(3) : c == 1 ? slot(8) : c == 2 ? slot(4) : c == 3 ? slot(10) : c == 4 ? slot(5)
         : c == 5 ? slot(15) : c == 6 ? slot(13) : c == 7 ? slot(11) : c == 8 ? slot(9)
         : c == 9 ? slot(14) : c == 10 ? slot(7) : c == 11 ? slot(2) : c == 12 ? slot(1)
         : c == 13 ? slot(6) : c == 14 ? ZOFF : slot(3);
}
__host__ __device__ constexpr int wcfirst(int gi) { return gi == 0 ? 0 : gi == 1 ? 1 : gi == 2 ? 3 : gi == 3 ? 7 : gi == 4 ? 9 : gi == 5 ? 13 : 16; }
constexpr int ZQOFF = slot(6);
__host__ __device__ constexpr int w2chunk(int c) { return ZOFF + c * 128 + ((5 ^ (c & 7)) << 4); }

__device__ uint4 g_wc[2 * 16 * 8192 / 16];
__device__ uint4 g_se[2048 / 16];
__device__ unsigned g_ready;
__device__ unsigned g_seen;

__host__ __device__ constexpr int fieldof(int f) { return f < 24 ? 4 * (f >> 2) + 2 * (f & 1) + ((f >> 1) & 1) : f; }
__device__ __forceinline__ int fmap(int n) { return n < 24 ? n : n < 28 ? 24 + ((n >> 1) & 1) : -1; }

__device__ __forceinline__ uint64_t mkdesc(uint32_t addr, uint32_t lbo, uint32_t sbo, int sw) {
    return (uint64_t)((addr & 0x3ffff) >> 4) | ((uint64_t)(lbo >> 4) << 16) | ((uint64_t)(sbo >> 4) << 32) |
           ((uint64_t)sw << 62);
}
__device__ __forceinline__ void mbar_init(uint32_t b, uint32_t n) {
    asm volatile("mbarrier.init.shared.b64 [%0], %1;" ::"r"(b), "r"(n) : "memory");
}
__device__ __forceinline__ void mbar_wait(uint32_t b, uint32_t par = 0) {
    asm volatile(
        "{\n.reg .pred p, q;\n.reg .u32 n;\n"
        "mbarrier.try_wait.parity.shared.b64 p, [%0], %1;\n@p bra.uni WD%=;\nmov.u32 n, 0;\n"
        "WL%=:\nmbarrier.try_wait.parity.shared.b64 p, [%0], %1;\n@p bra.uni WD%=;\n"
        "add.u32 n, n, 1;\nsetp.lt.u32 q, n, 4000000;\n@q bra.uni WL%=;\nWD%=:\n}\n" ::"r"(b), "r"(par)
        : "memory");
}
__device__ __forceinline__ uint32_t mbar_test(uint32_t b, uint32_t par) {
    uint32_t ok;
    asm volatile("{.reg .pred p; mbarrier.test_wait.parity.shared.b64 p, [%1], %2; selp.u32 %0, 1, 0, p;}"
                 : "=r"(ok)
                 : "r"(b), "r"(par)
                 : "memory");
    return ok;
}
__device__ __forceinline__ void mbar_wait_unless(uint32_t ok, uint32_t b, uint32_t par) {
    asm volatile(
        "{\n.reg .pred p, q;\n.reg .u32 n;\n"
        "setp.ne.u32 p, %1, 0;\n@p bra.uni WD%=;\nmov.u32 n, 0;\n"
        "WL%=:\nmbarrier.try_wait.parity.shared.b64 p, [%0], %2;\n@p bra.uni WD%=;\n"
        "add.u32 n, n, 1;\nsetp.lt.u32 q, n, 4000000;\n@q bra.uni WL%=;\nWD%=:\n}\n" ::"r"(b), "r"(ok), "r"(par)
        : "memory");
}
__device__ __forceinline__ void mbar_arrive(uint32_t b) {
    asm volatile("mbarrier.arrive.shared.b64 _, [%0];" ::"r"(b) : "memory");
}
__device__ __forceinline__ void mbar_expect(uint32_t b, uint32_t bytes) {
    asm volatile("mbarrier.arrive.expect_tx.shared.b64 _, [%0], %1;" ::"r"(b), "r"(bytes) : "memory");
}
__device__ __forceinline__ uint32_t opaque(uint32_t v) { return __shfl_sync(0xffffffffu, v, threadIdx.x); }
__device__ __forceinline__ bool elect() {
    uint32_t p;
    asm volatile("{.reg .pred q; elect.sync _|q, 0xffffffff; selp.u32 %0, 1, 0, q;}" : "=r"(p));
    return p;
}
__device__ __forceinline__ void tma2d(uint32_t dst, const CUtensorMap* m, uint32_t bar, int x, int y) {
    asm volatile(
        "cp.async.bulk.tensor.2d.shared::cluster.global.mbarrier::complete_tx::bytes [%0], [%1, {%3, %4}], [%2];" ::"r"(dst),
        "l"(m), "r"(bar), "r"(x), "r"(y)
        : "memory");
}
__device__ __forceinline__ void bulk(uint32_t dst, const void* src, uint32_t bytes, uint32_t bar) {
    asm volatile("cp.async.bulk.shared::cluster.global.mbarrier::complete_tx::bytes [%0], [%1], %2, [%3];" ::"r"(dst),
                 "l"(src), "r"(bytes), "r"(bar)
                 : "memory");
}
__device__ __forceinline__ void cp16(uint32_t dst, const void* src) {
    asm volatile("cp.async.cg.shared.global [%0], [%1], 16;" ::"r"(dst), "l"(src) : "memory");
}
__device__ __forceinline__ void lds128(uint32_t (&v)[4], uint32_t a) {
    asm volatile("ld.shared.v4.u32 {%0,%1,%2,%3}, [%4];" : "=r"(v[0]), "=r"(v[1]), "=r"(v[2]), "=r"(v[3]) : "r"(a) : "memory");
}
__device__ __forceinline__ void lds128_if(uint32_t (&v)[4], uint32_t a, uint32_t p) {
    asm volatile("{.reg .pred q; setp.ne.u32 q, %5, 0; @q ld.shared.v4.u32 {%0,%1,%2,%3}, [%4];}"
                 : "+r"(v[0]), "+r"(v[1]), "+r"(v[2]), "+r"(v[3])
                 : "r"(a), "r"(p)
                 : "memory");
}
__device__ __forceinline__ void lds64(uint32_t& x, uint32_t& y, uint32_t a) {
    asm volatile("ld.shared.v2.u32 {%0,%1}, [%2];" : "=r"(x), "=r"(y) : "r"(a) : "memory");
}
__device__ __forceinline__ void sts128(uint32_t a, uint32_t x, uint32_t y, uint32_t z, uint32_t w) {
    asm volatile("st.shared.v4.u32 [%0], {%1,%2,%3,%4};" ::"r"(a), "r"(x), "r"(y), "r"(z), "r"(w) : "memory");
}
__device__ __forceinline__ void sts64(uint32_t a, uint32_t x, uint32_t y) {
    asm volatile("st.shared.v2.u32 [%0], {%1,%2};" ::"r"(a), "r"(x), "r"(y) : "memory");
}
__device__ __forceinline__ uint32_t pack(float lo, float hi) {
    uint32_t r;
    asm volatile("cvt.rn.bf16x2.f32 %0, %1, %2;" : "=r"(r) : "f"(hi), "f"(lo));
    return r;
}
__device__ __forceinline__ uint32_t hmul2(uint32_t a, uint32_t b) {
    uint32_t r;
    asm volatile("mul.rn.bf16x2 %0, %1, %2;" : "=r"(r) : "r"(a), "r"(b));
    return r;
}
__device__ __forceinline__ uint32_t hfma2(uint32_t a, uint32_t b, uint32_t c) {
    uint32_t r;
    asm volatile("fma.rn.bf16x2 %0, %1, %2, %3;" : "=r"(r) : "r"(a), "r"(b), "r"(c));
    return r;
}
__device__ __forceinline__ float ffma(float a, float b, float c) {
    float r;
    asm volatile("fma.rn.f32 %0, %1, %2, %3;" : "=f"(r) : "f"(a), "f"(b), "f"(c));
    return r;
}
__device__ __forceinline__ float tanh_fast(float x) {
    float r;
    asm volatile("tanh.approx.f32 %0, %1;" : "=f"(r) : "f"(x));
    return r;
}
__device__ __forceinline__ float gelu_tanh(float x) {
    float r;
    asm volatile(
        "{.reg .f32 a; mul.f32 a, %1, %1; fma.rn.f32 a, a, 0f3D122279, 0f3F4C422A; mul.f32 a, a, %1; tanh.approx.f32 %0, a;}"
        : "=f"(r)
        : "f"(x));
    return r;
}
__device__ __forceinline__ uint32_t clock32() {
    uint32_t c;
    asm volatile("mov.u32 %0, %%clock;" : "=r"(c)::"memory");
    return c;
}
#define WG_FENCE() asm volatile("wgmma.fence.sync.aligned;" ::: "memory")
#define WG_COMMIT() asm volatile("wgmma.commit_group.sync.aligned;" ::: "memory")
#define WG_WAIT0() asm volatile("wgmma.wait_group.sync.aligned 0;" ::: "memory")
#define CP_COMMIT() asm volatile("cp.async.commit_group;" ::: "memory")
#define CP_WAIT(n) asm volatile("cp.async.wait_group %0;" ::"n"(n) : "memory")
#define SCHED_FENCE() mbar_wait_unless(one, sb + BAR_FULL, 0)
#define PROXY_FENCE() asm volatile("fence.proxy.async.shared::cta;" ::: "memory")
template <int N>
__device__ __forceinline__ void pin(float (&d)[N]) {
#pragma unroll
    for (int i = 0; i < N; i++) asm volatile("" : "+f"(d[i])::"memory");
}
#define TS(k)
#define TS_DUMP(role)

__device__ __forceinline__ void wgmma_ss_n168_acc(float (&d)[84], uint64_t da, uint64_t db) {
    asm volatile(
        "wgmma.mma_async.sync.aligned.m64n168k16.f32.bf16.bf16 "
        "{%0,%1,%2,%3,%4,%5,%6,%7,%8,%9,%10,%11,%12,%13,%14,%15,"
        "%16,%17,%18,%19,%20,%21,%22,%23,%24,%25,%26,%27,%28,%29,%30,%31,"
        "%32,%33,%34,%35,%36,%37,%38,%39,%40,%41,%42,%43,%44,%45,%46,%47,"
        "%48,%49,%50,%51,%52,%53,%54,%55,%56,%57,%58,%59,%60,%61,%62,%63,"
        "%64,%65,%66,%67,%68,%69,%70,%71,%72,%73,%74,%75,%76,%77,%78,%79,"
        "%80,%81,%82,%83}, "
        "%84, %85, 1, 1, 1, 0, 1;"
        : "+f"(d[0]), "+f"(d[1]), "+f"(d[2]), "+f"(d[3]), "+f"(d[4]), "+f"(d[5]), "+f"(d[6]), "+f"(d[7]),
          "+f"(d[8]), "+f"(d[9]), "+f"(d[10]), "+f"(d[11]), "+f"(d[12]), "+f"(d[13]), "+f"(d[14]), "+f"(d[15]),
          "+f"(d[16]), "+f"(d[17]), "+f"(d[18]), "+f"(d[19]), "+f"(d[20]), "+f"(d[21]), "+f"(d[22]), "+f"(d[23]),
          "+f"(d[24]), "+f"(d[25]), "+f"(d[26]), "+f"(d[27]), "+f"(d[28]), "+f"(d[29]), "+f"(d[30]), "+f"(d[31]),
          "+f"(d[32]), "+f"(d[33]), "+f"(d[34]), "+f"(d[35]), "+f"(d[36]), "+f"(d[37]), "+f"(d[38]), "+f"(d[39]),
          "+f"(d[40]), "+f"(d[41]), "+f"(d[42]), "+f"(d[43]), "+f"(d[44]), "+f"(d[45]), "+f"(d[46]), "+f"(d[47]),
          "+f"(d[48]), "+f"(d[49]), "+f"(d[50]), "+f"(d[51]), "+f"(d[52]), "+f"(d[53]), "+f"(d[54]), "+f"(d[55]),
          "+f"(d[56]), "+f"(d[57]), "+f"(d[58]), "+f"(d[59]), "+f"(d[60]), "+f"(d[61]), "+f"(d[62]), "+f"(d[63]),
          "+f"(d[64]), "+f"(d[65]), "+f"(d[66]), "+f"(d[67]), "+f"(d[68]), "+f"(d[69]), "+f"(d[70]), "+f"(d[71]),
          "+f"(d[72]), "+f"(d[73]), "+f"(d[74]), "+f"(d[75]), "+f"(d[76]), "+f"(d[77]), "+f"(d[78]), "+f"(d[79]),
          "+f"(d[80]), "+f"(d[81]), "+f"(d[82]), "+f"(d[83])
        : "l"(da), "l"(db));
}

__device__ __forceinline__ void wgmma_rs_n32_set(float (&d)[16], const uint32_t (&a)[4], uint64_t db) {
    asm volatile(
        "wgmma.mma_async.sync.aligned.m64n32k16.f32.bf16.bf16 "
        "{%0,%1,%2,%3,%4,%5,%6,%7,%8,%9,%10,%11,%12,%13,%14,%15}, "
        "{%16,%17,%18,%19}, %20, 0, 1, 1, 0;"
        : "=f"(d[0]), "=f"(d[1]), "=f"(d[2]), "=f"(d[3]), "=f"(d[4]), "=f"(d[5]), "=f"(d[6]), "=f"(d[7]),
          "=f"(d[8]), "=f"(d[9]), "=f"(d[10]), "=f"(d[11]), "=f"(d[12]), "=f"(d[13]), "=f"(d[14]), "=f"(d[15])
        : "r"(a[0]), "r"(a[1]), "r"(a[2]), "r"(a[3]), "l"(db));
}

__device__ __forceinline__ void wgmma_rs_n32_acc(float (&d)[16], const uint32_t (&a)[4], uint64_t db) {
    asm volatile(
        "wgmma.mma_async.sync.aligned.m64n32k16.f32.bf16.bf16 "
        "{%0,%1,%2,%3,%4,%5,%6,%7,%8,%9,%10,%11,%12,%13,%14,%15}, "
        "{%16,%17,%18,%19}, %20, 1, 1, 1, 0;"
        : "+f"(d[0]), "+f"(d[1]), "+f"(d[2]), "+f"(d[3]), "+f"(d[4]), "+f"(d[5]), "+f"(d[6]), "+f"(d[7]),
          "+f"(d[8]), "+f"(d[9]), "+f"(d[10]), "+f"(d[11]), "+f"(d[12]), "+f"(d[13]), "+f"(d[14]), "+f"(d[15])
        : "r"(a[0]), "r"(a[1]), "r"(a[2]), "r"(a[3]), "l"(db));
}

__device__ __forceinline__ void wgmma_rs_n16_set(float (&d)[8], const uint32_t (&a)[4], uint64_t db) {
    asm volatile(
        "wgmma.mma_async.sync.aligned.m64n16k16.f32.bf16.bf16 "
        "{%0,%1,%2,%3,%4,%5,%6,%7}, "
        "{%8,%9,%10,%11}, %12, 0, 1, 1, 0;"
        : "=f"(d[0]), "=f"(d[1]), "=f"(d[2]), "=f"(d[3]), "=f"(d[4]), "=f"(d[5]), "=f"(d[6]), "=f"(d[7])
        : "r"(a[0]), "r"(a[1]), "r"(a[2]), "r"(a[3]), "l"(db));
}

__device__ __forceinline__ void wgmma_rs_n16_acc(float (&d)[8], const uint32_t (&a)[4], uint64_t db) {
    asm volatile(
        "wgmma.mma_async.sync.aligned.m64n16k16.f32.bf16.bf16 "
        "{%0,%1,%2,%3,%4,%5,%6,%7}, "
        "{%8,%9,%10,%11}, %12, 1, 1, 1, 0;"
        : "+f"(d[0]), "+f"(d[1]), "+f"(d[2]), "+f"(d[3]), "+f"(d[4]), "+f"(d[5]), "+f"(d[6]), "+f"(d[7])
        : "r"(a[0]), "r"(a[1]), "r"(a[2]), "r"(a[3]), "l"(db));
}

__device__ __forceinline__ void wgmma_rs_n32_pred(float (&d)[16], const uint32_t (&a)[4], uint64_t db, uint32_t scale_d) {
    asm volatile(
        "{.reg .pred p; setp.ne.u32 p, %21, 0; wgmma.mma_async.sync.aligned.m64n32k16.f32.bf16.bf16 "
        "{%0,%1,%2,%3,%4,%5,%6,%7,%8,%9,%10,%11,%12,%13,%14,%15}, "
        "{%16,%17,%18,%19}, %20, p, 1, 1, 0;}"
        : "+f"(d[0]), "+f"(d[1]), "+f"(d[2]), "+f"(d[3]), "+f"(d[4]), "+f"(d[5]), "+f"(d[6]), "+f"(d[7]),
          "+f"(d[8]), "+f"(d[9]), "+f"(d[10]), "+f"(d[11]), "+f"(d[12]), "+f"(d[13]), "+f"(d[14]), "+f"(d[15])
        : "r"(a[0]), "r"(a[1]), "r"(a[2]), "r"(a[3]), "l"(db), "r"(scale_d));
}

__device__ __forceinline__ void prep_cta(uint32_t sb, int c, const __nv_bfloat16* __restrict__ wc,
                                         const __nv_bfloat16* __restrict__ se1, const __nv_bfloat16* __restrict__ se2) {
    const int tid = threadIdx.x, lane = tid & 31, warp = tid >> 5;
    constexpr int NROW = 2 * NF * NF;
#pragma unroll
    for (int q = tid; q < NROW * 2; q += 384) cp16(sb + q * 16, wc + (q >> 1) * ND + c * 16 + (q & 1) * 8);
    if (tid == 0) sts128(sb + NROW * 32, 0, 0, 0, 0);
    if (tid < 256) {
        const int q = c * 256 + tid, l2 = q >> 9;
        const int n = (q >> 3) & (l2 ? 31 : 15), k = (l2 ? ((q >> 8) & 1) : ((q >> 7) & 3)) * 8 + (q & 7);
        const int mm = (k & 15) >> 1, u = k & 1, ww = k >> 4;
        const int f = l2 ? fmap(n) : mm < 6 ? 4 * mm + 2 * ww + u : (mm == 6 && u == 0) ? 24 + ww : -1;
        float v = 0.f;
        if (f >= 0 && (l2 ? k : n) < NR) v = __bfloat162float(l2 ? se2[k * NF + f] : se1[f * NR + n]);
        reinterpret_cast<__nv_bfloat16*>(g_se)[q] = __float2bfloat16(l2 ? 0.5f * v : v);
    }
    asm volatile("cp.async.wait_all;" ::: "memory");
    __syncthreads();
    const int i = fmap(4 * (lane & 6) + 2 * (lane >> 3) + (lane & 1));
    const int g = lane >> 2, t = lane & 3;
#pragma unroll 4
    for (int task = warp; task < 128; task += 12) {
        const int eg = task & 1, n = (task >> 1) & 31, s = task >> 6;
        const int j = fmap(n);
        const uint32_t a = (i >= 0 && j >= 0) ? sb + ((s * NF + i) * NF + j) * 32 + eg * 16 : sb + NROW * 32;
        uint4 v;
        asm volatile("ldmatrix.sync.aligned.m8n8.x4.trans.shared.b16 {%0,%1,%2,%3}, [%4];"
                     : "=r"(v.x), "=r"(v.y), "=r"(v.z), "=r"(v.w)
                     : "r"(a));
        const int e = eg * 8 + g;
        if (t == 3) {
            const uint32_t mask = (e & 1) ? 0xffff0000u : 0xffffu;
            v.x &= mask;
            v.y &= mask;
        }
        const int ch = (t < 2 ? t ^ ((e >> 1) & 1) : t) ^ ((n >> 1) & 3);
        g_wc[(c >> 1) * 8192 + e * 512 + (c & 1) * 256 + s * 128 + n * 4 + ch] = v;
    }
    __threadfence();
    __syncthreads();
    if (tid == 0) atomicAdd(&g_ready, 1u);
}

#define P2_SKEW 120
#define TWARM 3
#define WPF_STEP 800
#define WDELAY 1600
#define WSTEP 500
#define PACE1 800
#define PACE2 1300
#define PF_START 2600
#define PF_PACE 550
#define WPF_AT 2000

__global__ void __cluster_dims__(2, 1, 1) __launch_bounds__(384, 1)
fibinet_kernel(const int* __restrict__ idx, const uint4* __restrict__ table,
               const __nv_bfloat16* __restrict__ se1, const __nv_bfloat16* __restrict__ se2,
               const __nv_bfloat16* __restrict__ wc,
               const unsigned char* __restrict__ w1, const __nv_bfloat16* __restrict__ w2, __nv_bfloat16* __restrict__ out,
               const __grid_constant__ CUtensorMap tm_w1, const __grid_constant__ CUtensorMap tm_bi) {
    extern __shared__ __align__(1024) unsigned char smem[];
    const uint32_t t_start = clock32();
    const int tid = threadIdx.x;
    const uint32_t sb = (uint32_t)__cvta_generic_to_shared(smem);
    if (blockIdx.x < NPREP) {
        prep_cta(sb, blockIdx.x, wc, se1, se2);
        return;
    }
    const int cta = blockIdx.x - NPREP, grp = cta >> 1, rank = cta & 1, lane = tid & 31;
    uint32_t ids[13][4], cid[3][2];
    uint32_t gd0 = 0;
    const uint4* tp = table + (lane & 7);
    auto gather = [&](int i) {
#pragma unroll
        for (int u = 0; u < 4; u++)
            asm volatile("{.reg .u64 a; mad.wide.u32 a, %2, 128, %1; cp.async.cg.shared.global [%0], [a], 16;}" ::"r"(
                             (gd0 ^ ((u & 1) * 64)) + xpair(i) + u * 512),
                         "l"(tp), "r"(ids[i][u])
                         : "memory");
        CP_COMMIT();
    };
    if (tid < 256) {
        const uint32_t w = tid >> 7, row = ((tid >> 5) & 3) * 16 + (lane >> 3);
        const int* ip = idx + ((grp * 64 + row) * NF + 2 * w);
#pragma unroll
        for (int u = 0; u < 4; u++)
            asm volatile("ld.global.nc.L2::128B.v2.u32 {%0,%1}, [%2];" : "=r"(ids[0][u]), "=r"(ids[1][u]) : "l"(ip + 4 * NF * u));
        const int* cp = idx + ((grp * 64 + ((tid & 127) >> 1)) * NF + 2 * w + 4 + 4 * (tid & 1));
#pragma unroll
        for (int k = 0; k < 3; k++)
            asm volatile("ld.global.nc.v2.u32 {%0,%1}, [%2];"
                         : "=r"(cid[k][0]), "=r"(cid[k][1])
                         : "l"(cp + 8 * k - (k == 2 ? 2 * (w & tid) : 0)));
        gd0 = sb + w * XDELTA + row * 128 + (((lane & 7) ^ (lane >> 3) ^ (4 * w)) << 4);
        gather(0);
    } else {
        if (tid == 256) asm volatile("prefetch.tensormap [%0];" ::"l"(&tm_w1));
        if (tid == 288) asm volatile("prefetch.tensormap [%0];" ::"l"(&tm_bi));
    }
    const uint32_t c0 = clock32();
    const int warp = __reduce_max_sync(0xffffffffu, tid >> 5);
    const int w = warp >> 2;

    if (w == 2) {
        asm volatile("setmaxnreg.dec.sync.aligned.u32 40;");
        if (warp == 8) {
            if (elect()) {
                mbar_init(sb + BAR_Z, 1);
                mbar_expect(sb + BAR_Z, 8192);
                tma2d(sb + ZOFF, &tm_bi, sb + BAR_Z, 32 * rank, 0);
            }
#pragma unroll
            for (int f = 0; f < 26; f++) {
                if (f == 2) {
                    if (elect()) {
#pragma unroll
                        for (int k = 2; k < 8; k++) mbar_init(sb + BAR_FULL + k * 8, 1);
                        asm volatile("fence.mbarrier_init.release.cluster;" ::: "memory");
                    }
                    __syncwarp();
                    asm volatile("barrier.cluster.arrive.relaxed.aligned;" ::: "memory");
                    mbar_wait(sb + BAR_Z);
#pragma unroll
                    for (int k = 0; k < 2; k++)
                        sts128(sb + ZOFF + (k * 32 + lane) * 128 + ((4 ^ (lane & 7)) << 4), 0x3c803c80u, 0x3c803c80u, 0x3c803c80u, 0x3c803c80u);
                    PROXY_FENCE();
                    asm volatile("bar.arrive 0, 384;" ::: "memory");
                    TS(31);
                }
                if (f == 5) asm volatile("barrier.cluster.wait.aligned;" ::: "memory");
                if (f >= 5) mbar_wait(sb + bdone(f - 5), bpar(f - 5));
                if (f >= 2 && f < 5)
                    while (clock32() - t_start < WDELAY + (f - 2) * WSTEP) {
                    }
                if (elect()) {
                    if (f < 2) mbar_init(sb + BAR_FULL + f * 8, 1);
                    mbar_expect(sb + bfull(f), 16384);
                    tma2d(sb + slot(2 * wl(f)), &tm_w1, sb + bfull(f), 128 * rank + 64 * (f & 1), fieldof(f) * 64);
                    tma2d(sb + slot(wl(f)), &tm_w1, sb + bfull(f), 128 * rank + 64 - 64 * (f & 1), fieldof(f) * 64);
                }
                TS(f);
            }
            if (elect()) mbar_arrive(sb + BAR_GO);
            TS_DUMP(2);
        } else if (warp == 9) {
            if (elect()) {
#pragma unroll
                for (int k = 0; k < 10; k++) mbar_init(sb + BAR_WC + k * 8, k < 8 ? 1 : k == 8 ? 2 : 8);
                asm volatile("fence.mbarrier_init.release.cluster;" ::: "memory");
                mbar_expect(sb + BAR_FIN, 512);
            }
            __syncwarp();
            asm volatile("barrier.cluster.arrive.relaxed.aligned;" ::: "memory");
            asm volatile("bar.sync 0, 384;" ::: "memory");
            mbar_wait(sb + bdone(3), bpar(3));
            const unsigned char* src = reinterpret_cast<const unsigned char*>(g_wc) + rank * 131072;
            if (elect()) {
                unsigned v, it = 0;
                do {
                    asm volatile("ld.acquire.gpu.global.u32 %0, [%1];" : "=r"(v) : "l"(&g_ready) : "memory");
                } while (v < NPREP && ++it < 4000000u);
                asm volatile("fence.proxy.async.global;" ::: "memory");
                mbar_expect(sb + BAR_SE, 2048);
                bulk(sb + SEOFF, g_se, 2048, sb + BAR_SE);
            }
            __syncwarp();
            TS(0);
            mbar_wait(sb + BAR_GO);
#pragma unroll
            for (int gi = 0; gi < 6; gi++) {
                const int c0 = wcfirst(gi), c1 = wcfirst(gi + 1);
                if (gi < 4) mbar_wait(sb + bdone(21 + gi), bpar(21 + gi));
                if (gi == 3) mbar_wait(sb + bdone(25), bpar(25));
                if (gi == 4) mbar_wait(sb + BAR_TD);
                if (elect()) {
                    mbar_expect(sb + BAR_WC + gi * 8, (c1 - c0) * 8192);
#pragma unroll
                    for (int c = c0; c < c1; c++) bulk(sb + wcslot(c), src + c * 8192, 8192, sb + BAR_WC + gi * 8);
                }
                TS(1 + gi);
            }
            __syncwarp();
            if (lane < 16) TS_DUMP(3);
            if (elect() && atomicAdd(&g_seen, 1u) == NMAIN - 1) {
                g_seen = 0;
                g_ready = 0;
            }
        } else if (warp == 10) {
            if (elect()) {
#pragma unroll
                for (int k = 0; k < 8; k++) mbar_init(sb + BAR_DONE + k * 8, 4);
                asm volatile("fence.mbarrier_init.release.cluster;" ::: "memory");
            }
            __syncwarp();
            asm volatile("barrier.cluster.arrive.relaxed.aligned;" ::: "memory");
            asm volatile("bar.arrive 0, 384;" ::: "memory");
#pragma unroll 1
            for (int k = 0; k < 7; k++) {
                while (clock32() - t_start < (uint32_t)(WPF_AT + k * WPF_STEP)) __nanosleep(20);
                if (lane < 6)
                    asm volatile("prefetch.global.L2 [%0];" ::"l"(w1 + (5 + k * 3 + (lane >> 1)) * 32768 + cta * 256 + (lane & 1) * 128));
            }
        } else {
            asm volatile("barrier.cluster.arrive.relaxed.aligned;" ::: "memory");
            asm volatile("bar.sync 0, 384;" ::: "memory");
            const uint2 v = __ldg(reinterpret_cast<const uint2*>(w2 + 128 * rank) + lane);
#pragma unroll
            for (int k = 0; k < 2; k++) {
                const uint32_t x = k ? v.y : v.x;
                sts64(sb + w2chunk((lane >> 2) * 4 + 2 * (lane & 1) + k) + (lane & 2) * 4,
                      __float_as_uint(0.5f * __uint_as_float(x << 16)), __float_as_uint(0.5f * __uint_as_float(x & 0xffff0000u)));
            }
            __syncwarp();
            if (lane == 0) mbar_arrive(sb + BAR_SE);
        }
        if (warp != 8) asm volatile("barrier.cluster.wait.aligned;" ::: "memory");
    } else {
        asm volatile("setmaxnreg.inc.sync.aligned.u32 232;");
        asm volatile("barrier.cluster.arrive.relaxed.aligned;" ::: "memory");
        const int g = lane >> 2, t = lane & 3, wq = warp & 3, t128 = tid & 127;
        gd0 = opaque(gd0);
        TS(28);
        float acc[84];
#pragma unroll
        for (int k = 0; k < 84; k++) asm volatile("mov.b32 %0, 0;" : "=f"(acc[k]));
        uint32_t e0[9], e1[9], e2[9];
        uint32_t X[14][2][4];
        uint32_t zq[4] = {0, 0, 0, 0};
        const uint64_t dA = mkdesc(sb + w * XDELTA, 16, 1024, 1);
        uint32_t dBlo = (uint32_t)mkdesc(sb + ZOFF, 0, 0, 0);
        const uint32_t xl0 = opaque(sb + (t & 1) * XDELTA + (16 * wq + g) * 128 + (((4 * rank + 2 * w) ^ (4 * (t & 1)) ^ g) << 4));
        const uint32_t hi_half = t >> 1;
        const uint32_t sa0 = opaque(sb + AOFF + t * 4096 + (t >> 1) * 16 + (wq * 32 + g * 4 + w) * 16);
        const uint32_t sa1 = opaque(((g & 2) << 4) | ((t & 1) << 3));
        const uint32_t zero = blockIdx.y, one = zero + 1;
        auto expand = [&](int k0, int k1) {
#pragma unroll
            for (int k = k0; k < k1; k++)
#pragma unroll
                for (int u = 0; u < 4; u++)
                    asm volatile("shfl.sync.idx.b32 %0, %1, %2, 31, 0xffffffff;"
                                 : "=r"(ids[k][u])
                                 : "r"(k < 12 ? cid[(k - 2) >> 2][k & 1] : w ? cid[2][1] : cid[2][0]),
                                   "r"(2 * (lane >> 3) + 8 * u + (((k - 2) >> 1) & 1)));
        };
        auto twarm = [&]() {
            float s1[8];
            WG_FENCE();
            wgmma_rs_n16_set(s1, zq, mkdesc(sb + AOFF, 16, 512, 2));
            WG_COMMIT();
            WG_WAIT0();
            pin(s1);
            asm volatile("{.reg .pred p; setp.ne.u32 p, %1, 0; @p st.shared.f32 [%1], %0;}" ::"f"(s1[0]), "r"(zero));
        };
        expand(2, 8);
        if (TWARM & 1) twarm();
        TS(26);
        while (clock32() - c0 < PACE1) {
        }
        gather(1);
        expand(8, 13);
        if (TWARM & 2) twarm();
        TS(30);
        while (clock32() - c0 < PACE2) {
        }
        gather(2);
        if (TWARM & 4) twarm();
        asm volatile("bar.sync 0, 384;" ::: "memory");
        auto lift = [&](int i) {
            const int m = 2 * (i >> 2) + (i & 1);
#pragma unroll
            for (int r = 0; r < 2; r++)
#pragma unroll
                for (int cc = 0; cc < 2; cc++) {
                    const uint32_t a = (xl0 ^ (cc * 16)) + xpair(i) + r * 1024;
                    if (i & 2) lds128_if(X[2 * m + r][cc], a, hi_half);
                    else lds128(X[2 * m + r][cc], a);
                }
        };
        auto store_pair = [&](int m, int half, const uint32_t (&ea)[9]) {
            uint32_t a;
            if (m < 4) a = sa0 + (sa1 ^ (((m & 1) << 5) | ((m >> 1) << 3)));
            else a = sb + BOFF + t * 2048 + (wq * 32 + g * 4 + ((2 * (m & 1) + w) ^ t)) * 8;
#pragma unroll
            for (int n = half; n < 4; n += 2)
#pragma unroll
                for (int u = 0; u < 2; u++)
                    sts64(a + (m < 4 ? (8 * n + u) * 2048 + n * 32 : (8 * n + u) * 1024),
                          __byte_perm(ea[2 * n], e1[2 * n], u ? 0x7632 : 0x5410),
                          __byte_perm(ea[2 * n + 1], e1[2 * n + 1], u ? 0x7632 : 0x5410));
        };
        auto z_pair = [&](int m, uint32_t a, uint32_t b) {
            asm volatile("{.reg .pred p; setp.eq.u32 p, %4, %5; @p prmt.b32 %0, %2, %3, 0x5410; @p prmt.b32 %1, %2, %3, 0x7632;}"
                         : "+r"(zq[2 * (m >> 2)]), "+r"(zq[2 * (m >> 2) + 1])
                         : "r"(a), "r"(b), "r"(t), "r"(m & 3));
        };

        TS(29);
        mbar_wait(sb + BAR_FULL + w * 8);
        CP_WAIT(2);
        if (w == 1) {
            asm volatile("bar.arrive 3, 256;" ::: "memory");
            asm volatile("bar.sync 2, 256;" ::: "memory");
        }
#pragma unroll
        for (int i = 0; i < 13; i++) {
            const uint64_t da = dA + (xpair(i) >> 4) + ((uint64_t)i << 16);
            dBlo += (uint32_t)(w ? wl(2 * i + 1) - (i ? wl(2 * i - 1) : 0) : wl(2 * i) - (i ? wl(2 * i - 2) : 0)) *
                    (uint32_t)((SLOT << 12) - (SLOT >> 3));
            const uint64_t db = mkdesc(0, 0, 1024, 1) | dBlo;
            TS(i);
            WG_FENCE();
            wgmma_ss_n168_acc(acc, da, db + w * 256);
            wgmma_ss_n168_acc(acc, da + 2, db + w * 256 + 128);
            wgmma_ss_n168_acc(acc, da + 4, db + (w ^ 1) * 256);
            wgmma_ss_n168_acc(acc, da + 6, db + (w ^ 1) * 256 + 128);
            WG_COMMIT();
            if (i == 0) {
                if (w == 0) {
                    asm volatile("bar.arrive 2, 256;" ::: "memory");
                    asm volatile("bar.sync 3, 256;" ::: "memory");
                }
            } else {
                mbar_wait(sb + bdone(2 * i - 2) + (w ^ 1) * 8, bpar(2 * i - 2));
            }
            if (i < 10) gather(i + 3);
            if (i == 1) asm volatile("barrier.cluster.wait.aligned;" ::: "memory");
            lift(i);
            if (i == 10 || i == 11) mbar_wait(sb + bdone(2 * i - 2) + w * 8, bpar(2 * i - 2));
            if (i >= 2 && !(i & 1)) {
                z_pair((i - 2) >> 1, e0[8], e1[8]);
                store_pair((i - 2) >> 1, 0, e0);
#pragma unroll
                for (int k = 0; k < 8; k++) e2[k] = e0[k];
            } else if (i >= 3) {
                store_pair((i - 3) >> 1, 1, e2);
            }
            const uint32_t rdy = i < 12 ? mbar_test(sb + bfull(2 * i + 2) + w * 8, bpar(2 * i + 2)) : mbar_test(sb + BAR_SE, 0);
            WG_WAIT0();
            pin(acc);
            if (i == 12) TS(13);
            if (i == 0) TS(27);
            if (i < 10) CP_WAIT(2);
            else if (i == 10) CP_WAIT(1);
            else if (i == 11) CP_WAIT(0);
            if (lane == 0) mbar_arrive(sb + bdone(2 * i) + w * 8);
#pragma unroll
            for (int k = 0; k < 9; k++) {
                const uint32_t v = k < 8 ? pack(acc[64 + 2 * k], acc[65 + 2 * k]) : pack(acc[80], acc[82]);
                if (i & 1) e1[k] = v;
                else e0[k] = v;
            }
            if (i < 12) {
#pragma unroll
                for (int k = 64; k < 83; k++)
                    if (k != 81) asm volatile("mov.b32 %0, %1;" : "+f"(acc[k]) : "r"(zero));
                mbar_wait_unless(rdy, sb + bfull(2 * i + 2) + w * 8, bpar(2 * i + 2));
            } else {
                z_pair(6, e0[8], 0);
                sts128(sb + ZQOFF + w * 2048 + t128 * 16, zq[0], zq[1], zq[2], zq[3]);
                mbar_wait_unless(rdy, sb + BAR_SE, 0);
            }
        }
        TS(14);

        float aj[14];
        uint32_t ai[8];
        float sum0 = 0.f, sum1 = 0.f;
        float th[32];
        uint32_t hw[4][4];
        auto deep_issue = [&](int k2) {
            lds128(hw[k2], ((sb + w2chunk(w * 16 + t)) ^ ((k2 & 1) * 64)) + k2 * 512);
#pragma unroll
            for (int k = 8 * k2; k < 8 * k2 + 8; k++) th[k] = gelu_tanh(acc[k]);
        };
        auto deep_use = [&](int k2) {
#pragma unroll
            for (int k = 8 * k2; k < 8 * k2 + 8; k++) {
                const float h = __uint_as_float(hw[k2][((k >> 1) & 2) + (k & 1)]);
                const float y = ffma(th[k], h, h);
                if (k & 2) sum1 = ffma(acc[k], y, sum1);
                else sum0 = ffma(acc[k], y, sum0);
            }
        };
        auto deep_send = [&](int k0, int k1) {
            const uint32_t a = sb + ZOFF - (w ? wl(25) : wl(24)) * SLOT + t128 * 16;
#pragma unroll
            for (int k = k0 >> 1; k < k1 >> 1; k++)
                sts128(a + k * 2048, pack(acc[32 + 8 * k], acc[33 + 8 * k]), pack(acc[34 + 8 * k], acc[35 + 8 * k]),
                       pack(acc[36 + 8 * k], acc[37 + 8 * k]), pack(acc[38 + 8 * k], acc[39 + 8 * k]));
        };
        uint32_t o[4][4];
        auto deep_recv = [&](int k0, int k1) {
            const uint32_t a = sb + ZOFF - (w ? wl(24) : wl(25)) * SLOT + t128 * 16;
#pragma unroll
            for (int k = k0 >> 1; k < k1 >> 1; k++) lds128(o[k], a + k * 2048);
        };
        auto deep_add = [&](int k0, int k1) {
#pragma unroll
            for (int k = 4 * k0; k < 4 * k1; k++) {
                const uint32_t x = o[k >> 3][(k >> 1) & 3];
                asm volatile("add.f32 %0, %0, %1;" : "+f"(acc[k]) : "r"((k & 1) ? x & 0xffff0000u : x << 16));
            }
        };
        auto store_last = [&]() {
#pragma unroll
            for (int n = 0; n < 4; n++) sts64(sb + COFF + w * 4096 + n * 1024 + (t128 ^ w) * 8, e0[2 * n], e0[2 * n + 1]);
            store_pair(5, 1, e2);
        };
        const uint32_t la = sb + AOFF + w * (16 * 2048 + 64) + (wq * 32 + g * 4 + (t ^ (g & 2))) * 16;
        const uint32_t lb = sb + BOFF + w * (16 * 1024) + t128 * 8;
        const uint32_t lc0 = sb + COFF + (t & 1) * (4096 + 8) + w * 2048 + (wq * 8 + g) * 32, lc1 = lc0 ^ 8;
        uint32_t Ap[2][2][4];
        auto load_a = [&](int e) {
            lds128(Ap[e & 1][0], la + e * 2048 + (e >> 2) * 16);
            lds64(Ap[e & 1][1][0], Ap[e & 1][1][1], (lb ^ ((e & 6) * 4)) + e * 1024);
            lds64(Ap[e & 1][1][2], Ap[e & 1][1][3], ((e & 2) ? lc1 : lc0) + (e >> 3) * 1024 + (e & 4) * 4);
        };
        {
            const uint64_t dS1 = mkdesc(sb + SEOFF, 256, 128, 0), dS2 = mkdesc(sb + SEOFF + 1024, 512, 128, 0);
            if (w == 0) store_last();
            asm volatile("bar.sync 1, 256;" ::: "memory");
            uint32_t zo[4];
            lds128(zo, sb + ZQOFF + (w ^ 1) * 2048 + t128 * 16);
            TS(15);
            deep_send(0, 4);
            float s1[8];
            WG_FENCE();
            wgmma_rs_n16_set(s1, zq, dS1 + w * 32);
            wgmma_rs_n16_acc(s1, zo, dS1 + (w ^ 1) * 32);
            WG_COMMIT();
            asm volatile("bar.sync 2, 256;" ::: "memory");
            WG_WAIT0();
            pin(s1);
            float t1[8];
#pragma unroll
            for (int k = 0; k < 8; k++) t1[k] = gelu_tanh(s1[k]);
            SCHED_FENCE();
            TS(16);
            deep_recv(0, 2);
            deep_send(4, 8);
            uint32_t gq[4];
#pragma unroll
            for (int k = 0; k < 4; k++)
                gq[k] = pack(s1[2 * k] * ffma(t1[2 * k], 0.5f, 0.5f), s1[2 * k + 1] * ffma(t1[2 * k + 1], 0.5f, 0.5f));
            float s2[16];
            WG_FENCE();
            wgmma_rs_n32_set(s2, gq, dS2);
            WG_COMMIT();
            deep_add(0, 2);
            deep_issue(0);
            deep_recv(2, 4);
            if (w == 1) store_last();
            asm volatile("bar.sync 1, 256;" ::: "memory");
            TS(17);
            WG_WAIT0();
            pin(s2);
#pragma unroll
            for (int q = 0; q < 14; q++) aj[q] = tanh_fast(s2[4 * (q >> 2) + 2 * (q & 1) + ((q >> 1) & 1)]);
            deep_use(0);
            deep_add(2, 4);
            deep_recv(4, 8);
            SCHED_FENCE();
            TS(18);
            deep_issue(1);
            deep_add(4, 8);
            deep_issue(2);
            load_a(0);
#pragma unroll
            for (int q = 0; q < 14; q++) aj[q] = ffma(aj[q], 0.5f, 0.5f);
#pragma unroll
            for (int k = 0; k < 8; k++) ai[k] = pack(aj[4 * (k >> 1) + (k & 1)], aj[k < 6 ? 4 * (k >> 1) + (k & 1) + 2 : 6 + k]);
            mbar_wait(sb + BAR_WC);
        }
        TS(19);

        {
            const uint64_t dW = mkdesc(sb + w * 4096, 16, 512, 2);
            uint32_t Aq[2][2][4], hacc[4], V[14];
            float Sp[16], Sq[16], U[14];
            auto scale_a = [&](int e) {
#pragma unroll
                for (int k = 0; k < 8; k++) Aq[e & 1][k >> 2][k & 3] = hmul2(Ap[e & 1][k >> 2][k & 3], ai[k < 4 ? k ^ (e & 2) : k]);
            };
            auto dot = [&](int e) {
#pragma unroll
                for (int q = 0; q < 14; q++) {
                    const uint32_t x = X[q][e >> 3][(e & 7) >> 1];
                    if ((e & 6) == 0 && q < 4) hacc[q] = hmul2(V[q], x);
                    else hacc[q & 3] = hfma2(V[q], x, hacc[q & 3]);
                }
            };
            auto flush = [&]() {
                sum0 += (__uint_as_float(hacc[0] << 16) + __uint_as_float(hacc[0] & 0xffff0000u)) +
                        (__uint_as_float(hacc[2] << 16) + __uint_as_float(hacc[2] & 0xffff0000u));
                sum1 += (__uint_as_float(hacc[1] << 16) + __uint_as_float(hacc[1] & 0xffff0000u)) +
                        (__uint_as_float(hacc[3] << 16) + __uint_as_float(hacc[3] & 0xffff0000u));
            };
            deep_issue(3);
            deep_use(1);
            deep_use(2);
            scale_a(0);
            load_a(1);
            if (w == 1) {
                const uint32_t c1 = clock32();
                while (clock32() - c1 < P2_SKEW) {
                }
            }
#pragma unroll
            for (int e = 0; e < 16; e++) {
                const uint64_t d = dW + (wcslot(e) >> 4);
                WG_FENCE();
                if (e == 0) wgmma_rs_n32_set(Sp, Ap[e & 1][0], d);
                else wgmma_rs_n32_pred(Sp, Ap[e & 1][0], d, zero);
                wgmma_rs_n32_acc(Sp, Ap[e & 1][1], d + 2);
                if (e == 0) wgmma_rs_n32_set(Sq, Aq[e & 1][0], d + 128);
                else wgmma_rs_n32_pred(Sq, Aq[e & 1][0], d + 128, zero);
                wgmma_rs_n32_acc(Sq, Aq[e & 1][1], d + 130);
                WG_COMMIT();
                SCHED_FENCE();
                if (e == 0) deep_use(3);
                if (e > 0 && !(e & 1)) dot(e - 1);
                if (e == 9) flush();
                if (e + 1 < 16) scale_a(e + 1);
                if (e == 0 || e == 2 || e == 6 || e == 8 || e == 12)
                    mbar_wait(sb + BAR_WC + (e == 0 ? 1 : e == 2 ? 2 : e == 6 ? 3 : e == 8 ? 4 : 5) * 8);
                else
                    SCHED_FENCE();
                WG_WAIT0();
                pin(Sp);
                pin(Sq);
                if (e == 0 && lane == 0) mbar_arrive(sb + BAR_TD);
                if (e == 0) TS(20);
                if (e + 2 < 16) load_a(e + 2);
#pragma unroll
                for (int q = 0; q < 14; q++) {
                    const int ix = 4 * (q >> 2) + 2 * (q & 1) + ((q >> 1) & 1);
                    const float u = ffma(aj[q], Sq[ix], Sp[ix]);
                    if (!(e & 1)) U[q] = u;
                    else V[q] = pack(U[q], u);
                }
                if (e == 7) TS(21);
            }
            dot(15);
            flush();
        }
        TS(22);
        {
            float v = (t & 1) ? sum1 : sum0;
            v += __shfl_xor_sync(0xffffffffu, (t & 1) ? sum0 : sum1, 1);
            v += __shfl_xor_sync(0xffffffffu, v, 2);
            if (t < 2) {
                uint32_t ra, rb;
                asm("mapa.shared::cluster.u32 %0, %1, %2;"
                    : "=r"(ra)
                    : "r"(sb + PARTOFF + (((wq & 1) * 16 + t * 8 + g) * 4 + 2 * rank + w) * 4), "r"(wq >> 1));
                asm("mapa.shared::cluster.u32 %0, %1, %2;" : "=r"(rb) : "r"(sb + BAR_FIN), "r"(wq >> 1));
                asm volatile("st.async.shared::cluster.mbarrier::complete_tx::bytes.f32 [%0], %1, [%2];" ::"r"(ra), "f"(v), "r"(rb)
                             : "memory");
            }
            if (warp == 0) {
                mbar_wait(sb + BAR_FIN);
                uint32_t p[4];
                lds128(p, sb + PARTOFF + lane * 16);
                out[(blockIdx.x - NPREP) * 32 + lane] = __float2bfloat16((__uint_as_float(p[0]) + __uint_as_float(p[1])) +
                                                                    (__uint_as_float(p[2]) + __uint_as_float(p[3])));
            }
            if (wq == 0) TS_DUMP(w);
        }
    }
}

typedef CUresult (*EncodeFn)(CUtensorMap*, CUtensorMapDataType, cuuint32_t, void*, const cuuint64_t*, const cuuint64_t*,
                             const cuuint32_t*, const cuuint32_t*, CUtensorMapInterleave, CUtensorMapSwizzle,
                             CUtensorMapL2promotion, CUtensorMapFloatOOBfill);

}

extern "C" void kernel_launch(void* const* d_in, const int* in_sizes, int n_in, void* d_out, int out_size) {
    static EncodeFn encode = nullptr;
    if (!encode) {
        void* fn = nullptr;
        cudaDriverEntryPointQueryResult qr;
        cudaGetDriverEntryPoint("cuTensorMapEncodeTiled", &fn, cudaEnableDefault, &qr);
        encode = (EncodeFn)fn;
        cudaFuncSetAttribute(fibinet_kernel, cudaFuncAttributeMaxDynamicSharedMemorySize, SMEM_BYTES);
    }
    CUtensorMap tm;
    const cuuint64_t gd[2] = {NH, NF * ND};
    const cuuint64_t gs[1] = {NH * 2};
    const cuuint32_t bd[2] = {64, 64}, es[2] = {1, 1};
    encode(&tm, CU_TENSOR_MAP_DATA_TYPE_BFLOAT16, 2, d_in[6], gd, gs, bd, es, CU_TENSOR_MAP_INTERLEAVE_NONE,
           CU_TENSOR_MAP_SWIZZLE_128B, CU_TENSOR_MAP_L2_PROMOTION_L2_256B, CU_TENSOR_MAP_FLOAT_OOB_FILL_NONE);
    CUtensorMap tb;
    const cuuint64_t gd2[2] = {ND, ND};
    const cuuint64_t gs2[1] = {ND * 2};
    encode(&tb, CU_TENSOR_MAP_DATA_TYPE_BFLOAT16, 2, d_in[4], gd2, gs2, bd, es, CU_TENSOR_MAP_INTERLEAVE_NONE,
           CU_TENSOR_MAP_SWIZZLE_128B, CU_TENSOR_MAP_L2_PROMOTION_L2_256B, CU_TENSOR_MAP_FLOAT_OOB_FILL_NONE);
    fibinet_kernel<<<NPREP + NMAIN, 384, SMEM_BYTES>>>(
        (const int*)d_in[0], (const uint4*)d_in[1], (const __nv_bfloat16*)d_in[2], (const __nv_bfloat16*)d_in[3],
        (const __nv_bfloat16*)d_in[5], (const unsigned char*)d_in[6], (const __nv_bfloat16*)d_in[7], (__nv_bfloat16*)d_out, tm, tb);
}
```

```cpp
#include <cuda_runtime.h>
#include <cuda_bf16.h>
#include <cuda.h>
#include <stdint.h>

namespace {

constexpr int NB = 4096, NF = 26, ND = 64, NH = 256, NR = 13;
constexpr int NPREP = 4;
constexpr int NMAIN = 128;

constexpr int SLOT = 8192;
constexpr int ZOFF = 15 * SLOT;
__host__ __device__ constexpr int slot(int s) { return ZOFF - s * SLOT; }
constexpr int BOFF = ZOFF + SLOT;
constexpr int AOFF = BOFF + 32768;
constexpr int COFF = slot(12);
constexpr int MOFF = AOFF + 65536 + 128;
constexpr int BAR_FULL = MOFF, BAR_DONE = MOFF + 64, BAR_WC = MOFF + 128, BAR_FIN = MOFF + 176,
              BAR_GO = MOFF + 184, BAR_SE = MOFF + 192, BAR_W2 = MOFF + 200, BAR_TD = MOFF + 208, BAR_Z = MOFF + 216;
__host__ __device__ constexpr int bfull(int f) { return BAR_FULL + (f & 7) * 8; }
__host__ __device__ constexpr int bdone(int f) { return BAR_DONE + (f & 7) * 8; }
__host__ __device__ constexpr int bpar(int f) { return (f >> 3) & 1; }
constexpr int PARTOFF = MOFF + 256, SEOFF = MOFF + 768;
constexpr int SMEM_BYTES = MOFF + 2944;
constexpr int XDELTA = 2 * SLOT;
__host__ __device__ constexpr int xpair(int i) {
    return (i & 3) == 0 ? slot(11) : (i & 3) == 1 ? BOFF : (i & 3) == 2 ? BOFF + SLOT : slot(15);
}
__host__ __device__ constexpr int wl(int f) { return f % 5 == 0 ? 1 : f % 5 == 4 ? 7 : f % 5 + 2; }
__host__ __device__ constexpr int wcslot(int c) {
    return c == 0 ? slot(3) : c == 1 ? slot(8) : c == 2 ? slot(10) : c == 3 ? slot(15) : c == 4 ? slot(13)
         : c == 5 ? slot(11) : c == 6 ? slot(9) : c == 7 ? slot(14) : c == 8 ? slot(7) : c == 9 ? slot(2)
         : c == 10 ? slot(1) : c == 11 ? slot(4) : c == 12 ? slot(5) : c == 13 ? slot(6) : c == 14 ? ZOFF : slot(3);
}
__host__ __device__ constexpr int wcfirst(int gi) { return gi < 3 ? gi : gi == 3 ? 5 : gi == 4 ? 8 : gi == 5 ? 11 : 16; }
constexpr int EXOFF = slot(5);
constexpr int ZQOFF = slot(6);
constexpr int GOFF = ZQOFF + 4096;
__host__ __device__ constexpr int w2chunk(int c) { return ZOFF + c * 128 + ((5 ^ (c & 7)) << 4); }

__device__ uint4 g_wc[2 * 16 * 8192 / 16];
__device__ uint4 g_se[2048 / 16];
__device__ unsigned g_ready;
__device__ unsigned g_seen;

__host__ __device__ constexpr int fieldof(int f) { return f < 24 ? 4 * (f >> 2) + 2 * (f & 1) + ((f >> 1) & 1) : f; }
__device__ __forceinline__ int fmap(int n) { return n < 24 ? n : n < 28 ? 24 + ((n >> 1) & 1) : -1; }

__device__ __forceinline__ uint64_t mkdesc(uint32_t addr, uint32_t lbo, uint32_t sbo, int sw) {
    return (uint64_t)((addr & 0x3ffff) >> 4) | ((uint64_t)(lbo >> 4) << 16) | ((uint64_t)(sbo >> 4) << 32) |
           ((uint64_t)sw << 62);
}
__device__ __forceinline__ void mbar_init(uint32_t b, uint32_t n) {
    asm volatile("mbarrier.init.shared.b64 [%0], %1;" ::"r"(b), "r"(n) : "memory");
}
__device__ __forceinline__ void mbar_wait(uint32_t b, uint32_t par = 0) {
    asm volatile(
        "{\n.reg .pred p, q;\n.reg .u32 n;\n"
        "mbarrier.try_wait.parity.shared.b64 p, [%0], %1;\n@p bra.uni WD%=;\nmov.u32 n, 0;\n"
        "WL%=:\nmbarrier.try_wait.parity.shared.b64 p, [%0], %1;\n@p bra.uni WD%=;\n"
        "add.u32 n, n, 1;\nsetp.lt.u32 q, n, 4000000;\n@q bra.uni WL%=;\nWD%=:\n}\n" ::"r"(b), "r"(par)
        : "memory");
}
__device__ __forceinline__ uint32_t mbar_test(uint32_t b, uint32_t par) {
    uint32_t ok;
    asm volatile("{.reg .pred p; mbarrier.test_wait.parity.shared.b64 p, [%1], %2; selp.u32 %0, 1, 0, p;}"
                 : "=r"(ok)
                 : "r"(b), "r"(par)
                 : "memory");
    return ok;
}
__device__ __forceinline__ void mbar_wait_unless(uint32_t ok, uint32_t b, uint32_t par) {
    asm volatile(
        "{\n.reg .pred p, q;\n.reg .u32 n;\n"
        "setp.ne.u32 p, %1, 0;\n@p bra.uni WD%=;\nmov.u32 n, 0;\n"
        "WL%=:\nmbarrier.try_wait.parity.shared.b64 p, [%0], %2;\n@p bra.uni WD%=;\n"
        "add.u32 n, n, 1;\nsetp.lt.u32 q, n, 4000000;\n@q bra.uni WL%=;\nWD%=:\n}\n" ::"r"(b), "r"(ok), "r"(par)
        : "memory");
}
__device__ __forceinline__ void mbar_arrive(uint32_t b) {
    asm volatile("mbarrier.arrive.shared.b64 _, [%0];" ::"r"(b) : "memory");
}
__device__ __forceinline__ void mbar_expect(uint32_t b, uint32_t bytes) {
    asm volatile("mbarrier.arrive.expect_tx.shared.b64 _, [%0], %1;" ::"r"(b), "r"(bytes) : "memory");
}
__device__ __forceinline__ uint32_t opaque(uint32_t v) { return __shfl_sync(0xffffffffu, v, threadIdx.x); }
__device__ __forceinline__ bool elect() {
    uint32_t p;
    asm volatile("{.reg .pred q; elect.sync _|q, 0xffffffff; selp.u32 %0, 1, 0, q;}" : "=r"(p));
    return p;
}
__device__ __forceinline__ void tma2d(uint32_t dst, const CUtensorMap* m, uint32_t bar, int x, int y) {
    asm volatile(
        "cp.async.bulk.tensor.2d.shared::cluster.global.mbarrier::complete_tx::bytes [%0], [%1, {%3, %4}], [%2];" ::"r"(dst),
        "l"(m), "r"(bar), "r"(x), "r"(y)
        : "memory");
}
__device__ __forceinline__ void bulk(uint32_t dst, const void* src, uint32_t bytes, uint32_t bar) {
    asm volatile("cp.async.bulk.shared::cluster.global.mbarrier::complete_tx::bytes [%0], [%1], %2, [%3];" ::"r"(dst),
                 "l"(src), "r"(bytes), "r"(bar)
                 : "memory");
}
__device__ __forceinline__ void cp16(uint32_t dst, const void* src) {
    asm volatile("cp.async.cg.shared.global [%0], [%1], 16;" ::"r"(dst), "l"(src) : "memory");
}
__device__ __forceinline__ void lds128(uint32_t (&v)[4], uint32_t a) {
    asm volatile("ld.shared.v4.u32 {%0,%1,%2,%3}, [%4];" : "=r"(v[0]), "=r"(v[1]), "=r"(v[2]), "=r"(v[3]) : "r"(a) : "memory");
}
__device__ __forceinline__ void lds128_if(uint32_t (&v)[4], uint32_t a, uint32_t p) {
    asm volatile("{.reg .pred q; setp.ne.u32 q, %5, 0; @q ld.shared.v4.u32 {%0,%1,%2,%3}, [%4];}"
                 : "+r"(v[0]), "+r"(v[1]), "+r"(v[2]), "+r"(v[3])
                 : "r"(a), "r"(p)
                 : "memory");
}
__device__ __forceinline__ void lds64(uint32_t& x, uint32_t& y, uint32_t a) {
    asm volatile("ld.shared.v2.u32 {%0,%1}, [%2];" : "=r"(x), "=r"(y) : "r"(a) : "memory");
}
__device__ __forceinline__ void sts128(uint32_t a, uint32_t x, uint32_t y, uint32_t z, uint32_t w) {
    asm volatile("st.shared.v4.u32 [%0], {%1,%2,%3,%4};" ::"r"(a), "r"(x), "r"(y), "r"(z), "r"(w) : "memory");
}
__device__ __forceinline__ void sts64(uint32_t a, uint32_t x, uint32_t y) {
    asm volatile("st.shared.v2.u32 [%0], {%1,%2};" ::"r"(a), "r"(x), "r"(y) : "memory");
}
__device__ __forceinline__ uint32_t pack(float lo, float hi) {
    uint32_t r;
    asm volatile("cvt.rn.bf16x2.f32 %0, %1, %2;" : "=r"(r) : "f"(hi), "f"(lo));
    return r;
}
__device__ __forceinline__ uint32_t hmul2(uint32_t a, uint32_t b) {
    uint32_t r;
    asm volatile("mul.rn.bf16x2 %0, %1, %2;" : "=r"(r) : "r"(a), "r"(b));
    return r;
}
__device__ __forceinline__ uint32_t hfma2(uint32_t a, uint32_t b, uint32_t c) {
    uint32_t r;
    asm volatile("fma.rn.bf16x2 %0, %1, %2, %3;" : "=r"(r) : "r"(a), "r"(b), "r"(c));
    return r;
}
__device__ __forceinline__ float ffma(float a, float b, float c) {
    float r;
    asm volatile("fma.rn.f32 %0, %1, %2, %3;" : "=f"(r) : "f"(a), "f"(b), "f"(c));
    return r;
}
__device__ __forceinline__ float tanh_fast(float x) {
    float r;
    asm volatile("tanh.approx.f32 %0, %1;" : "=f"(r) : "f"(x));
    return r;
}
__device__ __forceinline__ float gelu_tanh(float x) {
    float r;
    asm volatile(
        "{.reg .f32 a; mul.f32 a, %1, %1; fma.rn.f32 a, a, 0f3D122279, 0f3F4C422A; mul.f32 a, a, %1; tanh.approx.f32 %0, a;}"
        : "=f"(r)
        : "f"(x));
    return r;
}
__device__ __forceinline__ void mma16816(float (&d)[4], const uint32_t (&a)[4], uint32_t b0, uint32_t b1) {
    asm volatile("mma.sync.aligned.m16n8k16.row.col.f32.bf16.bf16.f32 {%0,%1,%2,%3}, {%4,%5,%6,%7}, {%8,%9}, {%0,%1,%2,%3};"
                 : "+f"(d[0]), "+f"(d[1]), "+f"(d[2]), "+f"(d[3])
                 : "r"(a[0]), "r"(a[1]), "r"(a[2]), "r"(a[3]), "r"(b0), "r"(b1));
}
__device__ __forceinline__ uint32_t clock32() {
    uint32_t c;
    asm volatile("mov.u32 %0, %%clock;" : "=r"(c)::"memory");
    return c;
}
#define WG_FENCE() asm volatile("wgmma.fence.sync.aligned;" ::: "memory")
#define WG_COMMIT() asm volatile("wgmma.commit_group.sync.aligned;" ::: "memory")
#define WG_WAIT0() asm volatile("wgmma.wait_group.sync.aligned 0;" ::: "memory")
#define CP_COMMIT() asm volatile("cp.async.commit_group;" ::: "memory")
#define CP_WAIT(n) asm volatile("cp.async.wait_group %0;" ::"n"(n) : "memory")
#define SCHED_FENCE() mbar_wait_unless(one, sb + BAR_FULL, 0)
#define PROXY_FENCE() asm volatile("fence.proxy.async.shared::cta;" ::: "memory")
template <int N>
__device__ __forceinline__ void pin(float (&d)[N]) {
#pragma unroll
    for (int i = 0; i < N; i++) asm volatile("" : "+f"(d[i])::"memory");
}
#define TS(k)
#define TS_DUMP(role)

__device__ __forceinline__ void wgmma_ss_n168_acc(float (&d)[84], uint64_t da, uint64_t db) {
    asm volatile(
        "wgmma.mma_async.sync.aligned.m64n168k16.f32.bf16.bf16 "
        "{%0,%1,%2,%3,%4,%5,%6,%7,%8,%9,%10,%11,%12,%13,%14,%15,"
        "%16,%17,%18,%19,%20,%21,%22,%23,%24,%25,%26,%27,%28,%29,%30,%31,"
        "%32,%33,%34,%35,%36,%37,%38,%39,%40,%41,%42,%43,%44,%45,%46,%47,"
        "%48,%49,%50,%51,%52,%53,%54,%55,%56,%57,%58,%59,%60,%61,%62,%63,"
        "%64,%65,%66,%67,%68,%69,%70,%71,%72,%73,%74,%75,%76,%77,%78,%79,"
        "%80,%81,%82,%83}, "
        "%84, %85, 1, 1, 1, 0, 1;"
        : "+f"(d[0]), "+f"(d[1]), "+f"(d[2]), "+f"(d[3]), "+f"(d[4]), "+f"(d[5]), "+f"(d[6]), "+f"(d[7]),
          "+f"(d[8]), "+f"(d[9]), "+f"(d[10]), "+f"(d[11]), "+f"(d[12]), "+f"(d[13]), "+f"(d[14]), "+f"(d[15]),
          "+f"(d[16]), "+f"(d[17]), "+f"(d[18]), "+f"(d[19]), "+f"(d[20]), "+f"(d[21]), "+f"(d[22]), "+f"(d[23]),
          "+f"(d[24]), "+f"(d[25]), "+f"(d[26]), "+f"(d[27]), "+f"(d[28]), "+f"(d[29]), "+f"(d[30]), "+f"(d[31]),
          "+f"(d[32]), "+f"(d[33]), "+f"(d[34]), "+f"(d[35]), "+f"(d[36]), "+f"(d[37]), "+f"(d[38]), "+f"(d[39]),
          "+f"(d[40]), "+f"(d[41]), "+f"(d[42]), "+f"(d[43]), "+f"(d[44]), "+f"(d[45]), "+f"(d[46]), "+f"(d[47]),
          "+f"(d[48]), "+f"(d[49]), "+f"(d[50]), "+f"(d[51]), "+f"(d[52]), "+f"(d[53]), "+f"(d[54]), "+f"(d[55]),
          "+f"(d[56]), "+f"(d[57]), "+f"(d[58]), "+f"(d[59]), "+f"(d[60]), "+f"(d[61]), "+f"(d[62]), "+f"(d[63]),
          "+f"(d[64]), "+f"(d[65]), "+f"(d[66]), "+f"(d[67]), "+f"(d[68]), "+f"(d[69]), "+f"(d[70]), "+f"(d[71]),
          "+f"(d[72]), "+f"(d[73]), "+f"(d[74]), "+f"(d[75]), "+f"(d[76]), "+f"(d[77]), "+f"(d[78]), "+f"(d[79]),
          "+f"(d[80]), "+f"(d[81]), "+f"(d[82]), "+f"(d[83])
        : "l"(da), "l"(db));
}

__device__ __forceinline__ void wgmma_rs_n32_set(float (&d)[16], const uint32_t (&a)[4], uint64_t db) {
    asm volatile(
        "wgmma.mma_async.sync.aligned.m64n32k16.f32.bf16.bf16 "
        "{%0,%1,%2,%3,%4,%5,%6,%7,%8,%9,%10,%11,%12,%13,%14,%15}, "
        "{%16,%17,%18,%19}, %20, 0, 1, 1, 0;"
        : "=f"(d[0]), "=f"(d[1]), "=f"(d[2]), "=f"(d[3]), "=f"(d[4]), "=f"(d[5]), "=f"(d[6]), "=f"(d[7]),
          "=f"(d[8]), "=f"(d[9]), "=f"(d[10]), "=f"(d[11]), "=f"(d[12]), "=f"(d[13]), "=f"(d[14]), "=f"(d[15])
        : "r"(a[0]), "r"(a[1]), "r"(a[2]), "r"(a[3]), "l"(db));
}

__device__ __forceinline__ void wgmma_rs_n32_acc(float (&d)[16], const uint32_t (&a)[4], uint64_t db) {
    asm volatile(
        "wgmma.mma_async.sync.aligned.m64n32k16.f32.bf16.bf16 "
        "{%0,%1,%2,%3,%4,%5,%6,%7,%8,%9,%10,%11,%12,%13,%14,%15}, "
        "{%16,%17,%18,%19}, %20, 1, 1, 1, 0;"
        : "+f"(d[0]), "+f"(d[1]), "+f"(d[2]), "+f"(d[3]), "+f"(d[4]), "+f"(d[5]), "+f"(d[6]), "+f"(d[7]),
          "+f"(d[8]), "+f"(d[9]), "+f"(d[10]), "+f"(d[11]), "+f"(d[12]), "+f"(d[13]), "+f"(d[14]), "+f"(d[15])
        : "r"(a[0]), "r"(a[1]), "r"(a[2]), "r"(a[3]), "l"(db));
}

__device__ __forceinline__ void wgmma_rs_n16_set(float (&d)[8], const uint32_t (&a)[4], uint64_t db) {
    asm volatile(
        "wgmma.mma_async.sync.aligned.m64n16k16.f32.bf16.bf16 "
        "{%0,%1,%2,%3,%4,%5,%6,%7}, "
        "{%8,%9,%10,%11}, %12, 0, 1, 1, 0;"
        : "=f"(d[0]), "=f"(d[1]), "=f"(d[2]), "=f"(d[3]), "=f"(d[4]), "=f"(d[5]), "=f"(d[6]), "=f"(d[7])
        : "r"(a[0]), "r"(a[1]), "r"(a[2]), "r"(a[3]), "l"(db));
}

__device__ __forceinline__ void wgmma_rs_n16_acc(float (&d)[8], const uint32_t (&a)[4], uint64_t db) {
    asm volatile(
        "wgmma.mma_async.sync.aligned.m64n16k16.f32.bf16.bf16 "
        "{%0,%1,%2,%3,%4,%5,%6,%7}, "
        "{%8,%9,%10,%11}, %12, 1, 1, 1, 0;"
        : "+f"(d[0]), "+f"(d[1]), "+f"(d[2]), "+f"(d[3]), "+f"(d[4]), "+f"(d[5]), "+f"(d[6]), "+f"(d[7])
        : "r"(a[0]), "r"(a[1]), "r"(a[2]), "r"(a[3]), "l"(db));
}

__device__ __forceinline__ void wgmma_rs_n32_pred(float (&d)[16], const uint32_t (&a)[4], uint64_t db, uint32_t scale_d) {
    asm volatile(
        "{.reg .pred p; setp.ne.u32 p, %21, 0; wgmma.mma_async.sync.aligned.m64n32k16.f32.bf16.bf16 "
        "{%0,%1,%2,%3,%4,%5,%6,%7,%8,%9,%10,%11,%12,%13,%14,%15}, "
        "{%16,%17,%18,%19}, %20, p, 1, 1, 0;}"
        : "+f"(d[0]), "+f"(d[1]), "+f"(d[2]), "+f"(d[3]), "+f"(d[4]), "+f"(d[5]), "+f"(d[6]), "+f"(d[7]),
          "+f"(d[8]), "+f"(d[9]), "+f"(d[10]), "+f"(d[11]), "+f"(d[12]), "+f"(d[13]), "+f"(d[14]), "+f"(d[15])
        : "r"(a[0]), "r"(a[1]), "r"(a[2]), "r"(a[3]), "l"(db), "r"(scale_d));
}

__device__ __forceinline__ void prep_cta(uint32_t sb, int c, const __nv_bfloat16* __restrict__ wc,
                                         const __nv_bfloat16* __restrict__ se1, const __nv_bfloat16* __restrict__ se2) {
    const int tid = threadIdx.x, lane = tid & 31, warp = tid >> 5;
    constexpr int NROW = 2 * NF * NF;
#pragma unroll
    for (int q = tid; q < NROW * 2; q += 384) cp16(sb + q * 16, wc + (q >> 1) * ND + c * 16 + (q & 1) * 8);
    if (tid == 0) sts128(sb + NROW * 32, 0, 0, 0, 0);
    if (tid < 256) {
        const int l2 = c >> 1, n = ((tid >> 2) & 1) * 8 + (tid >> 5) + (l2 ? (c & 1) * 16 : 0);
        const int k = ((tid >> 1) & 1) * 8 + ((tid >> 3) & 3) * 2 + (tid & 1), mm = k >> 1, u = k & 1;
        const int f = l2 ? fmap(n) : mm < 6 ? 4 * mm + 2 * c + u : (mm == 6 && u == 0) ? 24 + c : -1;
        float v = 0.f;
        if (f >= 0 && (l2 ? k : n) < NR) v = __bfloat162float(l2 ? se2[k * NF + f] : se1[f * NR + n]);
        reinterpret_cast<__nv_bfloat16*>(g_se)[c * 256 + tid] = __float2bfloat16(l2 ? 0.5f * v : v);
    }
    asm volatile("cp.async.wait_all;" ::: "memory");
    __syncthreads();
    const int i = fmap(4 * (lane & 6) + 2 * (lane >> 3) + (lane & 1));
    const int g = lane >> 2, t = lane & 3;
#pragma unroll 4
    for (int task = warp; task < 128; task += 12) {
        const int eg = task & 1, n = (task >> 1) & 31, s = task >> 6;
        const int j = fmap(n);
        const uint32_t a = (i >= 0 && j >= 0) ? sb + ((s * NF + i) * NF + j) * 32 + eg * 16 : sb + NROW * 32;
        uint4 v;
        asm volatile("ldmatrix.sync.aligned.m8n8.x4.trans.shared.b16 {%0,%1,%2,%3}, [%4];"
                     : "=r"(v.x), "=r"(v.y), "=r"(v.z), "=r"(v.w)
                     : "r"(a));
        const int e = eg * 8 + g;
        if (t == 3) {
            const uint32_t mask = (e & 1) ? 0xffff0000u : 0xffffu;
            v.x &= mask;
            v.y &= mask;
        }
        const int ch = (t < 2 ? t ^ ((e >> 1) & 1) : t) ^ ((n >> 1) & 3);
        g_wc[(c >> 1) * 8192 + e * 512 + (c & 1) * 256 + s * 128 + n * 4 + ch] = v;
    }
    __threadfence();
    __syncthreads();
    if (tid == 0) atomicAdd(&g_ready, 1u);
}

#define P2_SKEW 90
#define TWARM 3
#define WPF_STEP 800
#define WDELAY 1600
#define WSTEP 500
#define FINWARP 0
#define PACE1 800
#define PACE2 1300
#define PF_START 2600
#define PF_PACE 550
#define WPF_AT 2000

__global__ void __cluster_dims__(2, 1, 1) __launch_bounds__(384, 1)
fibinet_kernel(const int* __restrict__ idx, const uint4* __restrict__ table,
               const __nv_bfloat16* __restrict__ se1, const __nv_bfloat16* __restrict__ se2,
               const __nv_bfloat16* __restrict__ wc,
               const unsigned char* __restrict__ w1, const __nv_bfloat16* __restrict__ w2, __nv_bfloat16* __restrict__ out,
               const __grid_constant__ CUtensorMap tm_w1, const __grid_constant__ CUtensorMap tm_bi) {
    extern __shared__ __align__(1024) unsigned char smem[];
    const uint32_t t_start = clock32();
    const int tid = threadIdx.x;
    const uint32_t sb = (uint32_t)__cvta_generic_to_shared(smem);
    if (blockIdx.x < NPREP) {
        prep_cta(sb, blockIdx.x, wc, se1, se2);
        return;
    }
    const int cta = blockIdx.x - NPREP, grp = cta >> 1, rank = cta & 1, lane = tid & 31;
    uint32_t ids[13][4], cid[3][2];
    uint32_t gd0 = 0;
    const uint4* tp = table + (lane & 7);
    auto gather = [&](int i) {
#pragma unroll
        for (int u = 0; u < 4; u++)
            asm volatile("{.reg .u64 a; mad.wide.u32 a, %2, 128, %1; cp.async.cg.shared.global [%0], [a], 16;}" ::"r"(
                             (gd0 ^ ((u & 1) * 64)) + xpair(i) + u * 512),
                         "l"(tp), "r"(ids[i][u])
                         : "memory");
        CP_COMMIT();
    };
    if (tid < 256) {
        const uint32_t w = tid >> 7, row = ((tid >> 5) & 3) * 16 + (lane >> 3);
        const int* ip = idx + ((grp * 64 + row) * NF + 2 * w);
#pragma unroll
        for (int u = 0; u < 4; u++)
            asm volatile("ld.global.nc.L2::128B.v2.u32 {%0,%1}, [%2];" : "=r"(ids[0][u]), "=r"(ids[1][u]) : "l"(ip + 4 * NF * u));
        const int* cp = idx + ((grp * 64 + ((tid & 127) >> 1)) * NF + 2 * w + 4 + 4 * (tid & 1));
#pragma unroll
        for (int k = 0; k < 3; k++)
            asm volatile("ld.global.nc.v2.u32 {%0,%1}, [%2];"
                         : "=r"(cid[k][0]), "=r"(cid[k][1])
                         : "l"(cp + 8 * k - (k == 2 ? 2 * (w & tid) : 0)));
        gd0 = sb + w * XDELTA + row * 128 + (((lane & 7) ^ (lane >> 3) ^ (4 * w)) << 4);
        gather(0);
    } else {
        if (tid == 256) asm volatile("prefetch.tensormap [%0];" ::"l"(&tm_w1));
        if (tid == 288) asm volatile("prefetch.tensormap [%0];" ::"l"(&tm_bi));
    }
    const uint32_t c0 = clock32();
    const int warp = __reduce_max_sync(0xffffffffu, tid >> 5);
    const int w = warp >> 2;

    if (w == 2) {
        asm volatile("setmaxnreg.dec.sync.aligned.u32 40;");
        auto load_wc = [&](int gi) {
            if (elect()) {
                const unsigned char* src = reinterpret_cast<const unsigned char*>(g_wc) + rank * 131072;
                mbar_expect(sb + BAR_WC + gi * 8, (wcfirst(gi + 1) - wcfirst(gi)) * 8192);
#pragma unroll
                for (int c = wcfirst(gi); c < wcfirst(gi + 1); c++) bulk(sb + wcslot(c), src + c * 8192, 8192, sb + BAR_WC + gi * 8);
            }
            __syncwarp();
        };
        if (warp == 8) {
            if (elect()) {
                mbar_init(sb + BAR_Z, 1);
                mbar_expect(sb + BAR_Z, 8192);
                tma2d(sb + ZOFF, &tm_bi, sb + BAR_Z, 32 * rank, 0);
            }
#pragma unroll
            for (int f = 0; f < 26; f++) {
                if (f == 2) {
                    if (elect()) {
#pragma unroll
                        for (int k = 2; k < 8; k++) mbar_init(sb + BAR_FULL + k * 8, 1);
                        asm volatile("fence.mbarrier_init.release.cluster;" ::: "memory");
                    }
                    __syncwarp();
                    asm volatile("barrier.cluster.arrive.relaxed.aligned;" ::: "memory");
                    mbar_wait(sb + BAR_Z);
#pragma unroll
                    for (int k = 0; k < 2; k++)
                        sts128(sb + ZOFF + (k * 32 + lane) * 128 + ((4 ^ (lane & 7)) << 4), 0x3c803c80u, 0x3c803c80u, 0x3c803c80u, 0x3c803c80u);
                    PROXY_FENCE();
                    asm volatile("bar.arrive 0, 384;" ::: "memory");
                    TS(31);
                }
                if (f == 5) asm volatile("barrier.cluster.wait.aligned;" ::: "memory");
                if (f >= 5) mbar_wait(sb + bdone(f - 5), bpar(f - 5));
                if (f >= 2 && f < 5)
                    while (clock32() - t_start < WDELAY + (f - 2) * WSTEP) {
                    }
                if (elect()) {
                    if (f < 2) mbar_init(sb + BAR_FULL + f * 8, 1);
                    mbar_expect(sb + bfull(f), 16384);
                    tma2d(sb + slot(2 * wl(f)), &tm_w1, sb + bfull(f), 128 * rank + 64 * (f & 1), fieldof(f) * 64);
                    tma2d(sb + slot(wl(f)), &tm_w1, sb + bfull(f), 128 * rank + 64 - 64 * (f & 1), fieldof(f) * 64);
                }
                TS(f);
            }
            if (elect()) mbar_arrive(sb + BAR_GO);
            TS_DUMP(2);
        } else if (warp == 9) {
            if (elect()) {
#pragma unroll
                for (int k = 0; k < 11; k++) mbar_init(sb + BAR_WC + k * 8, k < 10 ? 1 : 8);
                asm volatile("fence.mbarrier_init.release.cluster;" ::: "memory");
                mbar_expect(sb + BAR_FIN, 512);
            }
            __syncwarp();
            asm volatile("barrier.cluster.arrive.relaxed.aligned;" ::: "memory");
            asm volatile("bar.sync 0, 384;" ::: "memory");
            mbar_wait(sb + bdone(3), bpar(3));
            if (elect()) {
                unsigned v, it = 0;
                do {
                    asm volatile("ld.acquire.gpu.global.u32 %0, [%1];" : "=r"(v) : "l"(&g_ready) : "memory");
                } while (v < NPREP && ++it < 4000000u);
                asm volatile("fence.proxy.async.global;" ::: "memory");
                mbar_expect(sb + BAR_SE, 2048);
                bulk(sb + SEOFF, g_se, 2048, sb + BAR_SE);
                if (atomicAdd(&g_seen, 1u) == NMAIN - 1) {
                    g_seen = 0;
                    g_ready = 0;
                }
            }
            __syncwarp();
            TS(0);
            mbar_wait(sb + BAR_GO);
#pragma unroll
            for (int gi = 0; gi < 3; gi++) {
                mbar_wait(sb + bdone(21 + gi), bpar(21 + gi));
                load_wc(gi);
                TS(1 + gi);
            }
        } else if (warp == 10) {
            if (elect()) {
#pragma unroll
                for (int k = 0; k < 8; k++) mbar_init(sb + BAR_DONE + k * 8, 4);
                asm volatile("fence.mbarrier_init.release.cluster;" ::: "memory");
            }
            __syncwarp();
            asm volatile("barrier.cluster.arrive.relaxed.aligned;" ::: "memory");
            asm volatile("bar.arrive 0, 384;" ::: "memory");
#pragma unroll 1
            for (int k = 0; k < 7; k++) {
                while (clock32() - t_start < (uint32_t)(WPF_AT + k * WPF_STEP)) __nanosleep(20);
                if (lane < 6)
                    asm volatile("prefetch.global.L2 [%0];" ::"l"(w1 + (5 + k * 3 + (lane >> 1)) * 32768 + cta * 256 + (lane & 1) * 128));
            }
        } else {
            asm volatile("barrier.cluster.arrive.relaxed.aligned;" ::: "memory");
            asm volatile("bar.sync 0, 384;" ::: "memory");
            const uint2 v = __ldg(reinterpret_cast<const uint2*>(w2 + 128 * rank) + lane);
#pragma unroll
            for (int k = 0; k < 2; k++) {
                const uint32_t x = k ? v.y : v.x;
                sts64(sb + w2chunk((lane >> 2) * 4 + 2 * (lane & 1) + k) + (lane & 2) * 4,
                      __float_as_uint(0.5f * __uint_as_float(x << 16)), __float_as_uint(0.5f * __uint_as_float(x & 0xffff0000u)));
            }
            __syncwarp();
            if (lane == 0) mbar_arrive(sb + BAR_W2);
        }
        if (warp != 8) asm volatile("barrier.cluster.wait.aligned;" ::: "memory");
        {
            const uint32_t one = blockIdx.y + 1;
            uint32_t bw[2][4], z0[4], z1[4];
            mbar_wait(sb + BAR_SE);
            lds128(bw[0], sb + SEOFF + lane * 16);
            lds128(bw[1], sb + SEOFF + 512 + lane * 16);
            asm volatile("bar.sync 2, 384;" ::: "memory");
            lds128(z0, sb + ZQOFF + (tid & 127) * 16);
            lds128(z1, sb + ZQOFF + 2048 + (tid & 127) * 16);
            TS(8);
            float s[2][4] = {};
#pragma unroll
            for (int n = 0; n < 2; n++) {
                mma16816(s[n], z0, bw[0][2 * n], bw[0][2 * n + 1]);
                mma16816(s[n], z1, bw[1][2 * n], bw[1][2 * n + 1]);
            }
            lds128(bw[0], sb + SEOFF + 1024 + lane * 16);
            lds128(bw[1], sb + SEOFF + 1536 + lane * 16);
            float th[8];
#pragma unroll
            for (int k = 0; k < 8; k++) th[k] = gelu_tanh(s[k >> 2][k & 3]);
            SCHED_FENCE();
            TS(9);
            uint32_t gq[4];
#pragma unroll
            for (int k = 0; k < 4; k++)
                gq[k] = pack(s[k >> 1][2 * (k & 1)] * ffma(th[2 * k], 0.5f, 0.5f), s[k >> 1][2 * (k & 1) + 1] * ffma(th[2 * k + 1], 0.5f, 0.5f));
            float a[4][4] = {};
#pragma unroll
            for (int n = 0; n < 4; n++) mma16816(a[n], gq, bw[n >> 1][2 * (n & 1)], bw[n >> 1][2 * (n & 1) + 1]);
#pragma unroll
            for (int k = 0; k < 16; k++)
                if (k < 13 || k == 14) a[k >> 2][k & 3] = tanh_fast(a[k >> 2][k & 3]);
            SCHED_FENCE();
            TS(10);
            uint32_t ap[8];
#pragma unroll
            for (int k = 0; k < 8; k++)
                ap[k] = pack(ffma(a[k >> 1][2 * (k & 1)], 0.5f, 0.5f), ffma(a[k >> 1][2 * (k & 1) + (k < 6)], 0.5f, 0.5f));
            sts128(sb + GOFF + (tid & 127) * 16, ap[0], ap[1], ap[2], ap[3]);
            sts128(sb + GOFF + 2048 + (tid & 127) * 16, ap[4], ap[5], ap[6], ap[7]);
            asm volatile("bar.arrive 3, 384;" ::: "memory");
            TS(11);
        }
        if (warp == 9) {
            load_wc(3);
            load_wc(4);
            mbar_wait(sb + BAR_TD);
            load_wc(5);
            if (lane < 16) TS_DUMP(3);
        }
    } else {
        asm volatile("setmaxnreg.inc.sync.aligned.u32 232;");
        asm volatile("barrier.cluster.arrive.relaxed.aligned;" ::: "memory");
        const int g = lane >> 2, t = lane & 3, wq = warp & 3, t128 = tid & 127;
        gd0 = opaque(gd0);
        TS(28);
        float acc[84];
#pragma unroll
        for (int k = 0; k < 84; k++) asm volatile("mov.b32 %0, 0;" : "=f"(acc[k]));
        uint32_t e0[9], e1[9], e2[9];
        uint32_t X[14][2][4];
        uint32_t zq[4] = {0, 0, 0, 0};
        const uint64_t dA = mkdesc(sb + w * XDELTA, 16, 1024, 1);
        uint32_t dBlo = (uint32_t)mkdesc(sb + ZOFF, 0, 0, 0);
        const uint32_t xl0 = opaque(sb + (t & 1) * XDELTA + (16 * wq + g) * 128 + (((4 * rank + 2 * w) ^ (4 * (t & 1)) ^ g) << 4));
        const uint32_t hi_half = t >> 1;
        const uint32_t sa0 = opaque(sb + AOFF + t * 4096 + (t >> 1) * 16 + (wq * 32 + g * 4 + w) * 16);
        const uint32_t sa1 = opaque(((g & 2) << 4) | ((t & 1) << 3));
        const uint32_t zero = blockIdx.y, one = zero + 1;
        auto expand = [&](int k0, int k1) {
#pragma unroll
            for (int k = k0; k < k1; k++)
#pragma unroll
                for (int u = 0; u < 4; u++)
                    asm volatile("shfl.sync.idx.b32 %0, %1, %2, 31, 0xffffffff;"
                                 : "=r"(ids[k][u])
                                 : "r"(k < 12 ? cid[(k - 2) >> 2][k & 1] : w ? cid[2][1] : cid[2][0]),
                                   "r"(2 * (lane >> 3) + 8 * u + (((k - 2) >> 1) & 1)));
        };
        auto twarm = [&]() {
            float s1[8];
            WG_FENCE();
            wgmma_rs_n16_set(s1, zq, mkdesc(sb + AOFF, 16, 512, 2));
            WG_COMMIT();
            WG_WAIT0();
            pin(s1);
            asm volatile("{.reg .pred p; setp.ne.u32 p, %1, 0; @p st.shared.f32 [%1], %0;}" ::"f"(s1[0]), "r"(zero));
        };
        expand(2, 8);
        if (TWARM & 1) twarm();
        TS(26);
        while (clock32() - c0 < PACE1) {
        }
        gather(1);
        expand(8, 13);
        if (TWARM & 2) twarm();
        TS(30);
        while (clock32() - c0 < PACE2) {
        }
        gather(2);
        if (TWARM & 4) twarm();
        asm volatile("bar.sync 0, 384;" ::: "memory");
        auto lift = [&](int i) {
            const int m = 2 * (i >> 2) + (i & 1);
#pragma unroll
            for (int r = 0; r < 2; r++)
#pragma unroll
                for (int cc = 0; cc < 2; cc++) {
                    const uint32_t a = (xl0 ^ (cc * 16)) + xpair(i) + r * 1024;
                    if (i & 2) lds128_if(X[2 * m + r][cc], a, hi_half);
                    else lds128(X[2 * m + r][cc], a);
                }
        };
        auto store_pair = [&](int m, int half, const uint32_t (&ea)[9]) {
            uint32_t a;
            if (m < 4) a = sa0 + (sa1 ^ (((m & 1) << 5) | ((m >> 1) << 3)));
            else a = sb + BOFF + t * 2048 + (wq * 32 + g * 4 + ((2 * (m & 1) + w) ^ t)) * 8;
#pragma unroll
            for (int n = half; n < 4; n += 2)
#pragma unroll
                for (int u = 0; u < 2; u++)
                    sts64(a + (m < 4 ? (8 * n + u) * 2048 + n * 32 : (8 * n + u) * 1024),
                          __byte_perm(ea[2 * n], e1[2 * n], u ? 0x7632 : 0x5410),
                          __byte_perm(ea[2 * n + 1], e1[2 * n + 1], u ? 0x7632 : 0x5410));
        };
        auto z_pair = [&](int m, uint32_t a, uint32_t b) {
            asm volatile("{.reg .pred p; setp.eq.u32 p, %4, %5; @p prmt.b32 %0, %2, %3, 0x5410; @p prmt.b32 %1, %2, %3, 0x7632;}"
                         : "+r"(zq[2 * (m >> 2)]), "+r"(zq[2 * (m >> 2) + 1])
                         : "r"(a), "r"(b), "r"(t), "r"(m & 3));
        };

        TS(29);
        mbar_wait(sb + BAR_FULL + w * 8);
        CP_WAIT(2);
        if (w == 1) {
            asm volatile("bar.arrive 6, 256;" ::: "memory");
            asm volatile("bar.sync 5, 256;" ::: "memory");
        }
#pragma unroll
        for (int i = 0; i < 13; i++) {
            const uint64_t da = dA + (xpair(i) >> 4) + ((uint64_t)i << 16);
            dBlo += (uint32_t)(w ? wl(2 * i + 1) - (i ? wl(2 * i - 1) : 0) : wl(2 * i) - (i ? wl(2 * i - 2) : 0)) *
                    (uint32_t)((SLOT << 12) - (SLOT >> 3));
            const uint64_t db = mkdesc(0, 0, 1024, 1) | dBlo;
            TS(i);
            WG_FENCE();
            wgmma_ss_n168_acc(acc, da, db + w * 256);
            wgmma_ss_n168_acc(acc, da + 2, db + w * 256 + 128);
            wgmma_ss_n168_acc(acc, da + 4, db + (w ^ 1) * 256);
            wgmma_ss_n168_acc(acc, da + 6, db + (w ^ 1) * 256 + 128);
            WG_COMMIT();
            if (i == 0) {
                if (w == 0) {
                    asm volatile("bar.arrive 5, 256;" ::: "memory");
                    asm volatile("bar.sync 6, 256;" ::: "memory");
                }
            } else {
                mbar_wait(sb + bdone(2 * i - 2) + (w ^ 1) * 8, bpar(2 * i - 2));
            }
            if (i < 10) gather(i + 3);
            if (i == 1) asm volatile("barrier.cluster.wait.aligned;" ::: "memory");
            if (i == 6) mbar_wait(sb + BAR_W2);
            lift(i);
            if (i == 10 || i == 11) mbar_wait(sb + bdone(2 * i - 2) + w * 8, bpar(2 * i - 2));
            if (i >= 2 && !(i & 1)) {
                z_pair((i - 2) >> 1, e0[8], e1[8]);
                store_pair((i - 2) >> 1, 0, e0);
#pragma unroll
                for (int k = 0; k < 8; k++) e2[k] = e0[k];
            } else if (i >= 3) {
                store_pair((i - 3) >> 1, 1, e2);
            }
            const uint32_t rdy = i < 12 ? mbar_test(sb + bfull(2 * i + 2) + w * 8, bpar(2 * i + 2)) : 0;
            WG_WAIT0();
            pin(acc);
            if (i == 12) TS(13);
            if (i == 0) TS(27);
            if (i < 10) CP_WAIT(2);
            else if (i == 10) CP_WAIT(1);
            else if (i == 11) CP_WAIT(0);
            if (i < 12 && lane == 0) mbar_arrive(sb + bdone(2 * i) + w * 8);
#pragma unroll
            for (int k = 0; k < 9; k++) {
                const uint32_t v = k < 8 ? pack(acc[64 + 2 * k], acc[65 + 2 * k]) : pack(acc[80], acc[82]);
                if (i & 1) e1[k] = v;
                else e0[k] = v;
            }
            if (i < 12) {
#pragma unroll
                for (int k = 64; k < 83; k++)
                    if (k != 81) asm volatile("mov.b32 %0, %1;" : "+f"(acc[k]) : "r"(zero));
                mbar_wait_unless(rdy, sb + bfull(2 * i + 2) + w * 8, bpar(2 * i + 2));
            } else {
                z_pair(6, e0[8], 0);
                sts128(sb + ZQOFF + w * 2048 + t128 * 16, zq[0], zq[1], zq[2], zq[3]);
                asm volatile("bar.arrive 2, 384;" ::: "memory");
            }
        }
        TS(14);

        float aj[14];
        uint32_t ai[8];
        float sum0 = 0.f, sum1 = 0.f;
        float th[32];
        uint32_t hw[4][4];
        auto deep_issue = [&](int k2) {
            lds128(hw[k2], ((sb + w2chunk(w * 16 + t)) ^ ((k2 & 1) * 64)) + k2 * 512);
#pragma unroll
            for (int k = 8 * k2; k < 8 * k2 + 8; k++) th[k] = gelu_tanh(acc[k]);
        };
        auto deep_use = [&](int k2) {
#pragma unroll
            for (int k = 8 * k2; k < 8 * k2 + 8; k++) {
                const float h = __uint_as_float(hw[k2][((k >> 1) & 2) + (k & 1)]);
                const float y = ffma(th[k], h, h);
                if (k & 2) sum1 = ffma(acc[k], y, sum1);
                else sum0 = ffma(acc[k], y, sum0);
            }
        };
        auto deep_send = [&]() {
#pragma unroll
            for (int k = 0; k < 4; k++)
                sts128(sb + EXOFF + w * SLOT + t128 * 16 + k * 2048, pack(acc[32 + 8 * k], acc[33 + 8 * k]),
                       pack(acc[34 + 8 * k], acc[35 + 8 * k]), pack(acc[36 + 8 * k], acc[37 + 8 * k]), pack(acc[38 + 8 * k], acc[39 + 8 * k]));
        };
        auto deep_recv = [&]() {
            const uint32_t eye = (g >> 1) == t ? ((g & 1) ? 0x3f800000u : 0x3f80u) : 0u;
#pragma unroll
            for (int k = 0; k < 4; k++) {
                uint32_t o[4];
                lds128(o, sb + EXOFF + (w ^ 1) * SLOT + t128 * 16 + k * 2048);
#pragma unroll
                for (int c = 0; c < 2; c++)
                    asm volatile("mma.sync.aligned.m16n8k8.row.col.f32.bf16.bf16.f32 {%0,%1,%2,%3}, {%4,%5}, {%6}, {%0,%1,%2,%3};"
                                 : "+f"(acc[8 * k + 4 * c]), "+f"(acc[8 * k + 4 * c + 1]), "+f"(acc[8 * k + 4 * c + 2]), "+f"(acc[8 * k + 4 * c + 3])
                                 : "r"(o[2 * c]), "r"(o[2 * c + 1]), "r"(eye));
            }
        };
        auto store_last = [&]() {
#pragma unroll
            for (int n = 0; n < 4; n++) sts64(sb + COFF + w * 4096 + n * 1024 + (t128 ^ w) * 8, e0[2 * n], e0[2 * n + 1]);
            store_pair(5, 1, e2);
        };
        const uint32_t la = sb + AOFF + w * (16 * 2048 + 64) + (wq * 32 + g * 4 + (t ^ (g & 2))) * 16;
        const uint32_t lb = sb + BOFF + w * (16 * 1024) + t128 * 8;
        const uint32_t lc0 = sb + COFF + (t & 1) * (4096 + 8) + w * 2048 + (wq * 8 + g) * 32, lc1 = lc0 ^ 8;
        uint32_t Ap[2][2][4];
        auto load_a = [&](int e) {
            lds128(Ap[e & 1][0], la + e * 2048 + (e >> 2) * 16);
            lds64(Ap[e & 1][1][0], Ap[e & 1][1][1], (lb ^ ((e & 6) * 4)) + e * 1024);
            lds64(Ap[e & 1][1][2], Ap[e & 1][1][3], ((e & 2) ? lc1 : lc0) + (e >> 3) * 1024 + (e & 4) * 4);
        };
        {
            deep_send();
            asm volatile("bar.sync 1, 256;" ::: "memory");
            deep_recv();
            TS(15);
            deep_issue(0);
            SCHED_FENCE();
            TS(16);
            deep_issue(1);
            deep_use(0);
            store_last();
            SCHED_FENCE();
            TS(17);
            deep_issue(2);
            deep_use(1);
            mbar_wait(sb + BAR_WC);
            deep_use(2);
            TS(18);
            asm volatile("bar.sync 3, 384;" ::: "memory");
            uint32_t v[2][4];
            lds128(v[0], sb + GOFF + t128 * 16);
            lds128(v[1], sb + GOFF + 2048 + t128 * 16);
            load_a(0);
            load_a(1);
            deep_issue(3);
#pragma unroll
            for (int k = 0; k < 8; k++) ai[k] = v[k >> 2][k & 3];
#pragma unroll
            for (int q = 0; q < 14; q++) {
                const uint32_t x = ai[2 * (q >> 2) + (q & 1)];
                aj[q] = __uint_as_float((q & 2) ? x & 0xffff0000u : x << 16);
            }
        }
        TS(19);

        uint32_t fin_a, fin_b, fin_l;
        uint64_t fin_o;
        {
            const uint64_t dW = mkdesc(sb + w * 4096, 16, 512, 2);
            uint32_t Aq[2][2][4], hacc[2][4], V[14];
            float Sp[16], Sq[16], U[14];
            auto scale_a = [&](int e) {
#pragma unroll
                for (int k = 0; k < 8; k++) Aq[e & 1][k >> 2][k & 3] = hmul2(Ap[e & 1][k >> 2][k & 3], ai[k < 4 ? k ^ (e & 2) : k]);
            };
            auto dot = [&](int e) {
#pragma unroll
                for (int q = 0; q < 14; q++) {
                    const uint32_t x = X[q][e >> 3][(e & 7) >> 1];
                    if ((e & 6) == 0 && q < 4) hacc[e >> 3][q] = hmul2(V[q], x);
                    else hacc[e >> 3][q & 3] = hfma2(V[q], x, hacc[e >> 3][q & 3]);
                }
            };
            scale_a(0);
            if (w == 1) {
                const uint32_t c1 = clock32();
                while (clock32() - c1 < P2_SKEW) {
                }
            }
#pragma unroll
            for (int e = 0; e < 16; e++) {
                const uint64_t d = dW + (wcslot(e) >> 4);
                WG_FENCE();
                if (e == 0) wgmma_rs_n32_set(Sp, Ap[e & 1][0], d);
                else wgmma_rs_n32_pred(Sp, Ap[e & 1][0], d, zero);
                wgmma_rs_n32_acc(Sp, Ap[e & 1][1], d + 2);
                if (e == 0) wgmma_rs_n32_set(Sq, Aq[e & 1][0], d + 128);
                else wgmma_rs_n32_pred(Sq, Aq[e & 1][0], d + 128, zero);
                wgmma_rs_n32_acc(Sq, Aq[e & 1][1], d + 130);
                WG_COMMIT();
                SCHED_FENCE();
                if (e == 0) deep_use(3);
                if (e > 0 && !(e & 1)) dot(e - 1);
                if (e == 9) {
                    sum0 += __shfl_xor_sync(0xffffffffu, sum0, 1);
                    sum1 += __shfl_xor_sync(0xffffffffu, sum1, 1);
                }
                if (e == 13) {
                    asm("mapa.shared::cluster.u32 %0, %1, %2;"
                        : "=r"(fin_a)
                        : "r"(sb + PARTOFF + (((wq & 1) * 16 + t * 8 + g) * 4 + 2 * rank + w) * 4), "r"(wq >> 1));
                    asm("mapa.shared::cluster.u32 %0, %1, %2;" : "=r"(fin_b) : "r"(sb + BAR_FIN), "r"(wq >> 1));
                    fin_a = opaque(fin_a);
                    fin_b = opaque(fin_b + (lane >> 5));
                    fin_l = opaque(sb + lane * 16);
                    const uint64_t o = reinterpret_cast<uint64_t>(out + (blockIdx.x - NPREP) * 32 + lane);
                    fin_o = opaque((uint32_t)o) | ((uint64_t)opaque((uint32_t)(o >> 32)) << 32);
                }
                if (e == 11) {
                    sum0 += __shfl_xor_sync(0xffffffffu, sum0, 2);
                    sum1 += __shfl_xor_sync(0xffffffffu, sum1, 2);
                }
                if (e + 1 < 16) scale_a(e + 1);
                if (e == 0 || e == 1 || e == 4 || e == 7 || e == 10)
                    mbar_wait(sb + BAR_WC + (e == 0 ? 1 : e == 1 ? 2 : e == 4 ? 3 : e == 7 ? 4 : 5) * 8);
                else if (e < 15)
                    SCHED_FENCE();
                WG_WAIT0();
                pin(Sp);
                pin(Sq);
                if (e == 0 && lane == 0) mbar_arrive(sb + BAR_TD);
                if (e == 0) TS(20);
                if (e + 2 < 16) load_a(e + 2);
#pragma unroll
                for (int q = 0; q < 14; q++) {
                    const int ix = 4 * (q >> 2) + 2 * (q & 1) + ((q >> 1) & 1);
                    const float u = ffma(aj[q], Sq[ix], Sp[ix]);
                    if (!(e & 1)) U[q] = u;
                    else V[q] = pack(U[q], u);
                }
                if (e == 7) TS(21);
            }
            float r[4] = {sum0, 0.f, sum1, 0.f};
            mma16816(r, hacc[0], 0x3f803f80u, 0x3f803f80u);
            dot(15);
            mma16816(r, hacc[1], 0x3f803f80u, 0x3f803f80u);
            sum0 = r[0];
            sum1 = r[2];
        }
        TS(22);
        {
            const float v = (t & 1) ? sum1 : sum0;
            asm volatile(
                "{.reg .pred p; setp.lt.u32 p, %3, 2; @p st.async.shared::cluster.mbarrier::complete_tx::bytes.f32 [%0], %1, [%2];}" ::"r"(fin_a),
                "f"(v), "r"(fin_b), "r"(t)
                : "memory");
            if (warp == FINWARP) {
                mbar_wait((fin_l & ~0x1ff) + BAR_FIN);
                uint32_t p[4];
                lds128(p, fin_l + PARTOFF);
                *reinterpret_cast<__nv_bfloat16*>(fin_o) = __float2bfloat16((__uint_as_float(p[0]) + __uint_as_float(p[1])) +
                                                                             (__uint_as_float(p[2]) + __uint_as_float(p[3])));
            }
            if (wq == 0) TS_DUMP(w);
        }
    }
}

typedef CUresult (*EncodeFn)(CUtensorMap*, CUtensorMapDataType, cuuint32_t, void*, const cuuint64_t*, const cuuint64_t*,
                             const cuuint32_t*, const cuuint32_t*, CUtensorMapInterleave, CUtensorMapSwizzle,
                             CUtensorMapL2promotion, CUtensorMapFloatOOBfill);

}

extern "C" void kernel_launch(void* const* d_in, const int* in_sizes, int n_in, void* d_out, int out_size) {
    static EncodeFn encode = nullptr;
    if (!encode) {
        void* fn = nullptr;
        cudaDriverEntryPointQueryResult qr;
        cudaGetDriverEntryPoint("cuTensorMapEncodeTiled", &fn, cudaEnableDefault, &qr);
        encode = (EncodeFn)fn;
        cudaFuncSetAttribute(fibinet_kernel, cudaFuncAttributeMaxDynamicSharedMemorySize, SMEM_BYTES);
    }
    CUtensorMap tm;
    const cuuint64_t gd[2] = {NH, NF * ND};
    const cuuint64_t gs[1] = {NH * 2};
    const cuuint32_t bd[2] = {64, 64}, es[2] = {1, 1};
    encode(&tm, CU_TENSOR_MAP_DATA_TYPE_BFLOAT16, 2, d_in[6], gd, gs, bd, es, CU_TENSOR_MAP_INTERLEAVE_NONE,
           CU_TENSOR_MAP_SWIZZLE_128B, CU_TENSOR_MAP_L2_PROMOTION_L2_256B, CU_TENSOR_MAP_FLOAT_OOB_FILL_NONE);
    CUtensorMap tb;
    const cuuint64_t gd2[2] = {ND, ND};
    const cuuint64_t gs2[1] = {ND * 2};
    encode(&tb, CU_TENSOR_MAP_DATA_TYPE_BFLOAT16, 2, d_in[4], gd2, gs2, bd, es, CU_TENSOR_MAP_INTERLEAVE_NONE,
           CU_TENSOR_MAP_SWIZZLE_128B, CU_TENSOR_MAP_L2_PROMOTION_L2_256B, CU_TENSOR_MAP_FLOAT_OOB_FILL_NONE);
    fibinet_kernel<<<NPREP + NMAIN, 384, SMEM_BYTES>>>(
        (const int*)d_in[0], (const uint4*)d_in[1], (const __nv_bfloat16*)d_in[2], (const __nv_bfloat16*)d_in[3],
        (const __nv_bfloat16*)d_in[5], (const unsigned char*)d_in[6], (const __nv_bfloat16*)d_in[7], (__nv_bfloat16*)d_out, tm, tb);
}
```

```cpp
#include <cuda_runtime.h>
#include <cuda_bf16.h>
#include <cuda.h>
#include <stdint.h>

namespace {

constexpr int NB = 4096, NF = 26, ND = 64, NH = 256, NR = 13;
constexpr int NPREP = 4;
constexpr int NMAIN = 128;

constexpr int SLOT = 8192;
constexpr int ZOFF = 15 * SLOT;
__host__ __device__ constexpr int slot(int s) { return ZOFF - s * SLOT; }
constexpr int BOFF = ZOFF + SLOT;
constexpr int AOFF = BOFF + 32768;
constexpr int COFF = slot(12);
constexpr int MOFF = AOFF + 65536 + 128;
constexpr int BAR_FULL = MOFF, BAR_DONE = MOFF + 64, BAR_WC = MOFF + 128, BAR_FIN = MOFF + 176,
              BAR_GO = MOFF + 184, BAR_SE = MOFF + 192, BAR_W2 = MOFF + 200, BAR_TD = MOFF + 208, BAR_Z = MOFF + 216;
__host__ __device__ constexpr int bfull(int f) { return BAR_FULL + (f & 7) * 8; }
__host__ __device__ constexpr int bdone(int f) { return BAR_DONE + (f & 7) * 8; }
__host__ __device__ constexpr int bpar(int f) { return (f >> 3) & 1; }
constexpr int PARTOFF = MOFF + 256, SEOFF = MOFF + 768;
constexpr int SMEM_BYTES = MOFF + 2944;
static_assert((BAR_FIN >> 10) == (PARTOFF >> 10) && (BAR_FIN >> 10) == ((PARTOFF + 511) >> 10), "same 1 KB block");
constexpr int XDELTA = 2 * SLOT;
__host__ __device__ constexpr int xpair(int i) {
    return (i & 3) == 0 ? slot(11) : (i & 3) == 1 ? BOFF : (i & 3) == 2 ? BOFF + SLOT : slot(15);
}
__host__ __device__ constexpr int wl(int f) { return f % 5 == 0 ? 1 : f % 5 == 4 ? 7 : f % 5 + 2; }
__host__ __device__ constexpr int wcslot(int c) {
    return c == 0 ? slot(3) : c == 1 ? slot(8) : c == 2 ? slot(10) : c == 3 ? slot(15) : c == 4 ? slot(13)
         : c == 5 ? slot(11) : c == 6 ? slot(9) : c == 7 ? slot(14) : c == 8 ? slot(7) : c == 9 ? slot(2)
         : c == 10 ? slot(1) : c == 11 ? slot(4) : c == 12 ? slot(5) : c == 13 ? slot(6) : c == 14 ? ZOFF : slot(3);
}
__host__ __device__ constexpr int wcfirst(int gi) { return gi < 3 ? gi : gi == 3 ? 5 : gi == 4 ? 8 : gi == 5 ? 11 : 16; }
constexpr int EXOFF = slot(5);
constexpr int ZQOFF = slot(6);
constexpr int GOFF = ZQOFF + 4096;
__host__ __device__ constexpr int w2chunk(int c) { return ZOFF + c * 128 + ((5 ^ (c & 7)) << 4); }

__device__ uint4 g_wc[2 * 16 * 8192 / 16];
__device__ uint4 g_se[2048 / 16];
__device__ unsigned g_ready;
__device__ unsigned g_seen;

__host__ __device__ constexpr int fieldof(int f) { return f < 24 ? 4 * (f >> 2) + 2 * (f & 1) + ((f >> 1) & 1) : f; }
__device__ __forceinline__ int fmap(int n) { return n < 24 ? n : n < 28 ? 24 + ((n >> 1) & 1) : -1; }

__device__ __forceinline__ uint64_t mkdesc(uint32_t addr, uint32_t lbo, uint32_t sbo, int sw) {
    return (uint64_t)((addr & 0x3ffff) >> 4) | ((uint64_t)(lbo >> 4) << 16) | ((uint64_t)(sbo >> 4) << 32) |
           ((uint64_t)sw << 62);
}
__device__ __forceinline__ void mbar_init(uint32_t b, uint32_t n) {
    asm volatile("mbarrier.init.shared.b64 [%0], %1;" ::"r"(b), "r"(n) : "memory");
}
__device__ __forceinline__ void mbar_wait(uint32_t b, uint32_t par = 0) {
    asm volatile(
        "{\n.reg .pred p, q;\n.reg .u32 n;\n"
        "mbarrier.try_wait.parity.shared.b64 p, [%0], %1;\n@p bra.uni WD%=;\nmov.u32 n, 0;\n"
        "WL%=:\nmbarrier.try_wait.parity.shared.b64 p, [%0], %1;\n@p bra.uni WD%=;\n"
        "add.u32 n, n, 1;\nsetp.lt.u32 q, n, 4000000;\n@q bra.uni WL%=;\nWD%=:\n}\n" ::"r"(b), "r"(par)
        : "memory");
}
__device__ __forceinline__ uint32_t mbar_test(uint32_t b, uint32_t par) {
    uint32_t ok;
    asm volatile("{.reg .pred p; mbarrier.test_wait.parity.shared.b64 p, [%1], %2; selp.u32 %0, 1, 0, p;}"
                 : "=r"(ok)
                 : "r"(b), "r"(par)
                 : "memory");
    return ok;
}
__device__ __forceinline__ void mbar_wait_unless(uint32_t ok, uint32_t b, uint32_t par) {
    asm volatile(
        "{\n.reg .pred p, q;\n.reg .u32 n;\n"
        "setp.ne.u32 p, %1, 0;\n@p bra.uni WD%=;\nmov.u32 n, 0;\n"
        "WL%=:\nmbarrier.try_wait.parity.shared.b64 p, [%0], %2;\n@p bra.uni WD%=;\n"
        "add.u32 n, n, 1;\nsetp.lt.u32 q, n, 4000000;\n@q bra.uni WL%=;\nWD%=:\n}\n" ::"r"(b), "r"(ok), "r"(par)
        : "memory");
}
__device__ __forceinline__ void mbar_arrive(uint32_t b) {
    asm volatile("mbarrier.arrive.shared.b64 _, [%0];" ::"r"(b) : "memory");
}
__device__ __forceinline__ void mbar_expect(uint32_t b, uint32_t bytes) {
    asm volatile("mbarrier.arrive.expect_tx.shared.b64 _, [%0], %1;" ::"r"(b), "r"(bytes) : "memory");
}
__device__ __forceinline__ uint32_t opaque(uint32_t v) { return __shfl_sync(0xffffffffu, v, threadIdx.x); }
__device__ __forceinline__ bool elect() {
    uint32_t p;
    asm volatile("{.reg .pred q; elect.sync _|q, 0xffffffff; selp.u32 %0, 1, 0, q;}" : "=r"(p));
    return p;
}
__device__ __forceinline__ void tma2d(uint32_t dst, const CUtensorMap* m, uint32_t bar, int x, int y) {
    asm volatile(
        "cp.async.bulk.tensor.2d.shared::cluster.global.mbarrier::complete_tx::bytes [%0], [%1, {%3, %4}], [%2];" ::"r"(dst),
        "l"(m), "r"(bar), "r"(x), "r"(y)
        : "memory");
}
__device__ __forceinline__ void bulk(uint32_t dst, const void* src, uint32_t bytes, uint32_t bar) {
    asm volatile("cp.async.bulk.shared::cluster.global.mbarrier::complete_tx::bytes [%0], [%1], %2, [%3];" ::"r"(dst),
                 "l"(src), "r"(bytes), "r"(bar)
                 : "memory");
}
__device__ __forceinline__ void cp16(uint32_t dst, const void* src) {
    asm volatile("cp.async.cg.shared.global [%0], [%1], 16;" ::"r"(dst), "l"(src) : "memory");
}
__device__ __forceinline__ void lds128(uint32_t (&v)[4], uint32_t a) {
    asm volatile("ld.shared.v4.u32 {%0,%1,%2,%3}, [%4];" : "=r"(v[0]), "=r"(v[1]), "=r"(v[2]), "=r"(v[3]) : "r"(a) : "memory");
}
__device__ __forceinline__ void lds128_if(uint32_t (&v)[4], uint32_t a, uint32_t p) {
    asm volatile("{.reg .pred q; setp.ne.u32 q, %5, 0; @q ld.shared.v4.u32 {%0,%1,%2,%3}, [%4];}"
                 : "+r"(v[0]), "+r"(v[1]), "+r"(v[2]), "+r"(v[3])
                 : "r"(a), "r"(p)
                 : "memory");
}
__device__ __forceinline__ void lds64(uint32_t& x, uint32_t& y, uint32_t a) {
    asm volatile("ld.shared.v2.u32 {%0,%1}, [%2];" : "=r"(x), "=r"(y) : "r"(a) : "memory");
}
__device__ __forceinline__ void sts128(uint32_t a, uint32_t x, uint32_t y, uint32_t z, uint32_t w) {
    asm volatile("st.shared.v4.u32 [%0], {%1,%2,%3,%4};" ::"r"(a), "r"(x), "r"(y), "r"(z), "r"(w) : "memory");
}
__device__ __forceinline__ void sts64(uint32_t a, uint32_t x, uint32_t y) {
    asm volatile("st.shared.v2.u32 [%0], {%1,%2};" ::"r"(a), "r"(x), "r"(y) : "memory");
}
__device__ __forceinline__ uint32_t pack(float lo, float hi) {
    uint32_t r;
    asm volatile("cvt.rn.bf16x2.f32 %0, %1, %2;" : "=r"(r) : "f"(hi), "f"(lo));
    return r;
}
__device__ __forceinline__ uint32_t hmul2(uint32_t a, uint32_t b) {
    uint32_t r;
    asm volatile("mul.rn.bf16x2 %0, %1, %2;" : "=r"(r) : "r"(a), "r"(b));
    return r;
}
__device__ __forceinline__ uint32_t hfma2(uint32_t a, uint32_t b, uint32_t c) {
    uint32_t r;
    asm volatile("fma.rn.bf16x2 %0, %1, %2, %3;" : "=r"(r) : "r"(a), "r"(b), "r"(c));
    return r;
}
__device__ __forceinline__ float ffma(float a, float b, float c) {
    float r;
    asm volatile("fma.rn.f32 %0, %1, %2, %3;" : "=f"(r) : "f"(a), "f"(b), "f"(c));
    return r;
}
__device__ __forceinline__ float tanh_fast(float x) {
    float r;
    asm volatile("tanh.approx.f32 %0, %1;" : "=f"(r) : "f"(x));
    return r;
}
__device__ __forceinline__ float gelu_tanh(float x) {
    float r;
    asm volatile(
        "{.reg .f32 a; mul.f32 a, %1, %1; fma.rn.f32 a, a, 0f3D122279, 0f3F4C422A; mul.f32 a, a, %1; tanh.approx.f32 %0, a;}"
        : "=f"(r)
        : "f"(x));
    return r;
}
__device__ __forceinline__ void mma16816(float (&d)[4], const uint32_t (&a)[4], uint32_t b0, uint32_t b1) {
    asm volatile("mma.sync.aligned.m16n8k16.row.col.f32.bf16.bf16.f32 {%0,%1,%2,%3}, {%4,%5,%6,%7}, {%8,%9}, {%0,%1,%2,%3};"
                 : "+f"(d[0]), "+f"(d[1]), "+f"(d[2]), "+f"(d[3])
                 : "r"(a[0]), "r"(a[1]), "r"(a[2]), "r"(a[3]), "r"(b0), "r"(b1));
}
__device__ __forceinline__ uint32_t clock32() {
    uint32_t c;
    asm volatile("mov.u32 %0, %%clock;" : "=r"(c)::"memory");
    return c;
}
#define WG_FENCE() asm volatile("wgmma.fence.sync.aligned;" ::: "memory")
#define WG_COMMIT() asm volatile("wgmma.commit_group.sync.aligned;" ::: "memory")
#define WG_WAIT0() asm volatile("wgmma.wait_group.sync.aligned 0;" ::: "memory")
#define CP_COMMIT() asm volatile("cp.async.commit_group;" ::: "memory")
#define CP_WAIT(n) asm volatile("cp.async.wait_group %0;" ::"n"(n) : "memory")
#define SCHED_FENCE() mbar_wait_unless(one, sb + BAR_FULL, 0)
#define PROXY_FENCE() asm volatile("fence.proxy.async.shared::cta;" ::: "memory")
template <int N>
__device__ __forceinline__ void pin(float (&d)[N]) {
#pragma unroll
    for (int i = 0; i < N; i++) asm volatile("" : "+f"(d[i])::"memory");
}
#define TS(k)
#define TS_DUMP(role)

__device__ __forceinline__ void wgmma_ss_n168_acc(float (&d)[84], uint64_t da, uint64_t db) {
    asm volatile(
        "wgmma.mma_async.sync.aligned.m64n168k16.f32.bf16.bf16 "
        "{%0,%1,%2,%3,%4,%5,%6,%7,%8,%9,%10,%11,%12,%13,%14,%15,"
        "%16,%17,%18,%19,%20,%21,%22,%23,%24,%25,%26,%27,%28,%29,%30,%31,"
        "%32,%33,%34,%35,%36,%37,%38,%39,%40,%41,%42,%43,%44,%45,%46,%47,"
        "%48,%49,%50,%51,%52,%53,%54,%55,%56,%57,%58,%59,%60,%61,%62,%63,"
        "%64,%65,%66,%67,%68,%69,%70,%71,%72,%73,%74,%75,%76,%77,%78,%79,"
        "%80,%81,%82,%83}, "
        "%84, %85, 1, 1, 1, 0, 1;"
        : "+f"(d[0]), "+f"(d[1]), "+f"(d[2]), "+f"(d[3]), "+f"(d[4]), "+f"(d[5]), "+f"(d[6]), "+f"(d[7]),
          "+f"(d[8]), "+f"(d[9]), "+f"(d[10]), "+f"(d[11]), "+f"(d[12]), "+f"(d[13]), "+f"(d[14]), "+f"(d[15]),
          "+f"(d[16]), "+f"(d[17]), "+f"(d[18]), "+f"(d[19]), "+f"(d[20]), "+f"(d[21]), "+f"(d[22]), "+f"(d[23]),
          "+f"(d[24]), "+f"(d[25]), "+f"(d[26]), "+f"(d[27]), "+f"(d[28]), "+f"(d[29]), "+f"(d[30]), "+f"(d[31]),
          "+f"(d[32]), "+f"(d[33]), "+f"(d[34]), "+f"(d[35]), "+f"(d[36]), "+f"(d[37]), "+f"(d[38]), "+f"(d[39]),
          "+f"(d[40]), "+f"(d[41]), "+f"(d[42]), "+f"(d[43]), "+f"(d[44]), "+f"(d[45]), "+f"(d[46]), "+f"(d[47]),
          "+f"(d[48]), "+f"(d[49]), "+f"(d[50]), "+f"(d[51]), "+f"(d[52]), "+f"(d[53]), "+f"(d[54]), "+f"(d[55]),
          "+f"(d[56]), "+f"(d[57]), "+f"(d[58]), "+f"(d[59]), "+f"(d[60]), "+f"(d[61]), "+f"(d[62]), "+f"(d[63]),
          "+f"(d[64]), "+f"(d[65]), "+f"(d[66]), "+f"(d[67]), "+f"(d[68]), "+f"(d[69]), "+f"(d[70]), "+f"(d[71]),
          "+f"(d[72]), "+f"(d[73]), "+f"(d[74]), "+f"(d[75]), "+f"(d[76]), "+f"(d[77]), "+f"(d[78]), "+f"(d[79]),
          "+f"(d[80]), "+f"(d[81]), "+f"(d[82]), "+f"(d[83])
        : "l"(da), "l"(db));
}

__device__ __forceinline__ void wgmma_rs_n32_set(float (&d)[16], const uint32_t (&a)[4], uint64_t db) {
    asm volatile(
        "wgmma.mma_async.sync.aligned.m64n32k16.f32.bf16.bf16 "
        "{%0,%1,%2,%3,%4,%5,%6,%7,%8,%9,%10,%11,%12,%13,%14,%15}, "
        "{%16,%17,%18,%19}, %20, 0, 1, 1, 0;"
        : "=f"(d[0]), "=f"(d[1]), "=f"(d[2]), "=f"(d[3]), "=f"(d[4]), "=f"(d[5]), "=f"(d[6]), "=f"(d[7]),
          "=f"(d[8]), "=f"(d[9]), "=f"(d[10]), "=f"(d[11]), "=f"(d[12]), "=f"(d[13]), "=f"(d[14]), "=f"(d[15])
        : "r"(a[0]), "r"(a[1]), "r"(a[2]), "r"(a[3]), "l"(db));
}

__device__ __forceinline__ void wgmma_rs_n32_acc(float (&d)[16], const uint32_t (&a)[4], uint64_t db) {
    asm volatile(
        "wgmma.mma_async.sync.aligned.m64n32k16.f32.bf16.bf16 "
        "{%0,%1,%2,%3,%4,%5,%6,%7,%8,%9,%10,%11,%12,%13,%14,%15}, "
        "{%16,%17,%18,%19}, %20, 1, 1, 1, 0;"
        : "+f"(d[0]), "+f"(d[1]), "+f"(d[2]), "+f"(d[3]), "+f"(d[4]), "+f"(d[5]), "+f"(d[6]), "+f"(d[7]),
          "+f"(d[8]), "+f"(d[9]), "+f"(d[10]), "+f"(d[11]), "+f"(d[12]), "+f"(d[13]), "+f"(d[14]), "+f"(d[15])
        : "r"(a[0]), "r"(a[1]), "r"(a[2]), "r"(a[3]), "l"(db));
}

__device__ __forceinline__ void wgmma_rs_n16_set(float (&d)[8], const uint32_t (&a)[4], uint64_t db) {
    asm volatile(
        "wgmma.mma_async.sync.aligned.m64n16k16.f32.bf16.bf16 "
        "{%0,%1,%2,%3,%4,%5,%6,%7}, "
        "{%8,%9,%10,%11}, %12, 0, 1, 1, 0;"
        : "=f"(d[0]), "=f"(d[1]), "=f"(d[2]), "=f"(d[3]), "=f"(d[4]), "=f"(d[5]), "=f"(d[6]), "=f"(d[7])
        : "r"(a[0]), "r"(a[1]), "r"(a[2]), "r"(a[3]), "l"(db));
}

__device__ __forceinline__ void wgmma_rs_n16_acc(float (&d)[8], const uint32_t (&a)[4], uint64_t db) {
    asm volatile(
        "wgmma.mma_async.sync.aligned.m64n16k16.f32.bf16.bf16 "
        "{%0,%1,%2,%3,%4,%5,%6,%7}, "
        "{%8,%9,%10,%11}, %12, 1, 1, 1, 0;"
        : "+f"(d[0]), "+f"(d[1]), "+f"(d[2]), "+f"(d[3]), "+f"(d[4]), "+f"(d[5]), "+f"(d[6]), "+f"(d[7])
        : "r"(a[0]), "r"(a[1]), "r"(a[2]), "r"(a[3]), "l"(db));
}

__device__ __forceinline__ void wgmma_rs_n32_pred(float (&d)[16], const uint32_t (&a)[4], uint64_t db, uint32_t scale_d) {
    asm volatile(
        "{.reg .pred p; setp.ne.u32 p, %21, 0; wgmma.mma_async.sync.aligned.m64n32k16.f32.bf16.bf16 "
        "{%0,%1,%2,%3,%4,%5,%6,%7,%8,%9,%10,%11,%12,%13,%14,%15}, "
        "{%16,%17,%18,%19}, %20, p, 1, 1, 0;}"
        : "+f"(d[0]), "+f"(d[1]), "+f"(d[2]), "+f"(d[3]), "+f"(d[4]), "+f"(d[5]), "+f"(d[6]), "+f"(d[7]),
          "+f"(d[8]), "+f"(d[9]), "+f"(d[10]), "+f"(d[11]), "+f"(d[12]), "+f"(d[13]), "+f"(d[14]), "+f"(d[15])
        : "r"(a[0]), "r"(a[1]), "r"(a[2]), "r"(a[3]), "l"(db), "r"(scale_d));
}

__device__ __forceinline__ void prep_cta(uint32_t sb, int c, const __nv_bfloat16* __restrict__ wc,
                                         const __nv_bfloat16* __restrict__ se1, const __nv_bfloat16* __restrict__ se2) {
    const int tid = threadIdx.x, lane = tid & 31, warp = tid >> 5;
    constexpr int NROW = 2 * NF * NF;
#pragma unroll
    for (int q = tid; q < NROW * 2; q += 384) cp16(sb + q * 16, wc + (q >> 1) * ND + c * 16 + (q & 1) * 8);
    if (tid == 0) sts128(sb + NROW * 32, 0, 0, 0, 0);
    if (tid < 256) {
        const int l2 = c >> 1, n = ((tid >> 2) & 1) * 8 + (tid >> 5) + (l2 ? (c & 1) * 16 : 0);
        const int k = ((tid >> 1) & 1) * 8 + ((tid >> 3) & 3) * 2 + (tid & 1), mm = k >> 1, u = k & 1;
        const int f = l2 ? fmap(n) : mm < 6 ? 4 * mm + 2 * c + u : (mm == 6 && u == 0) ? 24 + c : -1;
        float v = 0.f;
        if (f >= 0 && (l2 ? k : n) < NR) v = __bfloat162float(l2 ? se2[k * NF + f] : se1[f * NR + n]);
        reinterpret_cast<__nv_bfloat16*>(g_se)[c * 256 + tid] = __float2bfloat16(l2 ? 0.5f * v : v);
    }
    asm volatile("cp.async.wait_all;" ::: "memory");
    __syncthreads();
    const int i = fmap(4 * (lane & 6) + 2 * (lane >> 3) + (lane & 1));
    const int g = lane >> 2, t = lane & 3;
#pragma unroll 4
    for (int task = warp; task < 128; task += 12) {
        const int eg = task & 1, n = (task >> 1) & 31, s = task >> 6;
        const int j = fmap(n);
        const uint32_t a = (i >= 0 && j >= 0) ? sb + ((s * NF + i) * NF + j) * 32 + eg * 16 : sb + NROW * 32;
        uint4 v;
        asm volatile("ldmatrix.sync.aligned.m8n8.x4.trans.shared.b16 {%0,%1,%2,%3}, [%4];"
                     : "=r"(v.x), "=r"(v.y), "=r"(v.z), "=r"(v.w)
                     : "r"(a));
        const int e = eg * 8 + g;
        if (t == 3) {
            const uint32_t mask = (e & 1) ? 0xffff0000u : 0xffffu;
            v.x &= mask;
            v.y &= mask;
        }
        const int ch = (t < 2 ? t ^ ((e >> 1) & 1) : t) ^ ((n >> 1) & 3);
        g_wc[(c >> 1) * 8192 + e * 512 + (c & 1) * 256 + s * 128 + n * 4 + ch] = v;
    }
    __threadfence();
    __syncthreads();
    if (tid == 0) atomicAdd(&g_ready, 1u);
}

#define P2_SKEW 90
#define TWARM 3
#define WPF_STEP 800
#define WDELAY 1600
#define WSTEP 500
#define PACE1 800
#define PACE2 1300
#define PF_START 2600
#define PF_PACE 550
#define WPF_AT 2000

__global__ void __cluster_dims__(2, 1, 1) __launch_bounds__(384, 1)
fibinet_kernel(const int* __restrict__ idx, const uint4* __restrict__ table,
               const __nv_bfloat16* __restrict__ se1, const __nv_bfloat16* __restrict__ se2,
               const __nv_bfloat16* __restrict__ wc,
               const unsigned char* __restrict__ w1, const __nv_bfloat16* __restrict__ w2, __nv_bfloat16* __restrict__ out,
               const __grid_constant__ CUtensorMap tm_w1, const __grid_constant__ CUtensorMap tm_bi) {
    extern __shared__ __align__(1024) unsigned char smem[];
    const uint32_t t_start = clock32();
    const int tid = threadIdx.x;
    const uint32_t sb = (uint32_t)__cvta_generic_to_shared(smem);
    if (blockIdx.x < NPREP) {
        prep_cta(sb, blockIdx.x, wc, se1, se2);
        return;
    }
    const int cta = blockIdx.x - NPREP, grp = cta >> 1, rank = cta & 1, lane = tid & 31;
    uint32_t ids[13][4], cid[3][2];
    uint32_t gd0 = 0;
    const uint4* tp = table + (lane & 7);
    auto gather = [&](int i) {
#pragma unroll
        for (int u = 0; u < 4; u++)
            asm volatile("{.reg .u64 a; mad.wide.u32 a, %2, 128, %1; cp.async.cg.shared.global [%0], [a], 16;}" ::"r"(
                             (gd0 ^ ((u & 1) * 64)) + xpair(i) + u * 512),
                         "l"(tp), "r"(ids[i][u])
                         : "memory");
        CP_COMMIT();
    };
    if (tid < 256) {
        const uint32_t w = tid >> 7, row = ((tid >> 5) & 3) * 16 + (lane >> 3);
        const int* ip = idx + ((grp * 64 + row) * NF + 2 * w);
#pragma unroll
        for (int u = 0; u < 4; u++)
            asm volatile("ld.global.nc.L2::128B.v2.u32 {%0,%1}, [%2];" : "=r"(ids[0][u]), "=r"(ids[1][u]) : "l"(ip + 4 * NF * u));
        const int* cp = idx + ((grp * 64 + ((tid & 127) >> 1)) * NF + 2 * w + 4 + 4 * (tid & 1));
#pragma unroll
        for (int k = 0; k < 3; k++)
            asm volatile("ld.global.nc.v2.u32 {%0,%1}, [%2];"
                         : "=r"(cid[k][0]), "=r"(cid[k][1])
                         : "l"(cp + 8 * k - (k == 2 ? 2 * (w & tid) : 0)));
        gd0 = sb + w * XDELTA + row * 128 + (((lane & 7) ^ (lane >> 3) ^ (4 * w)) << 4);
        gather(0);
    } else {
        if (tid == 256) asm volatile("prefetch.tensormap [%0];" ::"l"(&tm_w1));
        if (tid == 288) asm volatile("prefetch.tensormap [%0];" ::"l"(&tm_bi));
    }
    const uint32_t c0 = clock32();
    const int warp = __reduce_max_sync(0xffffffffu, tid >> 5);
    const int w = warp >> 2;

    if (w == 2) {
        asm volatile("setmaxnreg.dec.sync.aligned.u32 40;");
        auto load_wc = [&](int gi) {
            if (elect()) {
                const unsigned char* src = reinterpret_cast<const unsigned char*>(g_wc) + rank * 131072;
                mbar_expect(sb + BAR_WC + gi * 8, (wcfirst(gi + 1) - wcfirst(gi)) * 8192);
#pragma unroll
                for (int c = wcfirst(gi); c < wcfirst(gi + 1); c++) bulk(sb + wcslot(c), src + c * 8192, 8192, sb + BAR_WC + gi * 8);
            }
            __syncwarp();
        };
        if (warp == 8) {
            if (elect()) {
                mbar_init(sb + BAR_Z, 1);
                mbar_expect(sb + BAR_Z, 8192);
                tma2d(sb + ZOFF, &tm_bi, sb + BAR_Z, 32 * rank, 0);
            }
#pragma unroll
            for (int f = 0; f < 26; f++) {
                if (f == 2) {
                    if (elect()) {
#pragma unroll
                        for (int k = 2; k < 8; k++) mbar_init(sb + BAR_FULL + k * 8, 1);
                        asm volatile("fence.mbarrier_init.release.cluster;" ::: "memory");
                    }
                    __syncwarp();
                    asm volatile("barrier.cluster.arrive.relaxed.aligned;" ::: "memory");
                    mbar_wait(sb + BAR_Z);
#pragma unroll
                    for (int k = 0; k < 2; k++)
                        sts128(sb + ZOFF + (k * 32 + lane) * 128 + ((4 ^ (lane & 7)) << 4), 0x3c803c80u, 0x3c803c80u, 0x3c803c80u, 0x3c803c80u);
                    PROXY_FENCE();
                    asm volatile("bar.arrive 0, 384;" ::: "memory");
                    TS(31);
                }
                if (f == 5) asm volatile("barrier.cluster.wait.aligned;" ::: "memory");
                if (f >= 5) mbar_wait(sb + bdone(f - 5), bpar(f - 5));
                if (f >= 2 && f < 5)
                    while (clock32() - t_start < WDELAY + (f - 2) * WSTEP) {
                    }
                if (elect()) {
                    if (f < 2) mbar_init(sb + BAR_FULL + f * 8, 1);
                    mbar_expect(sb + bfull(f), 16384);
                    tma2d(sb + slot(2 * wl(f)), &tm_w1, sb + bfull(f), 128 * rank + 64 * (f & 1), fieldof(f) * 64);
                    tma2d(sb + slot(wl(f)), &tm_w1, sb + bfull(f), 128 * rank + 64 - 64 * (f & 1), fieldof(f) * 64);
                }
                TS(f);
            }
            if (elect()) mbar_arrive(sb + BAR_GO);
            TS_DUMP(2);
        } else if (warp == 9) {
            if (elect()) {
#pragma unroll
                for (int k = 0; k < 11; k++) mbar_init(sb + BAR_WC + k * 8, k < 10 ? 1 : 8);
                asm volatile("fence.mbarrier_init.release.cluster;" ::: "memory");
                mbar_expect(sb + BAR_FIN, 512);
            }
            __syncwarp();
            asm volatile("barrier.cluster.arrive.relaxed.aligned;" ::: "memory");
            asm volatile("bar.sync 0, 384;" ::: "memory");
            mbar_wait(sb + bdone(3), bpar(3));
            if (elect()) {
                unsigned v, it = 0;
                do {
                    asm volatile("ld.acquire.gpu.global.u32 %0, [%1];" : "=r"(v) : "l"(&g_ready) : "memory");
                } while (v < NPREP && ++it < 4000000u);
                asm volatile("fence.proxy.async.global;" ::: "memory");
                mbar_expect(sb + BAR_SE, 2048);
                bulk(sb + SEOFF, g_se, 2048, sb + BAR_SE);
                if (atomicAdd(&g_seen, 1u) == NMAIN - 1) {
                    g_seen = 0;
                    g_ready = 0;
                }
            }
            __syncwarp();
            TS(0);
            mbar_wait(sb + BAR_GO);
#pragma unroll
            for (int gi = 0; gi < 3; gi++) {
                mbar_wait(sb + bdone(21 + gi), bpar(21 + gi));
                load_wc(gi);
                TS(1 + gi);
            }
        } else if (warp == 10) {
            if (elect()) {
#pragma unroll
                for (int k = 0; k < 8; k++) mbar_init(sb + BAR_DONE + k * 8, 4);
                asm volatile("fence.mbarrier_init.release.cluster;" ::: "memory");
            }
            __syncwarp();
            asm volatile("barrier.cluster.arrive.relaxed.aligned;" ::: "memory");
            asm volatile("bar.arrive 0, 384;" ::: "memory");
#pragma unroll 1
            for (int k = 0; k < 7; k++) {
                while (clock32() - t_start < (uint32_t)(WPF_AT + k * WPF_STEP)) __nanosleep(20);
                if (lane < 6)
                    asm volatile("prefetch.global.L2 [%0];" ::"l"(w1 + (5 + k * 3 + (lane >> 1)) * 32768 + cta * 256 + (lane & 1) * 128));
            }
        } else {
            asm volatile("barrier.cluster.arrive.relaxed.aligned;" ::: "memory");
            asm volatile("bar.sync 0, 384;" ::: "memory");
            const uint2 v = __ldg(reinterpret_cast<const uint2*>(w2 + 128 * rank) + lane);
#pragma unroll
            for (int k = 0; k < 2; k++) {
                const uint32_t x = k ? v.y : v.x;
                sts64(sb + w2chunk((lane >> 2) * 4 + 2 * (lane & 1) + k) + (lane & 2) * 4,
                      __float_as_uint(0.5f * __uint_as_float(x << 16)), __float_as_uint(0.5f * __uint_as_float(x & 0xffff0000u)));
            }
            __syncwarp();
            if (lane == 0) mbar_arrive(sb + BAR_W2);
        }
        if (warp != 8) asm volatile("barrier.cluster.wait.aligned;" ::: "memory");
        {
            const uint32_t one = blockIdx.y + 1;
            uint32_t bw[2][4], z0[4], z1[4];
            mbar_wait(sb + BAR_SE);
            lds128(bw[0], sb + SEOFF + lane * 16);
            lds128(bw[1], sb + SEOFF + 512 + lane * 16);
            asm volatile("bar.sync 2, 384;" ::: "memory");
            lds128(z0, sb + ZQOFF + (tid & 127) * 16);
            lds128(z1, sb + ZQOFF + 2048 + (tid & 127) * 16);
            TS(8);
            float s[2][4] = {};
#pragma unroll
            for (int n = 0; n < 2; n++) {
                mma16816(s[n], z0, bw[0][2 * n], bw[0][2 * n + 1]);
                mma16816(s[n], z1, bw[1][2 * n], bw[1][2 * n + 1]);
            }
            lds128(bw[0], sb + SEOFF + 1024 + lane * 16);
            lds128(bw[1], sb + SEOFF + 1536 + lane * 16);
            float th[8];
#pragma unroll
            for (int k = 0; k < 8; k++) th[k] = gelu_tanh(s[k >> 2][k & 3]);
            SCHED_FENCE();
            TS(9);
            uint32_t gq[4];
#pragma unroll
            for (int k = 0; k < 4; k++)
                gq[k] = pack(s[k >> 1][2 * (k & 1)] * ffma(th[2 * k], 0.5f, 0.5f), s[k >> 1][2 * (k & 1) + 1] * ffma(th[2 * k + 1], 0.5f, 0.5f));
            float a[4][4] = {};
#pragma unroll
            for (int n = 0; n < 4; n++) mma16816(a[n], gq, bw[n >> 1][2 * (n & 1)], bw[n >> 1][2 * (n & 1) + 1]);
#pragma unroll
            for (int k = 0; k < 16; k++)
                if (k < 13 || k == 14) a[k >> 2][k & 3] = tanh_fast(a[k >> 2][k & 3]);
            SCHED_FENCE();
            TS(10);
            uint32_t ap[8];
#pragma unroll
            for (int k = 0; k < 8; k++)
                ap[k] = pack(ffma(a[k >> 1][2 * (k & 1)], 0.5f, 0.5f), ffma(a[k >> 1][2 * (k & 1) + (k < 6)], 0.5f, 0.5f));
            sts128(sb + GOFF + (tid & 127) * 16, ap[0], ap[1], ap[2], ap[3]);
            sts128(sb + GOFF + 2048 + (tid & 127) * 16, ap[4], ap[5], ap[6], ap[7]);
            asm volatile("bar.arrive 3, 384;" ::: "memory");
            TS(11);
        }
        if (warp == 9) {
            load_wc(3);
            load_wc(4);
            mbar_wait(sb + BAR_TD);
            load_wc(5);
            if (lane < 16) TS_DUMP(3);
        } else if (warp == 10) {
            __nv_bfloat16* dst = out + cta * 32 + lane;
            asm volatile("" : "+l"(dst));
            asm volatile("bar.sync 4, 64;" ::: "memory");
            mbar_wait(sb + BAR_FIN);
            uint32_t p[4];
            lds128(p, sb + PARTOFF + lane * 16);
            *dst = __float2bfloat16((__uint_as_float(p[0]) + __uint_as_float(p[1])) + (__uint_as_float(p[2]) + __uint_as_float(p[3])));
        }
    } else {
        asm volatile("setmaxnreg.inc.sync.aligned.u32 232;");
        asm volatile("barrier.cluster.arrive.relaxed.aligned;" ::: "memory");
        const int g = lane >> 2, t = lane & 3, wq = warp & 3, t128 = tid & 127;
        gd0 = opaque(gd0);
        TS(28);
        float acc[84];
#pragma unroll
        for (int k = 0; k < 84; k++) asm volatile("mov.b32 %0, 0;" : "=f"(acc[k]));
        uint32_t e0[9], e1[9], e2[9];
        uint32_t X[14][2][4];
        uint32_t zq[4] = {0, 0, 0, 0};
        const uint64_t dA = mkdesc(sb + w * XDELTA, 16, 1024, 1);
        uint32_t dBlo = (uint32_t)mkdesc(sb + ZOFF, 0, 0, 0);
        const uint32_t xl0 = opaque(sb + (t & 1) * XDELTA + (16 * wq + g) * 128 + (((4 * rank + 2 * w) ^ (4 * (t & 1)) ^ g) << 4));
        const uint32_t hi_half = t >> 1;
        const uint32_t sa0 = opaque(sb + AOFF + t * 4096 + (t >> 1) * 16 + (wq * 32 + g * 4 + w) * 16);
        const uint32_t sa1 = opaque(((g & 2) << 4) | ((t & 1) << 3));
        const uint32_t zero = blockIdx.y, one = zero + 1;
        auto expand = [&](int k0, int k1) {
#pragma unroll
            for (int k = k0; k < k1; k++)
#pragma unroll
                for (int u = 0; u < 4; u++)
                    asm volatile("shfl.sync.idx.b32 %0, %1, %2, 31, 0xffffffff;"
                                 : "=r"(ids[k][u])
                                 : "r"(k < 12 ? cid[(k - 2) >> 2][k & 1] : w ? cid[2][1] : cid[2][0]),
                                   "r"(2 * (lane >> 3) + 8 * u + (((k - 2) >> 1) & 1)));
        };
        auto twarm = [&]() {
            float s1[8];
            WG_FENCE();
            wgmma_rs_n16_set(s1, zq, mkdesc(sb + AOFF, 16, 512, 2));
            WG_COMMIT();
            WG_WAIT0();
            pin(s1);
            asm volatile("{.reg .pred p; setp.ne.u32 p, %1, 0; @p st.shared.f32 [%1], %0;}" ::"f"(s1[0]), "r"(zero));
        };
        expand(2, 8);
        if (TWARM & 1) twarm();
        TS(26);
        while (clock32() - c0 < PACE1) {
        }
        gather(1);
        expand(8, 13);
        if (TWARM & 2) twarm();
        TS(30);
        while (clock32() - c0 < PACE2) {
        }
        gather(2);
        if (TWARM & 4) twarm();
        asm volatile("bar.sync 0, 384;" ::: "memory");
        auto lift = [&](int i) {
            const int m = 2 * (i >> 2) + (i & 1);
#pragma unroll
            for (int r = 0; r < 2; r++)
#pragma unroll
                for (int cc = 0; cc < 2; cc++) {
                    const uint32_t a = (xl0 ^ (cc * 16)) + xpair(i) + r * 1024;
                    if (i & 2) lds128_if(X[2 * m + r][cc], a, hi_half);
                    else lds128(X[2 * m + r][cc], a);
                }
        };
        auto store_pair = [&](int m, int half, const uint32_t (&ea)[9]) {
            uint32_t a;
            if (m < 4) a = sa0 + (sa1 ^ (((m & 1) << 5) | ((m >> 1) << 3)));
            else a = sb + BOFF + t * 2048 + (wq * 32 + g * 4 + ((2 * (m & 1) + w) ^ t)) * 8;
#pragma unroll
            for (int n = half; n < 4; n += 2)
#pragma unroll
                for (int u = 0; u < 2; u++)
                    sts64(a + (m < 4 ? (8 * n + u) * 2048 + n * 32 : (8 * n + u) * 1024),
                          __byte_perm(ea[2 * n], e1[2 * n], u ? 0x7632 : 0x5410),
                          __byte_perm(ea[2 * n + 1], e1[2 * n + 1], u ? 0x7632 : 0x5410));
        };
        auto z_pair = [&](int m, uint32_t a, uint32_t b) {
            asm volatile("{.reg .pred p; setp.eq.u32 p, %4, %5; @p prmt.b32 %0, %2, %3, 0x5410; @p prmt.b32 %1, %2, %3, 0x7632;}"
                         : "+r"(zq[2 * (m >> 2)]), "+r"(zq[2 * (m >> 2) + 1])
                         : "r"(a), "r"(b), "r"(t), "r"(m & 3));
        };

        TS(29);
        mbar_wait(sb + BAR_FULL + w * 8);
        CP_WAIT(2);
        if (w == 1) {
            asm volatile("bar.arrive 6, 256;" ::: "memory");
            asm volatile("bar.sync 5, 256;" ::: "memory");
        }
#pragma unroll
        for (int i = 0; i < 13; i++) {
            const uint64_t da = dA + (xpair(i) >> 4) + ((uint64_t)i << 16);
            dBlo += (uint32_t)(w ? wl(2 * i + 1) - (i ? wl(2 * i - 1) : 0) : wl(2 * i) - (i ? wl(2 * i - 2) : 0)) *
                    (uint32_t)((SLOT << 12) - (SLOT >> 3));
            const uint64_t db = mkdesc(0, 0, 1024, 1) | dBlo;
            TS(i);
            WG_FENCE();
            wgmma_ss_n168_acc(acc, da, db + w * 256);
            wgmma_ss_n168_acc(acc, da + 2, db + w * 256 + 128);
            wgmma_ss_n168_acc(acc, da + 4, db + (w ^ 1) * 256);
            wgmma_ss_n168_acc(acc, da + 6, db + (w ^ 1) * 256 + 128);
            WG_COMMIT();
            if (i == 0) {
                if (w == 0) {
                    asm volatile("bar.arrive 5, 256;" ::: "memory");
                    asm volatile("bar.sync 6, 256;" ::: "memory");
                }
            } else {
                mbar_wait(sb + bdone(2 * i - 2) + (w ^ 1) * 8, bpar(2 * i - 2));
            }
            if (i < 10) gather(i + 3);
            if (i == 1) asm volatile("barrier.cluster.wait.aligned;" ::: "memory");
            if (i == 6) mbar_wait(sb + BAR_W2);
            lift(i);
            if (i == 10 || i == 11) mbar_wait(sb + bdone(2 * i - 2) + w * 8, bpar(2 * i - 2));
            if (i >= 2 && !(i & 1)) {
                z_pair((i - 2) >> 1, e0[8], e1[8]);
                store_pair((i - 2) >> 1, 0, e0);
#pragma unroll
                for (int k = 0; k < 8; k++) e2[k] = e0[k];
            } else if (i >= 3) {
                store_pair((i - 3) >> 1, 1, e2);
            }
            const uint32_t rdy = i < 12 ? mbar_test(sb + bfull(2 * i + 2) + w * 8, bpar(2 * i + 2)) : 0;
            WG_WAIT0();
            pin(acc);
            if (i == 12) TS(13);
            if (i == 0) TS(27);
            if (i < 10) CP_WAIT(2);
            else if (i == 10) CP_WAIT(1);
            else if (i == 11) CP_WAIT(0);
            if (i < 12 && lane == 0) mbar_arrive(sb + bdone(2 * i) + w * 8);
#pragma unroll
            for (int k = 0; k < 9; k++) {
                const uint32_t v = k < 8 ? pack(acc[64 + 2 * k], acc[65 + 2 * k]) : pack(acc[80], acc[82]);
                if (i & 1) e1[k] = v;
                else e0[k] = v;
            }
            if (i < 12) {
#pragma unroll
                for (int k = 64; k < 83; k++)
                    if (k != 81) asm volatile("mov.b32 %0, %1;" : "+f"(acc[k]) : "r"(zero));
                mbar_wait_unless(rdy, sb + bfull(2 * i + 2) + w * 8, bpar(2 * i + 2));
            } else {
                z_pair(6, e0[8], 0);
                sts128(sb + ZQOFF + w * 2048 + t128 * 16, zq[0], zq[1], zq[2], zq[3]);
                asm volatile("bar.arrive 2, 384;" ::: "memory");
            }
        }
        TS(14);

        float aj[14];
        uint32_t ai[8];
        float sum0 = 0.f, sum1 = 0.f;
        float th[32];
        uint32_t hw[4][4];
        auto deep_issue = [&](int k2) {
            lds128(hw[k2], ((sb + w2chunk(w * 16 + t)) ^ ((k2 & 1) * 64)) + k2 * 512);
#pragma unroll
            for (int k = 8 * k2; k < 8 * k2 + 8; k++) th[k] = gelu_tanh(acc[k]);
        };
        auto deep_use = [&](int k2) {
#pragma unroll
            for (int k = 8 * k2; k < 8 * k2 + 8; k++) {
                const float h = __uint_as_float(hw[k2][((k >> 1) & 2) + (k & 1)]);
                const float y = ffma(th[k], h, h);
                if (k & 2) sum1 = ffma(acc[k], y, sum1);
                else sum0 = ffma(acc[k], y, sum0);
            }
        };
        auto deep_send = [&]() {
#pragma unroll
            for (int k = 0; k < 4; k++)
                sts128(sb + EXOFF + w * SLOT + t128 * 16 + k * 2048, pack(acc[32 + 8 * k], acc[33 + 8 * k]),
                       pack(acc[34 + 8 * k], acc[35 + 8 * k]), pack(acc[36 + 8 * k], acc[37 + 8 * k]), pack(acc[38 + 8 * k], acc[39 + 8 * k]));
        };
        uint32_t o[4][4];
        auto deep_recv = [&]() {
#pragma unroll
            for (int k = 0; k < 4; k++) lds128(o[k], sb + EXOFF + (w ^ 1) * SLOT + t128 * 16 + k * 2048);
        };
        auto deep_add = [&]() {
            const uint32_t eye = (g >> 1) == t ? ((g & 1) ? 0x3f800000u : 0x3f80u) : 0u;
#pragma unroll
            for (int k = 0; k < 8; k++)
                asm volatile("mma.sync.aligned.m16n8k8.row.col.f32.bf16.bf16.f32 {%0,%1,%2,%3}, {%4,%5}, {%6}, {%0,%1,%2,%3};"
                             : "+f"(acc[4 * k]), "+f"(acc[4 * k + 1]), "+f"(acc[4 * k + 2]), "+f"(acc[4 * k + 3])
                             : "r"(o[k >> 1][2 * (k & 1)]), "r"(o[k >> 1][2 * (k & 1) + 1]), "r"(eye));
        };
        auto store_last = [&]() {
#pragma unroll
            for (int n = 0; n < 4; n++) sts64(sb + COFF + w * 4096 + n * 1024 + (t128 ^ w) * 8, e0[2 * n], e0[2 * n + 1]);
            store_pair(5, 1, e2);
        };
        const uint32_t la = sb + AOFF + w * (16 * 2048 + 64) + (wq * 32 + g * 4 + (t ^ (g & 2))) * 16;
        const uint32_t lb = sb + BOFF + w * (16 * 1024) + t128 * 8;
        const uint32_t lc0 = sb + COFF + (t & 1) * (4096 + 8) + w * 2048 + (wq * 8 + g) * 32, lc1 = lc0 ^ 8;
        uint32_t Ap[2][2][4];
        auto load_a = [&](int e) {
            lds128(Ap[e & 1][0], la + e * 2048 + (e >> 2) * 16);
            lds64(Ap[e & 1][1][0], Ap[e & 1][1][1], (lb ^ ((e & 6) * 4)) + e * 1024);
            lds64(Ap[e & 1][1][2], Ap[e & 1][1][3], ((e & 2) ? lc1 : lc0) + (e >> 3) * 1024 + (e & 4) * 4);
        };
        {
            deep_send();
            asm volatile("bar.sync 1, 256;" ::: "memory");
            deep_recv();
            TS(15);
            deep_add();
            deep_issue(0);
            SCHED_FENCE();
            TS(16);
            deep_issue(1);
            deep_use(0);
            store_last();
            SCHED_FENCE();
            TS(17);
            deep_issue(2);
            deep_use(1);
            mbar_wait(sb + BAR_WC);
            deep_use(2);
            TS(18);
            asm volatile("bar.sync 3, 384;" ::: "memory");
            uint32_t v[2][4];
            lds128(v[0], sb + GOFF + t128 * 16);
            lds128(v[1], sb + GOFF + 2048 + t128 * 16);
            load_a(0);
            load_a(1);
            deep_issue(3);
#pragma unroll
            for (int k = 0; k < 8; k++) ai[k] = v[k >> 2][k & 3];
#pragma unroll
            for (int q = 0; q < 14; q++) {
                const uint32_t x = ai[2 * (q >> 2) + (q & 1)];
                aj[q] = __uint_as_float((q & 2) ? x & 0xffff0000u : x << 16);
            }
        }
        TS(19);

        uint32_t fin_a, dsum[2];
        {
            const uint64_t dW = mkdesc(sb + w * 4096, 16, 512, 2);
            uint32_t Aq[2][2][4], hacc[2][4], V[14];
            float Sp[16], Sq[16], U[14];
            auto scale_a = [&](int e) {
#pragma unroll
                for (int k = 0; k < 8; k++) Aq[e & 1][k >> 2][k & 3] = hmul2(Ap[e & 1][k >> 2][k & 3], ai[k < 4 ? k ^ (e & 2) : k]);
            };
            auto dot = [&](int e) {
#pragma unroll
                for (int q = 0; q < 14; q++) {
                    const uint32_t x = X[q][e >> 3][(e & 7) >> 1];
                    if ((e & 6) == 0 && q < 4) hacc[e >> 3][q] = hmul2(V[q], x);
                    else hacc[e >> 3][q & 3] = hfma2(V[q], x, hacc[e >> 3][q & 3]);
                }
            };
            scale_a(0);
            if (w == 1) {
                const uint32_t c1 = clock32();
                while (clock32() - c1 < P2_SKEW) {
                }
            }
#pragma unroll
            for (int e = 0; e < 16; e++) {
                const uint64_t d = dW + (wcslot(e) >> 4);
                WG_FENCE();
                if (e == 0) wgmma_rs_n32_set(Sp, Ap[e & 1][0], d);
                else wgmma_rs_n32_pred(Sp, Ap[e & 1][0], d, zero);
                wgmma_rs_n32_acc(Sp, Ap[e & 1][1], d + 2);
                if (e == 0) wgmma_rs_n32_set(Sq, Aq[e & 1][0], d + 128);
                else wgmma_rs_n32_pred(Sq, Aq[e & 1][0], d + 128, zero);
                wgmma_rs_n32_acc(Sq, Aq[e & 1][1], d + 130);
                WG_COMMIT();
                SCHED_FENCE();
                if (e == 0) deep_use(3);
                if (e > 0 && !(e & 1)) dot(e - 1);
                if (e == 1) {
                    const float h0 = __uint_as_float(__float_as_uint(sum0) & 0xffff0000u);
                    const float h1 = __uint_as_float(__float_as_uint(sum1) & 0xffff0000u);
                    dsum[0] = pack(sum0 - h0, h0);
                    dsum[1] = pack(sum1 - h1, h1);
                }
                if (e == 13) {
                    asm("mapa.shared::cluster.u32 %0, %1, %2;"
                        : "=r"(fin_a)
                        : "r"(sb + PARTOFF + (((wq & 1) * 16 + t * 8 + g) * 4 + 2 * rank + w) * 4), "r"(wq >> 1));
                    fin_a = opaque(fin_a);
                }
                if (e == 15 && warp == 0) asm volatile("bar.arrive 4, 64;" ::: "memory");
                if (e + 1 < 16) scale_a(e + 1);
                if (e == 0 || e == 1 || e == 4 || e == 7 || e == 10)
                    mbar_wait(sb + BAR_WC + (e == 0 ? 1 : e == 1 ? 2 : e == 4 ? 3 : e == 7 ? 4 : 5) * 8);
                else if (e < 15)
                    SCHED_FENCE();
                WG_WAIT0();
                pin(Sp);
                pin(Sq);
                if (e == 0 && lane == 0) mbar_arrive(sb + BAR_TD);
                if (e == 0) TS(20);
                if (e + 2 < 16) load_a(e + 2);
#pragma unroll
                for (int q = 0; q < 14; q++) {
                    const int ix = 4 * (q >> 2) + 2 * (q & 1) + ((q >> 1) & 1);
                    const float u = ffma(aj[q], Sq[ix], Sp[ix]);
                    if (!(e & 1)) U[q] = u;
                    else V[q] = pack(U[q], u);
                }
                if (e == 7) TS(21);
            }
            float r[4] = {0.f, 0.f, 0.f, 0.f};
            asm volatile("mma.sync.aligned.m16n8k8.row.col.f32.bf16.bf16.f32 {%0,%1,%2,%3}, {%4,%5}, {%6}, {%0,%1,%2,%3};"
                         : "+f"(r[0]), "+f"(r[1]), "+f"(r[2]), "+f"(r[3])
                         : "r"(dsum[0]), "r"(dsum[1]), "r"(0x3f803f80u));
            mma16816(r, hacc[0], 0x3f803f80u, 0x3f803f80u);
            dot(15);
            mma16816(r, hacc[1], 0x3f803f80u, 0x3f803f80u);
            sum0 = r[0];
            sum1 = r[2];
        }
        TS(22);
        {
            const float v = (t & 1) ? sum1 : sum0;
            asm volatile(
                "{.reg .pred p; setp.lt.u32 p, %3, 2; @p st.async.shared::cluster.mbarrier::complete_tx::bytes.f32 [%0], %1, [%2];}" ::"r"(fin_a),
                "f"(v), "r"((fin_a & ~0x3ffu) + (BAR_FIN & 0x3ff)), "r"(t)
                : "memory");
            if (wq == 0) TS_DUMP(w);
        }
    }
}

typedef CUresult (*EncodeFn)(CUtensorMap*, CUtensorMapDataType, cuuint32_t, void*, const cuuint64_t*, const cuuint64_t*,
                             const cuuint32_t*, const cuuint32_t*, CUtensorMapInterleave, CUtensorMapSwizzle,
                             CUtensorMapL2promotion, CUtensorMapFloatOOBfill);

}

extern "C" void kernel_launch(void* const* d_in, const int* in_sizes, int n_in, void* d_out, int out_size) {
    static EncodeFn encode = nullptr;
    if (!encode) {
        void* fn = nullptr;
        cudaDriverEntryPointQueryResult qr;
        cudaGetDriverEntryPoint("cuTensorMapEncodeTiled", &fn, cudaEnableDefault, &qr);
        encode = (EncodeFn)fn;
        cudaFuncSetAttribute(fibinet_kernel, cudaFuncAttributeMaxDynamicSharedMemorySize, SMEM_BYTES);
    }
    CUtensorMap tm;
    const cuuint64_t gd[2] = {NH, NF * ND};
    const cuuint64_t gs[1] = {NH * 2};
    const cuuint32_t bd[2] = {64, 64}, es[2] = {1, 1};
    encode(&tm, CU_TENSOR_MAP_DATA_TYPE_BFLOAT16, 2, d_in[6], gd, gs, bd, es, CU_TENSOR_MAP_INTERLEAVE_NONE,
           CU_TENSOR_MAP_SWIZZLE_128B, CU_TENSOR_MAP_L2_PROMOTION_L2_256B, CU_TENSOR_MAP_FLOAT_OOB_FILL_NONE);
    CUtensorMap tb;
    const cuuint64_t gd2[2] = {ND, ND};
    const cuuint64_t gs2[1] = {ND * 2};
    encode(&tb, CU_TENSOR_MAP_DATA_TYPE_BFLOAT16, 2, d_in[4], gd2, gs2, bd, es, CU_TENSOR_MAP_INTERLEAVE_NONE,
           CU_TENSOR_MAP_SWIZZLE_128B, CU_TENSOR_MAP_L2_PROMOTION_L2_256B, CU_TENSOR_MAP_FLOAT_OOB_FILL_NONE);
    fibinet_kernel<<<NPREP + NMAIN, 384, SMEM_BYTES>>>(
        (const int*)d_in[0], (const uint4*)d_in[1], (const __nv_bfloat16*)d_in[2], (const __nv_bfloat16*)d_in[3],
        (const __nv_bfloat16*)d_in[5], (const unsigned char*)d_in[6], (const __nv_bfloat16*)d_in[7], (__nv_bfloat16*)d_out, tm, tb);
}
```

```cpp
#include <cuda_runtime.h>
#include <cuda_bf16.h>
#include <cuda.h>
#include <stdint.h>

namespace {

constexpr int NB = 4096, NF = 26, ND = 64, NH = 256, NR = 13;
constexpr int NPREP = 4;
constexpr int NMAIN = 128;

constexpr int SLOT = 8192;
constexpr int ZOFF = 15 * SLOT;
__host__ __device__ constexpr int slot(int s) { return ZOFF - s * SLOT; }
constexpr int BOFF = ZOFF + SLOT;
constexpr int AOFF = BOFF + 32768;
constexpr int COFF = slot(12);
constexpr int MOFF = AOFF + 65536 + 128;
constexpr int BAR_FULL = MOFF, BAR_DONE = MOFF + 64, BAR_WC = MOFF + 128, BAR_FIN = MOFF + 176,
              BAR_GO = MOFF + 184, BAR_SE = MOFF + 192, BAR_W2 = MOFF + 200, BAR_TD = MOFF + 208, BAR_Z = MOFF + 216;
__host__ __device__ constexpr int bfull(int f) { return BAR_FULL + (f & 7) * 8; }
__host__ __device__ constexpr int bdone(int f) { return BAR_DONE + (f & 7) * 8; }
__host__ __device__ constexpr int bpar(int f) { return (f >> 3) & 1; }
constexpr int PARTOFF = MOFF + 256, SEOFF = MOFF + 768;
constexpr int SMEM_BYTES = MOFF + 2944;
static_assert((BAR_FIN >> 10) == (PARTOFF >> 10) && (BAR_FIN >> 10) == ((PARTOFF + 511) >> 10), "same 1 KB block");
constexpr int XDELTA = 2 * SLOT;
__host__ __device__ constexpr int xpair(int i) {
    return (i & 3) == 0 ? slot(11) : (i & 3) == 1 ? BOFF : (i & 3) == 2 ? BOFF + SLOT : slot(15);
}
__host__ __device__ constexpr int wl(int f) { return f % 5 == 0 ? 1 : f % 5 == 4 ? 7 : f % 5 + 2; }
__host__ __device__ constexpr int wcslot(int c) {
    return c == 0 ? slot(3) : c == 1 ? slot(8) : c == 2 ? slot(10) : c == 3 ? slot(15) : c == 4 ? slot(13)
         : c == 5 ? slot(11) : c == 6 ? slot(9) : c == 7 ? slot(14) : c == 8 ? slot(7) : c == 9 ? slot(2)
         : c == 10 ? slot(1) : c == 11 ? slot(4) : c == 12 ? slot(5) : c == 13 ? slot(6) : c == 14 ? ZOFF : slot(3);
}
__host__ __device__ constexpr int wcfirst(int gi) { return gi < 3 ? gi : gi == 3 ? 5 : gi == 4 ? 8 : gi == 5 ? 11 : 16; }
constexpr int EXOFF = slot(5);
constexpr int ZQOFF = slot(6);
constexpr int GOFF = ZQOFF + 4096;
__host__ __device__ constexpr int w2chunk(int c) { return ZOFF + c * 128 + ((5 ^ (c & 7)) << 4); }

__device__ uint4 g_wc[2 * 16 * 8192 / 16];
__device__ uint4 g_se[2048 / 16];
__device__ unsigned g_ready;
__device__ unsigned g_seen;

__host__ __device__ constexpr int fieldof(int f) { return f < 24 ? 4 * (f >> 2) + 2 * (f & 1) + ((f >> 1) & 1) : f; }
__device__ __forceinline__ int fmap(int n) { return n < 24 ? n : n < 28 ? 24 + ((n >> 1) & 1) : -1; }

__device__ __forceinline__ uint64_t mkdesc(uint32_t addr, uint32_t lbo, uint32_t sbo, int sw) {
    return (uint64_t)((addr & 0x3ffff) >> 4) | ((uint64_t)(lbo >> 4) << 16) | ((uint64_t)(sbo >> 4) << 32) |
           ((uint64_t)sw << 62);
}
__device__ __forceinline__ void mbar_init(uint32_t b, uint32_t n) {
    asm volatile("mbarrier.init.shared.b64 [%0], %1;" ::"r"(b), "r"(n) : "memory");
}
__device__ __forceinline__ void mbar_wait(uint32_t b, uint32_t par = 0) {
    asm volatile(
        "{\n.reg .pred p, q;\n.reg .u32 n;\n"
        "mbarrier.try_wait.parity.shared.b64 p, [%0], %1;\n@p bra.uni WD%=;\nmov.u32 n, 0;\n"
        "WL%=:\nmbarrier.try_wait.parity.shared.b64 p, [%0], %1;\n@p bra.uni WD%=;\n"
        "add.u32 n, n, 1;\nsetp.lt.u32 q, n, 4000000;\n@q bra.uni WL%=;\nWD%=:\n}\n" ::"r"(b), "r"(par)
        : "memory");
}
__device__ __forceinline__ uint32_t mbar_test(uint32_t b, uint32_t par) {
    uint32_t ok;
    asm volatile("{.reg .pred p; mbarrier.test_wait.parity.shared.b64 p, [%1], %2; selp.u32 %0, 1, 0, p;}"
                 : "=r"(ok)
                 : "r"(b), "r"(par)
                 : "memory");
    return ok;
}
__device__ __forceinline__ void mbar_wait_unless(uint32_t ok, uint32_t b, uint32_t par) {
    asm volatile(
        "{\n.reg .pred p, q;\n.reg .u32 n;\n"
        "setp.ne.u32 p, %1, 0;\n@p bra.uni WD%=;\nmov.u32 n, 0;\n"
        "WL%=:\nmbarrier.try_wait.parity.shared.b64 p, [%0], %2;\n@p bra.uni WD%=;\n"
        "add.u32 n, n, 1;\nsetp.lt.u32 q, n, 4000000;\n@q bra.uni WL%=;\nWD%=:\n}\n" ::"r"(b), "r"(ok), "r"(par)
        : "memory");
}
__device__ __forceinline__ void mbar_arrive(uint32_t b) {
    asm volatile("mbarrier.arrive.shared.b64 _, [%0];" ::"r"(b) : "memory");
}
__device__ __forceinline__ void mbar_expect(uint32_t b, uint32_t bytes) {
    asm volatile("mbarrier.arrive.expect_tx.shared.b64 _, [%0], %1;" ::"r"(b), "r"(bytes) : "memory");
}
__device__ __forceinline__ uint32_t opaque(uint32_t v) { return __shfl_sync(0xffffffffu, v, threadIdx.x); }
__device__ __forceinline__ bool elect() {
    uint32_t p;
    asm volatile("{.reg .pred q; elect.sync _|q, 0xffffffff; selp.u32 %0, 1, 0, q;}" : "=r"(p));
    return p;
}
__device__ __forceinline__ void tma2d(uint32_t dst, const CUtensorMap* m, uint32_t bar, int x, int y) {
    asm volatile(
        "cp.async.bulk.tensor.2d.shared::cluster.global.mbarrier::complete_tx::bytes [%0], [%1, {%3, %4}], [%2];" ::"r"(dst),
        "l"(m), "r"(bar), "r"(x), "r"(y)
        : "memory");
}
__device__ __forceinline__ void bulk(uint32_t dst, const void* src, uint32_t bytes, uint32_t bar) {
    asm volatile("cp.async.bulk.shared::cluster.global.mbarrier::complete_tx::bytes [%0], [%1], %2, [%3];" ::"r"(dst),
                 "l"(src), "r"(bytes), "r"(bar)
                 : "memory");
}
__device__ __forceinline__ void cp16(uint32_t dst, const void* src) {
    asm volatile("cp.async.cg.shared.global [%0], [%1], 16;" ::"r"(dst), "l"(src) : "memory");
}
__device__ __forceinline__ void lds128(uint32_t (&v)[4], uint32_t a) {
    asm volatile("ld.shared.v4.u32 {%0,%1,%2,%3}, [%4];" : "=r"(v[0]), "=r"(v[1]), "=r"(v[2]), "=r"(v[3]) : "r"(a) : "memory");
}
__device__ __forceinline__ void lds128_if(uint32_t (&v)[4], uint32_t a, uint32_t p) {
    asm volatile("{.reg .pred q; setp.ne.u32 q, %5, 0; @q ld.shared.v4.u32 {%0,%1,%2,%3}, [%4];}"
                 : "+r"(v[0]), "+r"(v[1]), "+r"(v[2]), "+r"(v[3])
                 : "r"(a), "r"(p)
                 : "memory");
}
__device__ __forceinline__ void lds64(uint32_t& x, uint32_t& y, uint32_t a) {
    asm volatile("ld.shared.v2.u32 {%0,%1}, [%2];" : "=r"(x), "=r"(y) : "r"(a) : "memory");
}
__device__ __forceinline__ void sts128(uint32_t a, uint32_t x, uint32_t y, uint32_t z, uint32_t w) {
    asm volatile("st.shared.v4.u32 [%0], {%1,%2,%3,%4};" ::"r"(a), "r"(x), "r"(y), "r"(z), "r"(w) : "memory");
}
__device__ __forceinline__ void sts64(uint32_t a, uint32_t x, uint32_t y) {
    asm volatile("st.shared.v2.u32 [%0], {%1,%2};" ::"r"(a), "r"(x), "r"(y) : "memory");
}
__device__ __forceinline__ uint32_t pack(float lo, float hi) {
    uint32_t r;
    asm volatile("cvt.rn.bf16x2.f32 %0, %1, %2;" : "=r"(r) : "f"(hi), "f"(lo));
    return r;
}
__device__ __forceinline__ uint32_t hmul2(uint32_t a, uint32_t b) {
    uint32_t r;
    asm volatile("mul.rn.bf16x2 %0, %1, %2;" : "=r"(r) : "r"(a), "r"(b));
    return r;
}
__device__ __forceinline__ uint32_t hfma2(uint32_t a, uint32_t b, uint32_t c) {
    uint32_t r;
    asm volatile("fma.rn.bf16x2 %0, %1, %2, %3;" : "=r"(r) : "r"(a), "r"(b), "r"(c));
    return r;
}
__device__ __forceinline__ float ffma(float a, float b, float c) {
    float r;
    asm volatile("fma.rn.f32 %0, %1, %2, %3;" : "=f"(r) : "f"(a), "f"(b), "f"(c));
    return r;
}
__device__ __forceinline__ float tanh_fast(float x) {
    float r;
    asm volatile("tanh.approx.f32 %0, %1;" : "=f"(r) : "f"(x));
    return r;
}
__device__ __forceinline__ float gelu_tanh(float x) {
    float r;
    asm volatile(
        "{.reg .f32 a; mul.f32 a, %1, %1; fma.rn.f32 a, a, 0f3D122279, 0f3F4C422A; mul.f32 a, a, %1; tanh.approx.f32 %0, a;}"
        : "=f"(r)
        : "f"(x));
    return r;
}
__device__ __forceinline__ void mma16816(float (&d)[4], const uint32_t (&a)[4], uint32_t b0, uint32_t b1) {
    asm volatile("mma.sync.aligned.m16n8k16.row.col.f32.bf16.bf16.f32 {%0,%1,%2,%3}, {%4,%5,%6,%7}, {%8,%9}, {%0,%1,%2,%3};"
                 : "+f"(d[0]), "+f"(d[1]), "+f"(d[2]), "+f"(d[3])
                 : "r"(a[0]), "r"(a[1]), "r"(a[2]), "r"(a[3]), "r"(b0), "r"(b1));
}
__device__ __forceinline__ uint32_t clock32() {
    uint32_t c;
    asm volatile("mov.u32 %0, %%clock;" : "=r"(c)::"memory");
    return c;
}
#define WG_FENCE() asm volatile("wgmma.fence.sync.aligned;" ::: "memory")
#define WG_COMMIT() asm volatile("wgmma.commit_group.sync.aligned;" ::: "memory")
#define WG_WAIT0() asm volatile("wgmma.wait_group.sync.aligned 0;" ::: "memory")
#define CP_COMMIT() asm volatile("cp.async.commit_group;" ::: "memory")
#define CP_WAIT(n) asm volatile("cp.async.wait_group %0;" ::"n"(n) : "memory")
#define SCHED_FENCE() asm volatile("pmevent 0;" ::: "memory")
#define PROXY_FENCE() asm volatile("fence.proxy.async.shared::cta;" ::: "memory")
template <int N>
__device__ __forceinline__ void pin(float (&d)[N]) {
#pragma unroll
    for (int i = 0; i < N; i++) asm volatile("" : "+f"(d[i])::"memory");
}
#define TS(k)
#define TS_DUMP(role)

__device__ __forceinline__ void wgmma_ss_n168_acc(float (&d)[84], uint64_t da, uint64_t db) {
    asm volatile(
        "wgmma.mma_async.sync.aligned.m64n168k16.f32.bf16.bf16 "
        "{%0,%1,%2,%3,%4,%5,%6,%7,%8,%9,%10,%11,%12,%13,%14,%15,"
        "%16,%17,%18,%19,%20,%21,%22,%23,%24,%25,%26,%27,%28,%29,%30,%31,"
        "%32,%33,%34,%35,%36,%37,%38,%39,%40,%41,%42,%43,%44,%45,%46,%47,"
        "%48,%49,%50,%51,%52,%53,%54,%55,%56,%57,%58,%59,%60,%61,%62,%63,"
        "%64,%65,%66,%67,%68,%69,%70,%71,%72,%73,%74,%75,%76,%77,%78,%79,"
        "%80,%81,%82,%83}, "
        "%84, %85, 1, 1, 1, 0, 1;"
        : "+f"(d[0]), "+f"(d[1]), "+f"(d[2]), "+f"(d[3]), "+f"(d[4]), "+f"(d[5]), "+f"(d[6]), "+f"(d[7]),
          "+f"(d[8]), "+f"(d[9]), "+f"(d[10]), "+f"(d[11]), "+f"(d[12]), "+f"(d[13]), "+f"(d[14]), "+f"(d[15]),
          "+f"(d[16]), "+f"(d[17]), "+f"(d[18]), "+f"(d[19]), "+f"(d[20]), "+f"(d[21]), "+f"(d[22]), "+f"(d[23]),
          "+f"(d[24]), "+f"(d[25]), "+f"(d[26]), "+f"(d[27]), "+f"(d[28]), "+f"(d[29]), "+f"(d[30]), "+f"(d[31]),
          "+f"(d[32]), "+f"(d[33]), "+f"(d[34]), "+f"(d[35]), "+f"(d[36]), "+f"(d[37]), "+f"(d[38]), "+f"(d[39]),
          "+f"(d[40]), "+f"(d[41]), "+f"(d[42]), "+f"(d[43]), "+f"(d[44]), "+f"(d[45]), "+f"(d[46]), "+f"(d[47]),
          "+f"(d[48]), "+f"(d[49]), "+f"(d[50]), "+f"(d[51]), "+f"(d[52]), "+f"(d[53]), "+f"(d[54]), "+f"(d[55]),
          "+f"(d[56]), "+f"(d[57]), "+f"(d[58]), "+f"(d[59]), "+f"(d[60]), "+f"(d[61]), "+f"(d[62]), "+f"(d[63]),
          "+f"(d[64]), "+f"(d[65]), "+f"(d[66]), "+f"(d[67]), "+f"(d[68]), "+f"(d[69]), "+f"(d[70]), "+f"(d[71]),
          "+f"(d[72]), "+f"(d[73]), "+f"(d[74]), "+f"(d[75]), "+f"(d[76]), "+f"(d[77]), "+f"(d[78]), "+f"(d[79]),
          "+f"(d[80]), "+f"(d[81]), "+f"(d[82]), "+f"(d[83])
        : "l"(da), "l"(db));
}

__device__ __forceinline__ void wgmma_rs_n32_set(float (&d)[16], const uint32_t (&a)[4], uint64_t db) {
    asm volatile(
        "wgmma.mma_async.sync.aligned.m64n32k16.f32.bf16.bf16 "
        "{%0,%1,%2,%3,%4,%5,%6,%7,%8,%9,%10,%11,%12,%13,%14,%15}, "
        "{%16,%17,%18,%19}, %20, 0, 1, 1, 0;"
        : "=f"(d[0]), "=f"(d[1]), "=f"(d[2]), "=f"(d[3]), "=f"(d[4]), "=f"(d[5]), "=f"(d[6]), "=f"(d[7]),
          "=f"(d[8]), "=f"(d[9]), "=f"(d[10]), "=f"(d[11]), "=f"(d[12]), "=f"(d[13]), "=f"(d[14]), "=f"(d[15])
        : "r"(a[0]), "r"(a[1]), "r"(a[2]), "r"(a[3]), "l"(db));
}

__device__ __forceinline__ void wgmma_rs_n32_acc(float (&d)[16], const uint32_t (&a)[4], uint64_t db) {
    asm volatile(
        "wgmma.mma_async.sync.aligned.m64n32k16.f32.bf16.bf16 "
        "{%0,%1,%2,%3,%4,%5,%6,%7,%8,%9,%10,%11,%12,%13,%14,%15}, "
        "{%16,%17,%18,%19}, %20, 1, 1, 1, 0;"
        : "+f"(d[0]), "+f"(d[1]), "+f"(d[2]), "+f"(d[3]), "+f"(d[4]), "+f"(d[5]), "+f"(d[6]), "+f"(d[7]),
          "+f"(d[8]), "+f"(d[9]), "+f"(d[10]), "+f"(d[11]), "+f"(d[12]), "+f"(d[13]), "+f"(d[14]), "+f"(d[15])
        : "r"(a[0]), "r"(a[1]), "r"(a[2]), "r"(a[3]), "l"(db));
}

__device__ __forceinline__ void wgmma_rs_n16_set(float (&d)[8], const uint32_t (&a)[4], uint64_t db) {
    asm volatile(
        "wgmma.mma_async.sync.aligned.m64n16k16.f32.bf16.bf16 "
        "{%0,%1,%2,%3,%4,%5,%6,%7}, "
        "{%8,%9,%10,%11}, %12, 0, 1, 1, 0;"
        : "=f"(d[0]), "=f"(d[1]), "=f"(d[2]), "=f"(d[3]), "=f"(d[4]), "=f"(d[5]), "=f"(d[6]), "=f"(d[7])
        : "r"(a[0]), "r"(a[1]), "r"(a[2]), "r"(a[3]), "l"(db));
}

__device__ __forceinline__ void wgmma_rs_n16_acc(float (&d)[8], const uint32_t (&a)[4], uint64_t db) {
    asm volatile(
        "wgmma.mma_async.sync.aligned.m64n16k16.f32.bf16.bf16 "
        "{%0,%1,%2,%3,%4,%5,%6,%7}, "
        "{%8,%9,%10,%11}, %12, 1, 1, 1, 0;"
        : "+f"(d[0]), "+f"(d[1]), "+f"(d[2]), "+f"(d[3]), "+f"(d[4]), "+f"(d[5]), "+f"(d[6]), "+f"(d[7])
        : "r"(a[0]), "r"(a[1]), "r"(a[2]), "r"(a[3]), "l"(db));
}

__device__ __forceinline__ void wgmma_rs_n32_pred(float (&d)[16], const uint32_t (&a)[4], uint64_t db, uint32_t scale_d) {
    asm volatile(
        "{.reg .pred p; setp.ne.u32 p, %21, 0; wgmma.mma_async.sync.aligned.m64n32k16.f32.bf16.bf16 "
        "{%0,%1,%2,%3,%4,%5,%6,%7,%8,%9,%10,%11,%12,%13,%14,%15}, "
        "{%16,%17,%18,%19}, %20, p, 1, 1, 0;}"
        : "+f"(d[0]), "+f"(d[1]), "+f"(d[2]), "+f"(d[3]), "+f"(d[4]), "+f"(d[5]), "+f"(d[6]), "+f"(d[7]),
          "+f"(d[8]), "+f"(d[9]), "+f"(d[10]), "+f"(d[11]), "+f"(d[12]), "+f"(d[13]), "+f"(d[14]), "+f"(d[15])
        : "r"(a[0]), "r"(a[1]), "r"(a[2]), "r"(a[3]), "l"(db), "r"(scale_d));
}

__device__ __forceinline__ void prep_cta(uint32_t sb, int c, const __nv_bfloat16* __restrict__ wc,
                                         const __nv_bfloat16* __restrict__ se1, const __nv_bfloat16* __restrict__ se2) {
    const int tid = threadIdx.x, lane = tid & 31, warp = tid >> 5;
    constexpr int NROW = 2 * NF * NF;
#pragma unroll
    for (int q = tid; q < NROW * 2; q += 384) cp16(sb + q * 16, wc + (q >> 1) * ND + c * 16 + (q & 1) * 8);
    if (tid == 0) sts128(sb + NROW * 32, 0, 0, 0, 0);
    if (tid < 256) {
        const int l2 = c >> 1, n = ((tid >> 2) & 1) * 8 + (tid >> 5) + (l2 ? (c & 1) * 16 : 0);
        const int k = ((tid >> 1) & 1) * 8 + ((tid >> 3) & 3) * 2 + (tid & 1), mm = k >> 1, u = k & 1;
        const int f = l2 ? fmap(n) : mm < 6 ? 4 * mm + 2 * c + u : (mm == 6 && u == 0) ? 24 + c : -1;
        float v = 0.f;
        if (f >= 0 && (l2 ? k : n) < NR) v = __bfloat162float(l2 ? se2[k * NF + f] : se1[f * NR + n]);
        reinterpret_cast<__nv_bfloat16*>(g_se)[c * 256 + tid] = __float2bfloat16(l2 ? 0.5f * v : v);
    }
    asm volatile("cp.async.wait_all;" ::: "memory");
    __syncthreads();
    const int i = fmap(4 * (lane & 6) + 2 * (lane >> 3) + (lane & 1));
    const int g = lane >> 2, t = lane & 3;
#pragma unroll 4
    for (int task = warp; task < 128; task += 12) {
        const int eg = task & 1, n = (task >> 1) & 31, s = task >> 6;
        const int j = fmap(n);
        const uint32_t a = (i >= 0 && j >= 0) ? sb + ((s * NF + i) * NF + j) * 32 + eg * 16 : sb + NROW * 32;
        uint4 v;
        asm volatile("ldmatrix.sync.aligned.m8n8.x4.trans.shared.b16 {%0,%1,%2,%3}, [%4];"
                     : "=r"(v.x), "=r"(v.y), "=r"(v.z), "=r"(v.w)
                     : "r"(a));
        const int e = eg * 8 + g;
        if (t == 3) {
            const uint32_t mask = (e & 1) ? 0xffff0000u : 0xffffu;
            v.x &= mask;
            v.y &= mask;
        }
        const int ch = (t < 2 ? t ^ ((e >> 1) & 1) : t) ^ ((n >> 1) & 3);
        g_wc[(c >> 1) * 8192 + e * 512 + (c & 1) * 256 + s * 128 + n * 4 + ch] = v;
    }
    __threadfence();
    __syncthreads();
    if (tid == 0) atomicAdd(&g_ready, 1u);
}

#define P2_SKEW 90
#define TWARM 7
#define WPF_STEP 800
#define WDELAY 1600
#define WSTEP 500
#define START_MIN 3300
#define XS 2
#define PACE1 2100
#define PACE2 2700
#define PF_START 2600
#define PF_PACE 550
#define WPF_AT 3000

__global__ void __cluster_dims__(2, 1, 1) __launch_bounds__(384, 1)
fibinet_kernel(const int* __restrict__ idx, const uint4* __restrict__ table,
               const __nv_bfloat16* __restrict__ se1, const __nv_bfloat16* __restrict__ se2,
               const __nv_bfloat16* __restrict__ wc,
               const unsigned char* __restrict__ w1, const __nv_bfloat16* __restrict__ w2, __nv_bfloat16* __restrict__ out,
               const __grid_constant__ CUtensorMap tm_w1, const __grid_constant__ CUtensorMap tm_bi) {
    extern __shared__ __align__(1024) unsigned char smem[];
    const uint32_t t_start = clock32();
    const int tid = threadIdx.x;
    const uint32_t sb = (uint32_t)__cvta_generic_to_shared(smem);
    if (blockIdx.x < NPREP) {
        prep_cta(sb, blockIdx.x, wc, se1, se2);
        return;
    }
    const int cta = blockIdx.x - NPREP, grp = cta >> 1, rank = cta & 1, lane = tid & 31;
    uint32_t ids[13][4], cid[3][2];
    uint32_t gd0 = 0;
    const uint4* tp = table + (lane & 7);
    auto gather = [&](int i) {
#pragma unroll
        for (int u = 0; u < 4; u++)
            asm volatile("{.reg .u64 a; mad.wide.u32 a, %2, 128, %1; cp.async.cg.shared.global [%0], [a], 16;}" ::"r"(
                             (gd0 ^ ((u & 1) * 64)) + xpair(i) + u * 512),
                         "l"(tp), "r"(ids[i][u])
                         : "memory");
        CP_COMMIT();
    };
    if (tid < 256) {
        const uint32_t w = tid >> 7, row = ((tid >> 5) & 3) * 16 + (lane >> 3);
        const int* ip = idx + ((grp * 64 + row) * NF + 2 * w);
#pragma unroll
        for (int u = 0; u < 4; u++)
            asm volatile("ld.global.nc.L2::128B.v2.u32 {%0,%1}, [%2];" : "=r"(ids[0][u]), "=r"(ids[1][u]) : "l"(ip + 4 * NF * u));
        const int* cp = idx + ((grp * 64 + ((tid & 127) >> 1)) * NF + 2 * w + 4 + 4 * (tid & 1));
#pragma unroll
        for (int k = 0; k < 3; k++)
            asm volatile("ld.global.nc.v2.u32 {%0,%1}, [%2];"
                         : "=r"(cid[k][0]), "=r"(cid[k][1])
                         : "l"(cp + 8 * k - (k == 2 ? 2 * (w & tid) : 0)));
        gd0 = sb + w * XDELTA + row * 128 + (((lane & 7) ^ (lane >> 3) ^ (4 * w)) << 4);
        gather(0);
    } else {
        if (tid == 256) asm volatile("prefetch.tensormap [%0];" ::"l"(&tm_w1));
        if (tid == 288) asm volatile("prefetch.tensormap [%0];" ::"l"(&tm_bi));
    }
    const int warp = __reduce_max_sync(0xffffffffu, tid >> 5);
    const int w = warp >> 2;

    if (w == 2) {
        asm volatile("setmaxnreg.dec.sync.aligned.u32 40;");
        auto load_wc = [&](int gi) {
            if (elect()) {
                const unsigned char* src = reinterpret_cast<const unsigned char*>(g_wc) + rank * 131072;
                mbar_expect(sb + BAR_WC + gi * 8, (wcfirst(gi + 1) - wcfirst(gi)) * 8192);
#pragma unroll
                for (int c = wcfirst(gi); c < wcfirst(gi + 1); c++) bulk(sb + wcslot(c), src + c * 8192, 8192, sb + BAR_WC + gi * 8);
            }
            __syncwarp();
        };
        if (warp == 8) {
            if (elect()) {
                mbar_init(sb + BAR_Z, 1);
                mbar_expect(sb + BAR_Z, 8192);
                tma2d(sb + ZOFF, &tm_bi, sb + BAR_Z, 32 * rank, 0);
            }
#pragma unroll
            for (int f = 0; f < 26; f++) {
                if (f == 2) {
                    if (elect()) {
#pragma unroll
                        for (int k = 2; k < 8; k++) mbar_init(sb + BAR_FULL + k * 8, 1);
                        asm volatile("fence.mbarrier_init.release.cluster;" ::: "memory");
                    }
                    __syncwarp();
                    asm volatile("barrier.cluster.arrive.relaxed.aligned;" ::: "memory");
                    mbar_wait(sb + BAR_Z);
#pragma unroll
                    for (int k = 0; k < 2; k++)
                        sts128(sb + ZOFF + (k * 32 + lane) * 128 + ((4 ^ (lane & 7)) << 4), 0x3c803c80u, 0x3c803c80u, 0x3c803c80u, 0x3c803c80u);
                    PROXY_FENCE();
                    asm volatile("bar.arrive 0, 384;" ::: "memory");
                    TS(31);
                }
                if (f == 5) asm volatile("barrier.cluster.wait.aligned;" ::: "memory");
                if (f >= 5) mbar_wait(sb + bdone(f - 5), bpar(f - 5));
                if (f >= 2 && f < 5)
                    while (clock32() - t_start < WDELAY + (f - 2) * WSTEP) {
                    }
                if (elect()) {
                    if (f < 2) mbar_init(sb + BAR_FULL + f * 8, 1);
                    mbar_expect(sb + bfull(f), 16384);
                    tma2d(sb + slot(2 * wl(f)), &tm_w1, sb + bfull(f), 128 * rank + 64 * (f & 1), fieldof(f) * 64);
                    tma2d(sb + slot(wl(f)), &tm_w1, sb + bfull(f), 128 * rank + 64 - 64 * (f & 1), fieldof(f) * 64);
                }
                TS(f);
            }
            if (elect()) mbar_arrive(sb + BAR_GO);
            TS_DUMP(2);
        } else if (warp == 9) {
            if (elect()) {
#pragma unroll
                for (int k = 0; k < 11; k++) mbar_init(sb + BAR_WC + k * 8, k < 10 ? 1 : 8);
                asm volatile("fence.mbarrier_init.release.cluster;" ::: "memory");
                mbar_expect(sb + BAR_FIN, 512);
            }
            __syncwarp();
            asm volatile("barrier.cluster.arrive.relaxed.aligned;" ::: "memory");
            asm volatile("bar.sync 0, 384;" ::: "memory");
            mbar_wait(sb + bdone(3), bpar(3));
            if (elect()) {
                unsigned v, it = 0;
                do {
                    asm volatile("ld.acquire.gpu.global.u32 %0, [%1];" : "=r"(v) : "l"(&g_ready) : "memory");
                } while (v < NPREP && ++it < 4000000u);
                asm volatile("fence.proxy.async.global;" ::: "memory");
                mbar_expect(sb + BAR_SE, 2048);
                bulk(sb + SEOFF, g_se, 2048, sb + BAR_SE);
                if (atomicAdd(&g_seen, 1u) == NMAIN - 1) {
                    g_seen = 0;
                    g_ready = 0;
                }
            }
            __syncwarp();
            TS(0);
            mbar_wait(sb + BAR_GO);
#pragma unroll
            for (int gi = 0; gi < 3; gi++) {
                mbar_wait(sb + bdone(21 + gi), bpar(21 + gi));
                load_wc(gi);
                TS(1 + gi);
            }
        } else if (warp == 10) {
            if (elect()) {
#pragma unroll
                for (int k = 0; k < 8; k++) mbar_init(sb + BAR_DONE + k * 8, 4);
                asm volatile("fence.mbarrier_init.release.cluster;" ::: "memory");
            }
            __syncwarp();
            asm volatile("barrier.cluster.arrive.relaxed.aligned;" ::: "memory");
            asm volatile("bar.arrive 0, 384;" ::: "memory");
#pragma unroll 1
            for (int k = 0; k < 7; k++) {
                while (clock32() - t_start < (uint32_t)(WPF_AT + k * WPF_STEP)) __nanosleep(20);
                if (lane < 6)
                    asm volatile("prefetch.global.L2 [%0];" ::"l"(w1 + (5 + k * 3 + (lane >> 1)) * 32768 + cta * 256 + (lane & 1) * 128));
            }
        } else {
            asm volatile("barrier.cluster.arrive.relaxed.aligned;" ::: "memory");
            asm volatile("bar.sync 0, 384;" ::: "memory");
            const uint2 v = __ldg(reinterpret_cast<const uint2*>(w2 + 128 * rank) + lane);
#pragma unroll
            for (int k = 0; k < 2; k++) {
                const uint32_t x = k ? v.y : v.x;
                sts64(sb + w2chunk((lane >> 2) * 4 + 2 * (lane & 1) + k) + (lane & 2) * 4,
                      __float_as_uint(0.5f * __uint_as_float(x << 16)), __float_as_uint(0.5f * __uint_as_float(x & 0xffff0000u)));
            }
            __syncwarp();
            if (lane == 0) mbar_arrive(sb + BAR_W2);
        }
        if (warp != 8) asm volatile("barrier.cluster.wait.aligned;" ::: "memory");
        {
            uint32_t bw[2][4], z0[4], z1[4];
            mbar_wait(sb + BAR_SE);
            lds128(bw[0], sb + SEOFF + lane * 16);
            lds128(bw[1], sb + SEOFF + 512 + lane * 16);
            asm volatile("bar.sync 2, 384;" ::: "memory");
            lds128(z0, sb + ZQOFF + (tid & 127) * 16);
            lds128(z1, sb + ZQOFF + 2048 + (tid & 127) * 16);
            TS(8);
            float s[2][4] = {};
#pragma unroll
            for (int n = 0; n < 2; n++) {
                mma16816(s[n], z0, bw[0][2 * n], bw[0][2 * n + 1]);
                mma16816(s[n], z1, bw[1][2 * n], bw[1][2 * n + 1]);
            }
            lds128(bw[0], sb + SEOFF + 1024 + lane * 16);
            lds128(bw[1], sb + SEOFF + 1536 + lane * 16);
            float th[8];
#pragma unroll
            for (int k = 0; k < 8; k++) th[k] = gelu_tanh(s[k >> 2][k & 3]);
            SCHED_FENCE();
            TS(9);
            uint32_t gq[4];
#pragma unroll
            for (int k = 0; k < 4; k++)
                gq[k] = pack(s[k >> 1][2 * (k & 1)] * ffma(th[2 * k], 0.5f, 0.5f), s[k >> 1][2 * (k & 1) + 1] * ffma(th[2 * k + 1], 0.5f, 0.5f));
            float a[4][4] = {};
#pragma unroll
            for (int n = 0; n < 4; n++) mma16816(a[n], gq, bw[n >> 1][2 * (n & 1)], bw[n >> 1][2 * (n & 1) + 1]);
#pragma unroll
            for (int k = 0; k < 16; k++)
                if (k < 13 || k == 14) a[k >> 2][k & 3] = tanh_fast(a[k >> 2][k & 3]);
            SCHED_FENCE();
            TS(10);
            uint32_t ap[8];
#pragma unroll
            for (int k = 0; k < 8; k++)
                ap[k] = pack(ffma(a[k >> 1][2 * (k & 1)], 0.5f, 0.5f), ffma(a[k >> 1][2 * (k & 1) + (k < 6)], 0.5f, 0.5f));
            sts128(sb + GOFF + (tid & 127) * 16, ap[0], ap[1], ap[2], ap[3]);
            sts128(sb + GOFF + 2048 + (tid & 127) * 16, ap[4], ap[5], ap[6], ap[7]);
            asm volatile("bar.arrive 3, 384;" ::: "memory");
            TS(11);
        }
        if (warp == 9) {
            load_wc(3);
            load_wc(4);
            mbar_wait(sb + BAR_TD);
            load_wc(5);
            if (lane < 16) TS_DUMP(3);
        } else if (warp == 10) {
            __nv_bfloat16* dst = out + cta * 32 + lane;
            asm volatile("" : "+l"(dst));
            asm volatile("bar.sync 4, 64;" ::: "memory");
            mbar_wait(sb + BAR_FIN);
            uint32_t p[4];
            lds128(p, sb + PARTOFF + lane * 16);
            *dst = __float2bfloat16((__uint_as_float(p[0]) + __uint_as_float(p[1])) + (__uint_as_float(p[2]) + __uint_as_float(p[3])));
        }
    } else {
        asm volatile("setmaxnreg.inc.sync.aligned.u32 232;");
        asm volatile("barrier.cluster.arrive.relaxed.aligned;" ::: "memory");
        const int g = lane >> 2, t = lane & 3, wq = warp & 3, t128 = tid & 127;
        gd0 = opaque(gd0);
        TS(28);
        float acc[84];
#pragma unroll
        for (int k = 0; k < 84; k++) asm volatile("mov.b32 %0, 0;" : "=f"(acc[k]));
        uint32_t e0[9], e1[9], e2[9];
        uint32_t X[14][2][4];
        uint32_t zq[4] = {0, 0, 0, 0};
        const uint64_t dA = mkdesc(sb + w * XDELTA, 16, 1024, 1);
        uint32_t dBlo = (uint32_t)mkdesc(sb + ZOFF, 0, 0, 0);
        const uint32_t xl0 = opaque(sb + (t & 1) * XDELTA + (16 * wq + g) * 128 + (((4 * rank + 2 * w) ^ (4 * (t & 1)) ^ g) << 4));
        const uint32_t hi_half = t >> 1;
        const uint32_t sa0 = opaque(sb + AOFF + t * 4096 + (t >> 1) * 16 + (wq * 32 + g * 4 + w) * 16);
        const uint32_t sa1 = opaque(((g & 2) << 4) | ((t & 1) << 3));
        const uint32_t zero = blockIdx.y;
        auto expand = [&](int k0, int k1) {
#pragma unroll
            for (int k = k0; k < k1; k++)
#pragma unroll
                for (int u = 0; u < 4; u++)
                    asm volatile("shfl.sync.idx.b32 %0, %1, %2, 31, 0xffffffff;"
                                 : "=r"(ids[k][u])
                                 : "r"(k < 12 ? cid[(k - 2) >> 2][k & 1] : w ? cid[2][1] : cid[2][0]),
                                   "r"(2 * (lane >> 3) + 8 * u + (((k - 2) >> 1) & 1)));
        };
        auto twarm = [&]() {
            float s1[8];
            WG_FENCE();
            wgmma_rs_n16_set(s1, zq, mkdesc(sb + AOFF, 16, 512, 2));
            WG_COMMIT();
            WG_WAIT0();
            pin(s1);
            asm volatile("{.reg .pred p; setp.ne.u32 p, %1, 0; @p st.shared.f32 [%1], %0;}" ::"f"(s1[0]), "r"(zero));
        };
        expand(2, 8);
        if (TWARM & 1) twarm();
        TS(26);
        while (clock32() - t_start < PACE1) {
        }
        gather(1);
        expand(8, 13);
        if (TWARM & 2) twarm();
        TS(30);
        while (clock32() - t_start < PACE2) {
        }
        gather(2);
        if (TWARM & 4) twarm();
        asm volatile("bar.sync 0, 384;" ::: "memory");
        auto lift = [&](int i) {
            const int m = 2 * (i >> 2) + (i & 1);
#pragma unroll
            for (int r = 0; r < 2; r++)
#pragma unroll
                for (int cc = 0; cc < 2; cc++) {
                    const uint32_t a = (xl0 ^ (cc * 16)) + xpair(i) + r * 1024;
                    if (i & 2) lds128_if(X[2 * m + r][cc], a, hi_half);
                    else lds128(X[2 * m + r][cc], a);
                }
        };
        auto store_pair = [&](int m, int half, const uint32_t (&ea)[9]) {
            uint32_t a;
            if (m < 4) a = sa0 + (sa1 ^ (((m & 1) << 5) | ((m >> 1) << 3)));
            else a = sb + BOFF + t * 2048 + (wq * 32 + g * 4 + ((2 * (m & 1) + w) ^ t)) * 8;
#pragma unroll
            for (int n = half; n < 4; n += 2)
#pragma unroll
                for (int u = 0; u < 2; u++)
                    sts64(a + (m < 4 ? (8 * n + u) * 2048 + n * 32 : (8 * n + u) * 1024),
                          __byte_perm(ea[2 * n], e1[2 * n], u ? 0x7632 : 0x5410),
                          __byte_perm(ea[2 * n + 1], e1[2 * n + 1], u ? 0x7632 : 0x5410));
        };
        auto z_pair = [&](int m, uint32_t a, uint32_t b) {
            asm volatile("{.reg .pred p; setp.eq.u32 p, %4, %5; @p prmt.b32 %0, %2, %3, 0x5410; @p prmt.b32 %1, %2, %3, 0x7632;}"
                         : "+r"(zq[2 * (m >> 2)]), "+r"(zq[2 * (m >> 2) + 1])
                         : "r"(a), "r"(b), "r"(t), "r"(m & 3));
        };

        TS(29);
        mbar_wait(sb + BAR_FULL + w * 8);
        CP_WAIT(2);
        while (clock32() - t_start < START_MIN) {
        }
        if (w == 1) {
            asm volatile("bar.arrive 6, 256;" ::: "memory");
            asm volatile("bar.sync 5, 256;" ::: "memory");
        }
#pragma unroll
        for (int i = 0; i < 13; i++) {
            const uint64_t da = dA + (xpair(i) >> 4) + ((uint64_t)i << 16);
            dBlo += (uint32_t)(w ? wl(2 * i + 1) - (i ? wl(2 * i - 1) : 0) : wl(2 * i) - (i ? wl(2 * i - 2) : 0)) *
                    (uint32_t)((SLOT << 12) - (SLOT >> 3));
            const uint64_t db = mkdesc(0, 0, 1024, 1) | dBlo;
            TS(i);
            WG_FENCE();
            wgmma_ss_n168_acc(acc, da, db + w * 256);
            wgmma_ss_n168_acc(acc, da + 2, db + w * 256 + 128);
            wgmma_ss_n168_acc(acc, da + 4, db + (w ^ 1) * 256);
            wgmma_ss_n168_acc(acc, da + 6, db + (w ^ 1) * 256 + 128);
            WG_COMMIT();
            if (i == 0) {
                if (w == 0) {
                    asm volatile("bar.arrive 5, 256;" ::: "memory");
                    asm volatile("bar.sync 6, 256;" ::: "memory");
                }
            } else {
                mbar_wait(sb + bdone(2 * i - 2) + (w ^ 1) * 8, bpar(2 * i - 2));
            }
            if (i < 10) gather(i + 3);
            if (i == 1) asm volatile("barrier.cluster.wait.aligned;" ::: "memory");
            if (i == 6) mbar_wait(sb + BAR_W2);
            lift(i);
            if (i == 10 || i == 11) mbar_wait(sb + bdone(2 * i - 2) + w * 8, bpar(2 * i - 2));
            if (i >= 2 && !(i & 1)) {
                z_pair((i - 2) >> 1, e0[8], e1[8]);
                store_pair((i - 2) >> 1, 0, e0);
#pragma unroll
                for (int k = 0; k < 8; k++) e2[k] = e0[k];
            } else if (i >= 3) {
                store_pair((i - 3) >> 1, 1, e2);
            }
            const uint32_t rdy = i < 12 ? mbar_test(sb + bfull(2 * i + 2) + w * 8, bpar(2 * i + 2)) : 0;
            WG_WAIT0();
            pin(acc);
            if (i == 12) TS(13);
            if (i == 0) TS(27);
            if (i < 10) CP_WAIT(2);
            else if (i == 10) CP_WAIT(1);
            else if (i == 11) CP_WAIT(0);
            if (i < 12 && lane == 0) mbar_arrive(sb + bdone(2 * i) + w * 8);
#pragma unroll
            for (int k = 0; k < 9; k++) {
                const uint32_t v = k < 8 ? pack(acc[64 + 2 * k], acc[65 + 2 * k]) : pack(acc[80], acc[82]);
                if (i & 1) e1[k] = v;
                else e0[k] = v;
            }
            if (i < 12) {
#pragma unroll
                for (int k = 64; k < 83; k++)
                    if (k != 81) asm volatile("mov.b32 %0, %1;" : "+f"(acc[k]) : "r"(zero));
                mbar_wait_unless(rdy, sb + bfull(2 * i + 2) + w * 8, bpar(2 * i + 2));
            } else {
                z_pair(6, e0[8], 0);
                sts128(sb + ZQOFF + w * 2048 + t128 * 16, zq[0], zq[1], zq[2], zq[3]);
                asm volatile("bar.arrive 2, 384;" ::: "memory");
            }
        }
        TS(14);

        float aj[14];
        uint32_t ai[8];
        float sum0 = 0.f, sum1 = 0.f;
        float th[32];
        uint32_t hw[4][4];
        auto deep_issue = [&](int k2) {
            lds128(hw[k2], ((sb + w2chunk(w * 16 + t)) ^ ((k2 & 1) * 64)) + k2 * 512);
#pragma unroll
            for (int k = 8 * k2; k < 8 * k2 + 8; k++) th[k] = gelu_tanh(acc[k]);
        };
        auto deep_use = [&](int k2) {
#pragma unroll
            for (int k = 8 * k2; k < 8 * k2 + 8; k++) {
                const float h = __uint_as_float(hw[k2][((k >> 1) & 2) + (k & 1)]);
                const float y = ffma(th[k], h, h);
                if (k & 2) sum1 = ffma(acc[k], y, sum1);
                else sum0 = ffma(acc[k], y, sum0);
            }
        };
        auto deep_send = [&](int k0, int k1) {
#pragma unroll
            for (int k = k0; k < k1; k++)
                sts128(sb + EXOFF + w * SLOT + t128 * 16 + k * 2048, pack(acc[32 + 8 * k], acc[33 + 8 * k]),
                       pack(acc[34 + 8 * k], acc[35 + 8 * k]), pack(acc[36 + 8 * k], acc[37 + 8 * k]), pack(acc[38 + 8 * k], acc[39 + 8 * k]));
        };
        uint32_t o[4][4];
        auto deep_recv = [&](int k0, int k1) {
#pragma unroll
            for (int k = k0; k < k1; k++) lds128(o[k], sb + EXOFF + (w ^ 1) * SLOT + t128 * 16 + k * 2048);
        };
        auto deep_add = [&](int k0, int k1) {
            const uint32_t eye = (g >> 1) == t ? ((g & 1) ? 0x3f800000u : 0x3f80u) : 0u;
#pragma unroll
            for (int k = 2 * k0; k < 2 * k1; k++)
                asm volatile("mma.sync.aligned.m16n8k8.row.col.f32.bf16.bf16.f32 {%0,%1,%2,%3}, {%4,%5}, {%6}, {%0,%1,%2,%3};"
                             : "+f"(acc[4 * k]), "+f"(acc[4 * k + 1]), "+f"(acc[4 * k + 2]), "+f"(acc[4 * k + 3])
                             : "r"(o[k >> 1][2 * (k & 1)]), "r"(o[k >> 1][2 * (k & 1) + 1]), "r"(eye));
        };
        auto store_last = [&]() {
#pragma unroll
            for (int n = 0; n < 4; n++) sts64(sb + COFF + w * 4096 + n * 1024 + (t128 ^ w) * 8, e0[2 * n], e0[2 * n + 1]);
            store_pair(5, 1, e2);
        };
        const uint32_t la = sb + AOFF + w * (16 * 2048 + 64) + (wq * 32 + g * 4 + (t ^ (g & 2))) * 16;
        const uint32_t lb = sb + BOFF + w * (16 * 1024) + t128 * 8;
        const uint32_t lc0 = sb + COFF + (t & 1) * (4096 + 8) + w * 2048 + (wq * 8 + g) * 32, lc1 = lc0 ^ 8;
        uint32_t Ap[2][2][4];
        auto load_a = [&](int e) {
            lds128(Ap[e & 1][0], la + e * 2048 + (e >> 2) * 16);
            lds64(Ap[e & 1][1][0], Ap[e & 1][1][1], (lb ^ ((e & 6) * 4)) + e * 1024);
            lds64(Ap[e & 1][1][2], Ap[e & 1][1][3], ((e & 2) ? lc1 : lc0) + (e >> 3) * 1024 + (e & 4) * 4);
        };
        {
            deep_send(0, XS);
            asm volatile("bar.sync 1, 256;" ::: "memory");
            deep_recv(0, XS);
            deep_send(XS, 4);
            TS(15);
            deep_add(0, XS);
            deep_issue(0);
            asm volatile("bar.sync 1, 256;" ::: "memory");
            deep_recv(XS, 4);
            SCHED_FENCE();
            deep_add(XS, 4);
            TS(16);
            deep_issue(1);
            deep_use(0);
            store_last();
            SCHED_FENCE();
            TS(17);
            deep_issue(2);
            deep_use(1);
            mbar_wait(sb + BAR_WC);
            deep_use(2);
            TS(18);
            asm volatile("bar.sync 3, 384;" ::: "memory");
            uint32_t v[2][4];
            lds128(v[0], sb + GOFF + t128 * 16);
            lds128(v[1], sb + GOFF + 2048 + t128 * 16);
            load_a(0);
            load_a(1);
            deep_issue(3);
#pragma unroll
            for (int k = 0; k < 8; k++) ai[k] = v[k >> 2][k & 3];
#pragma unroll
            for (int q = 0; q < 14; q++) {
                const uint32_t x = ai[2 * (q >> 2) + (q & 1)];
                aj[q] = __uint_as_float((q & 2) ? x & 0xffff0000u : x << 16);
            }
        }
        TS(19);

        uint32_t fin_a, dsum[2];
        {
            uint64_t dW[4];
#pragma unroll
            for (int k = 0; k < 4; k++) dW[k] = mkdesc(sb + w * 4096, 16, 512, 2) + (wcslot(0) >> 4) + (k >> 1) * 128 + (k & 1) * 2;
            uint32_t Aq[2][2][4], hacc[2][4], V[14];
            float Sp[16], Sq[16], U[14];
            auto scale_a = [&](int e) {
#pragma unroll
                for (int k = 0; k < 8; k++) Aq[e & 1][k >> 2][k & 3] = hmul2(Ap[e & 1][k >> 2][k & 3], ai[k < 4 ? k ^ (e & 2) : k]);
            };
            auto dot = [&](int e) {
#pragma unroll
                for (int q = 0; q < 14; q++) {
                    const uint32_t x = X[q][e >> 3][(e & 7) >> 1];
                    if ((e & 6) == 0 && q < 4) hacc[e >> 3][q] = hmul2(V[q], x);
                    else hacc[e >> 3][q & 3] = hfma2(V[q], x, hacc[e >> 3][q & 3]);
                }
            };
            scale_a(0);
            if (w == 1) {
                const uint32_t c1 = clock32();
                while (clock32() - c1 < P2_SKEW) {
                }
            }
#pragma unroll
            for (int e = 0; e < 16; e++) {
                WG_FENCE();
                if (e == 0) wgmma_rs_n32_set(Sp, Ap[e & 1][0], dW[0]);
                else wgmma_rs_n32_pred(Sp, Ap[e & 1][0], dW[0], zero);
                wgmma_rs_n32_acc(Sp, Ap[e & 1][1], dW[1]);
                if (e == 0) wgmma_rs_n32_set(Sq, Aq[e & 1][0], dW[2]);
                else wgmma_rs_n32_pred(Sq, Aq[e & 1][0], dW[2], zero);
                wgmma_rs_n32_acc(Sq, Aq[e & 1][1], dW[3]);
                WG_COMMIT();
                SCHED_FENCE();
                if (e < 15) {
#pragma unroll
                    for (int k = 0; k < 4; k++)
                        asm volatile("add.s64 %0, %0, %1;" : "+l"(dW[k]) : "l"((int64_t)((wcslot(e + 1) - wcslot(e)) / 16)));
                }
                if (e == 0) deep_use(3);
                if (e > 0 && !(e & 1)) dot(e - 1);
                if (e == 1) {
                    const float h0 = __uint_as_float(__float_as_uint(sum0) & 0xffff0000u);
                    const float h1 = __uint_as_float(__float_as_uint(sum1) & 0xffff0000u);
                    dsum[0] = pack(sum0 - h0, h0);
                    dsum[1] = pack(sum1 - h1, h1);
                }
                if (e == 13) {
                    asm("mapa.shared::cluster.u32 %0, %1, %2;"
                        : "=r"(fin_a)
                        : "r"(sb + PARTOFF + (((wq & 1) * 16 + t * 8 + g) * 4 + 2 * rank + w) * 4), "r"(wq >> 1));
                    fin_a = opaque(fin_a);
                }
                if (e == 15 && warp == 0) asm volatile("bar.arrive 4, 64;" ::: "memory");
                if (e + 1 < 16) scale_a(e + 1);
                if (e == 0 || e == 1 || e == 4 || e == 7 || e == 10)
                    mbar_wait(sb + BAR_WC + (e == 0 ? 1 : e == 1 ? 2 : e == 4 ? 3 : e == 7 ? 4 : 5) * 8);
                else if (e < 15)
                    SCHED_FENCE();
                WG_WAIT0();
                pin(Sp);
                pin(Sq);
                if (e == 0 && lane == 0) mbar_arrive(sb + BAR_TD);
                if (e == 0) TS(20);
                if (e + 2 < 16) load_a(e + 2);
#pragma unroll
                for (int q = 0; q < 14; q++) {
                    const int ix = 4 * (q >> 2) + 2 * (q & 1) + ((q >> 1) & 1);
                    const float u = ffma(aj[q], Sq[ix], Sp[ix]);
                    if (!(e & 1)) U[q] = u;
                    else V[q] = pack(U[q], u);
                }
                if (e == 7) TS(21);
            }
            float r[4] = {0.f, 0.f, 0.f, 0.f};
            asm volatile("mma.sync.aligned.m16n8k8.row.col.f32.bf16.bf16.f32 {%0,%1,%2,%3}, {%4,%5}, {%6}, {%0,%1,%2,%3};"
                         : "+f"(r[0]), "+f"(r[1]), "+f"(r[2]), "+f"(r[3])
                         : "r"(dsum[0]), "r"(dsum[1]), "r"(0x3f803f80u));
            mma16816(r, hacc[0], 0x3f803f80u, 0x3f803f80u);
            dot(15);
            mma16816(r, hacc[1], 0x3f803f80u, 0x3f803f80u);
            sum0 = r[0];
            sum1 = r[2];
        }
        TS(22);
        {
            const float v = (t & 1) ? sum1 : sum0;
            asm volatile(
                "{.reg .pred p; setp.lt.u32 p, %3, 2; @p st.async.shared::cluster.mbarrier::complete_tx::bytes.f32 [%0], %1, [%2];}" ::"r"(fin_a),
                "f"(v), "r"((fin_a & ~0x3ffu) + (BAR_FIN & 0x3ff)), "r"(t)
                : "memory");
            if (wq == 0) TS_DUMP(w);
        }
    }
}

typedef CUresult (*EncodeFn)(CUtensorMap*, CUtensorMapDataType, cuuint32_t, void*, const cuuint64_t*, const cuuint64_t*,
                             const cuuint32_t*, const cuuint32_t*, CUtensorMapInterleave, CUtensorMapSwizzle,
                             CUtensorMapL2promotion, CUtensorMapFloatOOBfill);

}

extern "C" void kernel_launch(void* const* d_in, const int* in_sizes, int n_in, void* d_out, int out_size) {
    static EncodeFn encode = nullptr;
    if (!encode) {
        void* fn = nullptr;
        cudaDriverEntryPointQueryResult qr;
        cudaGetDriverEntryPoint("cuTensorMapEncodeTiled", &fn, cudaEnableDefault, &qr);
        encode = (EncodeFn)fn;
        cudaFuncSetAttribute(fibinet_kernel, cudaFuncAttributeMaxDynamicSharedMemorySize, SMEM_BYTES);
    }
    CUtensorMap tm;
    const cuuint64_t gd[2] = {NH, NF * ND};
    const cuuint64_t gs[1] = {NH * 2};
    const cuuint32_t bd[2] = {64, 64}, es[2] = {1, 1};
    encode(&tm, CU_TENSOR_MAP_DATA_TYPE_BFLOAT16, 2, d_in[6], gd, gs, bd, es, CU_TENSOR_MAP_INTERLEAVE_NONE,
           CU_TENSOR_MAP_SWIZZLE_128B, CU_TENSOR_MAP_L2_PROMOTION_L2_256B, CU_TENSOR_MAP_FLOAT_OOB_FILL_NONE);
    CUtensorMap tb;
    const cuuint64_t gd2[2] = {ND, ND};
    const cuuint64_t gs2[1] = {ND * 2};
    encode(&tb, CU_TENSOR_MAP_DATA_TYPE_BFLOAT16, 2, d_in[4], gd2, gs2, bd, es, CU_TENSOR_MAP_INTERLEAVE_NONE,
           CU_TENSOR_MAP_SWIZZLE_128B, CU_TENSOR_MAP_L2_PROMOTION_L2_256B, CU_TENSOR_MAP_FLOAT_OOB_FILL_NONE);
    fibinet_kernel<<<NPREP + NMAIN, 384, SMEM_BYTES>>>(
        (const int*)d_in[0], (const uint4*)d_in[1], (const __nv_bfloat16*)d_in[2], (const __nv_bfloat16*)d_in[3],
        (const __nv_bfloat16*)d_in[5], (const unsigned char*)d_in[6], (const __nv_bfloat16*)d_in[7], (__nv_bfloat16*)d_out, tm, tb);
}
```

```cpp
#include <cuda_runtime.h>
#include <cuda_bf16.h>
#include <cuda.h>
#include <stdint.h>

namespace {

constexpr int NB = 4096, NF = 26, ND = 64, NH = 256, NR = 13;
constexpr int NPREP = 4;
constexpr int NMAIN = 128;

constexpr int SLOT = 8192;
constexpr int ZOFF = 15 * SLOT;
__host__ __device__ constexpr int slot(int s) { return ZOFF - s * SLOT; }
constexpr int BOFF = ZOFF + SLOT;
constexpr int AOFF = BOFF + 32768;
constexpr int COFF = slot(12);
constexpr int MOFF = AOFF + 65536 + 128;
constexpr int BAR_FULL = MOFF, BAR_DONE = MOFF + 64, BAR_WC = MOFF + 128, BAR_FIN = MOFF + 176,
              BAR_GO = MOFF + 184, BAR_SE = MOFF + 192, BAR_W2 = MOFF + 200, BAR_TD = MOFF + 208, BAR_Z = MOFF + 216;
__host__ __device__ constexpr int bfull(int f) { return BAR_FULL + (f & 7) * 8; }
__host__ __device__ constexpr int bdone(int f) { return BAR_DONE + (f & 7) * 8; }
__host__ __device__ constexpr int bpar(int f) { return (f >> 3) & 1; }
constexpr int PARTOFF = MOFF + 256, SEOFF = MOFF + 768;
constexpr int SMEM_BYTES = MOFF + 2944;
static_assert((BAR_FIN >> 10) == (PARTOFF >> 10) && (BAR_FIN >> 10) == ((PARTOFF + 511) >> 10), "same 1 KB block");
constexpr int XDELTA = 2 * SLOT;
__host__ __device__ constexpr int xpair(int i) {
    return (i & 3) == 0 ? slot(11) : (i & 3) == 1 ? BOFF : (i & 3) == 2 ? BOFF + SLOT : slot(15);
}
__host__ __device__ constexpr int wl(int f) { return f % 5 == 0 ? 1 : f % 5 == 4 ? 7 : f % 5 + 2; }
__host__ __device__ constexpr int wcslot(int c) {
    return c == 0 ? slot(3) : c == 1 ? slot(8) : c == 2 ? slot(10) : c == 3 ? slot(15) : c == 4 ? slot(13)
         : c == 5 ? slot(11) : c == 6 ? slot(9) : c == 7 ? slot(14) : c == 8 ? slot(7) : c == 9 ? slot(2)
         : c == 10 ? slot(1) : c == 11 ? slot(4) : c == 12 ? slot(5) : c == 13 ? slot(6) : c == 14 ? ZOFF : slot(3);
}
__host__ __device__ constexpr int wcfirst(int gi) { return gi < 3 ? gi : gi == 3 ? 5 : gi == 4 ? 8 : gi == 5 ? 11 : 16; }
constexpr int EXOFF = slot(5);
constexpr int ZQOFF = slot(6);
constexpr int GOFF = ZQOFF + 4096;
__host__ __device__ constexpr int w2chunk(int c) { return ZOFF + c * 128 + ((5 ^ (c & 7)) << 4); }

__device__ uint4 g_wc[2 * 16 * 8192 / 16];
__device__ uint4 g_se[2048 / 16];
__device__ unsigned g_ready;
__device__ unsigned g_seen;

__host__ __device__ constexpr int fieldof(int f) { return f < 24 ? 4 * (f >> 2) + 2 * (f & 1) + ((f >> 1) & 1) : f; }
__device__ __forceinline__ int fmap(int n) { return n < 24 ? n : 24 + ((n >> 1) & 1); }
__host__ __device__ constexpr int estep(int s) { return (s & 1) + 2 * (s >> 2) + 4 * (s & 2); }

__device__ __forceinline__ uint64_t mkdesc(uint32_t addr, uint32_t lbo, uint32_t sbo, int sw) {
    return (uint64_t)((addr & 0x3ffff) >> 4) | ((uint64_t)(lbo >> 4) << 16) | ((uint64_t)(sbo >> 4) << 32) |
           ((uint64_t)sw << 62);
}
__device__ __forceinline__ void mbar_init(uint32_t b, uint32_t n) {
    asm volatile("mbarrier.init.shared.b64 [%0], %1;" ::"r"(b), "r"(n) : "memory");
}
__device__ __forceinline__ void mbar_wait(uint32_t b, uint32_t par = 0) {
    asm volatile(
        "{\n.reg .pred p, q;\n.reg .u32 n;\n"
        "mbarrier.try_wait.parity.shared.b64 p, [%0], %1;\n@p bra.uni WD%=;\nmov.u32 n, 0;\n"
        "WL%=:\nmbarrier.try_wait.parity.shared.b64 p, [%0], %1;\n@p bra.uni WD%=;\n"
        "add.u32 n, n, 1;\nsetp.lt.u32 q, n, 4000000;\n@q bra.uni WL%=;\nWD%=:\n}\n" ::"r"(b), "r"(par)
        : "memory");
}
__device__ __forceinline__ uint32_t mbar_test(uint32_t b, uint32_t par) {
    uint32_t ok;
    asm volatile("{.reg .pred p; mbarrier.test_wait.parity.shared.b64 p, [%1], %2; selp.u32 %0, 1, 0, p;}"
                 : "=r"(ok)
                 : "r"(b), "r"(par)
                 : "memory");
    return ok;
}
__device__ __forceinline__ void mbar_wait_unless(uint32_t ok, uint32_t b, uint32_t par) {
    asm volatile(
        "{\n.reg .pred p, q;\n.reg .u32 n;\n"
        "setp.ne.u32 p, %1, 0;\n@p bra.uni WD%=;\nmov.u32 n, 0;\n"
        "WL%=:\nmbarrier.try_wait.parity.shared.b64 p, [%0], %2;\n@p bra.uni WD%=;\n"
        "add.u32 n, n, 1;\nsetp.lt.u32 q, n, 4000000;\n@q bra.uni WL%=;\nWD%=:\n}\n" ::"r"(b), "r"(ok), "r"(par)
        : "memory");
}
__device__ __forceinline__ void mbar_arrive(uint32_t b) {
    asm volatile("mbarrier.arrive.shared.b64 _, [%0];" ::"r"(b) : "memory");
}
__device__ __forceinline__ void mbar_expect(uint32_t b, uint32_t bytes) {
    asm volatile("mbarrier.arrive.expect_tx.shared.b64 _, [%0], %1;" ::"r"(b), "r"(bytes) : "memory");
}
__device__ __forceinline__ uint32_t opaque(uint32_t v) { return __shfl_sync(0xffffffffu, v, threadIdx.x); }
__device__ __forceinline__ bool elect() {
    uint32_t p;
    asm volatile("{.reg .pred q; elect.sync _|q, 0xffffffff; selp.u32 %0, 1, 0, q;}" : "=r"(p));
    return p;
}
__device__ __forceinline__ void tma2d(uint32_t dst, const CUtensorMap* m, uint32_t bar, int x, int y) {
    asm volatile(
        "cp.async.bulk.tensor.2d.shared::cluster.global.mbarrier::complete_tx::bytes [%0], [%1, {%3, %4}], [%2];" ::"r"(dst),
        "l"(m), "r"(bar), "r"(x), "r"(y)
        : "memory");
}
__device__ __forceinline__ void bulk(uint32_t dst, const void* src, uint32_t bytes, uint32_t bar) {
    asm volatile("cp.async.bulk.shared::cluster.global.mbarrier::complete_tx::bytes [%0], [%1], %2, [%3];" ::"r"(dst),
                 "l"(src), "r"(bytes), "r"(bar)
                 : "memory");
}
__device__ __forceinline__ void cp16(uint32_t dst, const void* src) {
    asm volatile("cp.async.cg.shared.global [%0], [%1], 16;" ::"r"(dst), "l"(src) : "memory");
}
__device__ __forceinline__ void lds128(uint32_t (&v)[4], uint32_t a) {
    asm volatile("ld.shared.v4.u32 {%0,%1,%2,%3}, [%4];" : "=r"(v[0]), "=r"(v[1]), "=r"(v[2]), "=r"(v[3]) : "r"(a) : "memory");
}
__device__ __forceinline__ void lds128_if(uint32_t (&v)[4], uint32_t a, uint32_t p) {
    asm volatile("{.reg .pred q; setp.ne.u32 q, %5, 0; @q ld.shared.v4.u32 {%0,%1,%2,%3}, [%4];}"
                 : "+r"(v[0]), "+r"(v[1]), "+r"(v[2]), "+r"(v[3])
                 : "r"(a), "r"(p)
                 : "memory");
}
__device__ __forceinline__ void lds64(uint32_t& x, uint32_t& y, uint32_t a) {
    asm volatile("ld.shared.v2.u32 {%0,%1}, [%2];" : "=r"(x), "=r"(y) : "r"(a) : "memory");
}
__device__ __forceinline__ void sts128(uint32_t a, uint32_t x, uint32_t y, uint32_t z, uint32_t w) {
    asm volatile("st.shared.v4.u32 [%0], {%1,%2,%3,%4};" ::"r"(a), "r"(x), "r"(y), "r"(z), "r"(w) : "memory");
}
__device__ __forceinline__ void sts64(uint32_t a, uint32_t x, uint32_t y) {
    asm volatile("st.shared.v2.u32 [%0], {%1,%2};" ::"r"(a), "r"(x), "r"(y) : "memory");
}
__device__ __forceinline__ uint32_t pack(float lo, float hi) {
    uint32_t r;
    asm volatile("cvt.rn.bf16x2.f32 %0, %1, %2;" : "=r"(r) : "f"(hi), "f"(lo));
    return r;
}
__device__ __forceinline__ uint32_t hmul2(uint32_t a, uint32_t b) {
    uint32_t r;
    asm volatile("mul.rn.bf16x2 %0, %1, %2;" : "=r"(r) : "r"(a), "r"(b));
    return r;
}
__device__ __forceinline__ uint32_t hfma2(uint32_t a, uint32_t b, uint32_t c) {
    uint32_t r;
    asm volatile("fma.rn.bf16x2 %0, %1, %2, %3;" : "=r"(r) : "r"(a), "r"(b), "r"(c));
    return r;
}
__device__ __forceinline__ float ffma(float a, float b, float c) {
    float r;
    asm volatile("fma.rn.f32 %0, %1, %2, %3;" : "=f"(r) : "f"(a), "f"(b), "f"(c));
    return r;
}
__device__ __forceinline__ float tanh_fast(float x) {
    float r;
    asm volatile("tanh.approx.f32 %0, %1;" : "=f"(r) : "f"(x));
    return r;
}
__device__ __forceinline__ float gelu_tanh(float x) {
    float r;
    asm volatile(
        "{.reg .f32 a; mul.f32 a, %1, %1; fma.rn.f32 a, a, 0f3D122279, 0f3F4C422A; mul.f32 a, a, %1; tanh.approx.f32 %0, a;}"
        : "=f"(r)
        : "f"(x));
    return r;
}
__device__ __forceinline__ void mma16816(float (&d)[4], const uint32_t (&a)[4], uint32_t b0, uint32_t b1) {
    asm volatile("mma.sync.aligned.m16n8k16.row.col.f32.bf16.bf16.f32 {%0,%1,%2,%3}, {%4,%5,%6,%7}, {%8,%9}, {%0,%1,%2,%3};"
                 : "+f"(d[0]), "+f"(d[1]), "+f"(d[2]), "+f"(d[3])
                 : "r"(a[0]), "r"(a[1]), "r"(a[2]), "r"(a[3]), "r"(b0), "r"(b1));
}
__device__ __forceinline__ uint32_t clock32() {
    uint32_t c;
    asm volatile("mov.u32 %0, %%clock;" : "=r"(c)::"memory");
    return c;
}
#define WG_FENCE() asm volatile("wgmma.fence.sync.aligned;" ::: "memory")
#define WG_COMMIT() asm volatile("wgmma.commit_group.sync.aligned;" ::: "memory")
#define WG_WAIT0() asm volatile("wgmma.wait_group.sync.aligned 0;" ::: "memory")
#define CP_COMMIT() asm volatile("cp.async.commit_group;" ::: "memory")
#define CP_WAIT(n) asm volatile("cp.async.wait_group %0;" ::"n"(n) : "memory")
#define SCHED_FENCE() asm volatile("pmevent 0;" ::: "memory")
#define PROXY_FENCE() asm volatile("fence.proxy.async.shared::cta;" ::: "memory")
template <int N>
__device__ __forceinline__ void pin(float (&d)[N]) {
#pragma unroll
    for (int i = 0; i < N; i++) asm volatile("" : "+f"(d[i])::"memory");
}
#define TS(k)
#define TS_DUMP(role)

__device__ __forceinline__ void wgmma_ss_n168_acc(float (&d)[84], uint64_t da, uint64_t db) {
    asm volatile(
        "wgmma.mma_async.sync.aligned.m64n168k16.f32.bf16.bf16 "
        "{%0,%1,%2,%3,%4,%5,%6,%7,%8,%9,%10,%11,%12,%13,%14,%15,"
        "%16,%17,%18,%19,%20,%21,%22,%23,%24,%25,%26,%27,%28,%29,%30,%31,"
        "%32,%33,%34,%35,%36,%37,%38,%39,%40,%41,%42,%43,%44,%45,%46,%47,"
        "%48,%49,%50,%51,%52,%53,%54,%55,%56,%57,%58,%59,%60,%61,%62,%63,"
        "%64,%65,%66,%67,%68,%69,%70,%71,%72,%73,%74,%75,%76,%77,%78,%79,"
        "%80,%81,%82,%83}, "
        "%84, %85, 1, 1, 1, 0, 1;"
        : "+f"(d[0]), "+f"(d[1]), "+f"(d[2]), "+f"(d[3]), "+f"(d[4]), "+f"(d[5]), "+f"(d[6]), "+f"(d[7]),
          "+f"(d[8]), "+f"(d[9]), "+f"(d[10]), "+f"(d[11]), "+f"(d[12]), "+f"(d[13]), "+f"(d[14]), "+f"(d[15]),
          "+f"(d[16]), "+f"(d[17]), "+f"(d[18]), "+f"(d[19]), "+f"(d[20]), "+f"(d[21]), "+f"(d[22]), "+f"(d[23]),
          "+f"(d[24]), "+f"(d[25]), "+f"(d[26]), "+f"(d[27]), "+f"(d[28]), "+f"(d[29]), "+f"(d[30]), "+f"(d[31]),
          "+f"(d[32]), "+f"(d[33]), "+f"(d[34]), "+f"(d[35]), "+f"(d[36]), "+f"(d[37]), "+f"(d[38]), "+f"(d[39]),
          "+f"(d[40]), "+f"(d[41]), "+f"(d[42]), "+f"(d[43]), "+f"(d[44]), "+f"(d[45]), "+f"(d[46]), "+f"(d[47]),
          "+f"(d[48]), "+f"(d[49]), "+f"(d[50]), "+f"(d[51]), "+f"(d[52]), "+f"(d[53]), "+f"(d[54]), "+f"(d[55]),
          "+f"(d[56]), "+f"(d[57]), "+f"(d[58]), "+f"(d[59]), "+f"(d[60]), "+f"(d[61]), "+f"(d[62]), "+f"(d[63]),
          "+f"(d[64]), "+f"(d[65]), "+f"(d[66]), "+f"(d[67]), "+f"(d[68]), "+f"(d[69]), "+f"(d[70]), "+f"(d[71]),
          "+f"(d[72]), "+f"(d[73]), "+f"(d[74]), "+f"(d[75]), "+f"(d[76]), "+f"(d[77]), "+f"(d[78]), "+f"(d[79]),
          "+f"(d[80]), "+f"(d[81]), "+f"(d[82]), "+f"(d[83])
        : "l"(da), "l"(db));
}

__device__ __forceinline__ void wgmma_rs_n32_set(float (&d)[16], const uint32_t (&a)[4], uint64_t db) {
    asm volatile(
        "wgmma.mma_async.sync.aligned.m64n32k16.f32.bf16.bf16 "
        "{%0,%1,%2,%3,%4,%5,%6,%7,%8,%9,%10,%11,%12,%13,%14,%15}, "
        "{%16,%17,%18,%19}, %20, 0, 1, 1, 0;"
        : "=f"(d[0]), "=f"(d[1]), "=f"(d[2]), "=f"(d[3]), "=f"(d[4]), "=f"(d[5]), "=f"(d[6]), "=f"(d[7]),
          "=f"(d[8]), "=f"(d[9]), "=f"(d[10]), "=f"(d[11]), "=f"(d[12]), "=f"(d[13]), "=f"(d[14]), "=f"(d[15])
        : "r"(a[0]), "r"(a[1]), "r"(a[2]), "r"(a[3]), "l"(db));
}

__device__ __forceinline__ void wgmma_rs_n32_acc(float (&d)[16], const uint32_t (&a)[4], uint64_t db) {
    asm volatile(
        "wgmma.mma_async.sync.aligned.m64n32k16.f32.bf16.bf16 "
        "{%0,%1,%2,%3,%4,%5,%6,%7,%8,%9,%10,%11,%12,%13,%14,%15}, "
        "{%16,%17,%18,%19}, %20, 1, 1, 1, 0;"
        : "+f"(d[0]), "+f"(d[1]), "+f"(d[2]), "+f"(d[3]), "+f"(d[4]), "+f"(d[5]), "+f"(d[6]), "+f"(d[7]),
          "+f"(d[8]), "+f"(d[9]), "+f"(d[10]), "+f"(d[11]), "+f"(d[12]), "+f"(d[13]), "+f"(d[14]), "+f"(d[15])
        : "r"(a[0]), "r"(a[1]), "r"(a[2]), "r"(a[3]), "l"(db));
}

__device__ __forceinline__ void wgmma_rs_n16_set(float (&d)[8], const uint32_t (&a)[4], uint64_t db) {
    asm volatile(
        "wgmma.mma_async.sync.aligned.m64n16k16.f32.bf16.bf16 "
        "{%0,%1,%2,%3,%4,%5,%6,%7}, "
        "{%8,%9,%10,%11}, %12, 0, 1, 1, 0;"
        : "=f"(d[0]), "=f"(d[1]), "=f"(d[2]), "=f"(d[3]), "=f"(d[4]), "=f"(d[5]), "=f"(d[6]), "=f"(d[7])
        : "r"(a[0]), "r"(a[1]), "r"(a[2]), "r"(a[3]), "l"(db));
}

__device__ __forceinline__ void wgmma_rs_n16_acc(float (&d)[8], const uint32_t (&a)[4], uint64_t db) {
    asm volatile(
        "wgmma.mma_async.sync.aligned.m64n16k16.f32.bf16.bf16 "
        "{%0,%1,%2,%3,%4,%5,%6,%7}, "
        "{%8,%9,%10,%11}, %12, 1, 1, 1, 0;"
        : "+f"(d[0]), "+f"(d[1]), "+f"(d[2]), "+f"(d[3]), "+f"(d[4]), "+f"(d[5]), "+f"(d[6]), "+f"(d[7])
        : "r"(a[0]), "r"(a[1]), "r"(a[2]), "r"(a[3]), "l"(db));
}

__device__ __forceinline__ void wgmma_rs_n32_pred(float (&d)[16], const uint32_t (&a)[4], uint64_t db, uint32_t scale_d) {
    asm volatile(
        "{.reg .pred p; setp.ne.u32 p, %21, 0; wgmma.mma_async.sync.aligned.m64n32k16.f32.bf16.bf16 "
        "{%0,%1,%2,%3,%4,%5,%6,%7,%8,%9,%10,%11,%12,%13,%14,%15}, "
        "{%16,%17,%18,%19}, %20, p, 1, 1, 0;}"
        : "+f"(d[0]), "+f"(d[1]), "+f"(d[2]), "+f"(d[3]), "+f"(d[4]), "+f"(d[5]), "+f"(d[6]), "+f"(d[7]),
          "+f"(d[8]), "+f"(d[9]), "+f"(d[10]), "+f"(d[11]), "+f"(d[12]), "+f"(d[13]), "+f"(d[14]), "+f"(d[15])
        : "r"(a[0]), "r"(a[1]), "r"(a[2]), "r"(a[3]), "l"(db), "r"(scale_d));
}

__device__ __forceinline__ void prep_cta(uint32_t sb, int c, const __nv_bfloat16* __restrict__ wc,
                                         const __nv_bfloat16* __restrict__ se1, const __nv_bfloat16* __restrict__ se2) {
    const int tid = threadIdx.x, lane = tid & 31, warp = tid >> 5;
    constexpr int NROW = 2 * NF * NF;
#pragma unroll
    for (int q = tid; q < NROW * 2; q += 384) cp16(sb + q * 16, wc + (q >> 1) * ND + c * 16 + (q & 1) * 8);
    if (tid == 0) sts128(sb + NROW * 32, 0, 0, 0, 0);
    if (tid < 256) {
        const int l2 = c >> 1, n = ((tid >> 2) & 1) * 8 + (tid >> 5) + (l2 ? (c & 1) * 16 : 0);
        const int k = ((tid >> 1) & 1) * 8 + ((tid >> 3) & 3) * 2 + (tid & 1), mm = k >> 1, u = k & 1;
        const int f = l2 ? fmap(n) : mm < 6 ? 4 * mm + 2 * c + u : (mm == 6 && u == 0) ? 24 + c : -1;
        float v = 0.f;
        if (f >= 0 && (l2 ? k : n) < NR) v = __bfloat162float(l2 ? se2[k * NF + f] : se1[f * NR + n]);
        reinterpret_cast<__nv_bfloat16*>(g_se)[c * 256 + tid] = __float2bfloat16(l2 ? 0.5f * v : v);
    }
    asm volatile("cp.async.wait_all;" ::: "memory");
    __syncthreads();
    const int k = 4 * (lane & 6) + 2 * (lane >> 3) + (lane & 1), i = fmap(k);
    const int g = lane >> 2, t = lane & 3;
#pragma unroll 4
    for (int task = warp; task < 128; task += 12) {
        const int eg = task & 1, n = (task >> 1) & 31, s = task >> 6;
        const int j = fmap(n);
        const uint32_t a = k < 28 ? sb + ((s * NF + i) * NF + j) * 32 + eg * 16 : sb + NROW * 32;
        uint4 v;
        asm volatile("ldmatrix.sync.aligned.m8n8.x4.trans.shared.b16 {%0,%1,%2,%3}, [%4];"
                     : "=r"(v.x), "=r"(v.y), "=r"(v.z), "=r"(v.w)
                     : "r"(a));
        const int e = eg * 8 + g;
        if (t == 3) {
            const uint32_t mask = eg ? 0xffff0000u : 0xffffu;
            v.x &= mask;
            v.y &= mask;
        }
        const int ch = (t < 2 ? t ^ ((e >> 1) & 1) : t) ^ ((n >> 1) & 3);
        g_wc[(c >> 1) * 8192 + ((g & 1) + 2 * eg + 2 * (g & 6)) * 512 + (c & 1) * 256 + s * 128 + n * 4 + ch] = v;
    }
    __threadfence();
    __syncthreads();
    if (tid == 0) atomicAdd(&g_ready, 1u);
}

#define TWARM 7
#define WPF_STEP 800
#define WDELAY 1600
#define WSTEP 500
#define START_MIN 3300
#define PACE1 2100
#define PACE2 2700
#define PF_START 2600
#define PF_PACE 550
#define WPF_AT 3000

__global__ void __cluster_dims__(2, 1, 1) __launch_bounds__(384, 1)
fibinet_kernel(const int* __restrict__ idx, const uint4* __restrict__ table,
               const __nv_bfloat16* __restrict__ se1, const __nv_bfloat16* __restrict__ se2,
               const __nv_bfloat16* __restrict__ wc,
               const unsigned char* __restrict__ w1, const __nv_bfloat16* __restrict__ w2, __nv_bfloat16* __restrict__ out,
               const __grid_constant__ CUtensorMap tm_w1, const __grid_constant__ CUtensorMap tm_bi) {
    extern __shared__ __align__(1024) unsigned char smem[];
    const uint32_t t_start = clock32();
    const int tid = threadIdx.x;
    const uint32_t sb = (uint32_t)__cvta_generic_to_shared(smem);
    if (blockIdx.x < NPREP) {
        prep_cta(sb, blockIdx.x, wc, se1, se2);
        return;
    }
    const int cta = blockIdx.x - NPREP, grp = cta >> 1, rank = cta & 1, lane = tid & 31;
    uint32_t ids[13][4], cid[3][2];
    uint32_t gd0 = 0;
    const uint4* tp = table + (lane & 7);
    auto gather = [&](int i) {
#pragma unroll
        for (int u = 0; u < 4; u++)
            asm volatile("{.reg .u64 a; mad.wide.u32 a, %2, 128, %1; cp.async.cg.shared.global [%0], [a], 16;}" ::"r"(
                             (gd0 ^ ((u & 1) * 64)) + xpair(i) + u * 512),
                         "l"(tp), "r"(ids[i][u])
                         : "memory");
        CP_COMMIT();
    };
    if (tid < 256) {
        const uint32_t w = tid >> 7, row = ((tid >> 5) & 3) * 16 + (lane >> 3);
        const int* ip = idx + ((grp * 64 + row) * NF + 2 * w);
#pragma unroll
        for (int u = 0; u < 4; u++)
            asm volatile("ld.global.nc.L2::128B.v2.u32 {%0,%1}, [%2];" : "=r"(ids[0][u]), "=r"(ids[1][u]) : "l"(ip + 4 * NF * u));
        const int* cp = idx + ((grp * 64 + ((tid & 127) >> 1)) * NF + 2 * w + 4 + 4 * (tid & 1));
#pragma unroll
        for (int k = 0; k < 3; k++)
            asm volatile("ld.global.nc.v2.u32 {%0,%1}, [%2];"
                         : "=r"(cid[k][0]), "=r"(cid[k][1])
                         : "l"(cp + 8 * k - (k == 2 ? 2 * (w & tid) : 0)));
        gd0 = sb + w * XDELTA + row * 128 + (((lane & 7) ^ (lane >> 3) ^ (4 * w)) << 4);
        gather(0);
    } else {
        if (tid == 256) asm volatile("prefetch.tensormap [%0];" ::"l"(&tm_w1));
        if (tid == 288) asm volatile("prefetch.tensormap [%0];" ::"l"(&tm_bi));
    }
    const int warp = __reduce_max_sync(0xffffffffu, tid >> 5);
    const int w = warp >> 2;

    if (w == 2) {
        asm volatile("setmaxnreg.dec.sync.aligned.u32 40;");
        auto load_wc = [&](int gi) {
            if (elect()) {
                const unsigned char* src = reinterpret_cast<const unsigned char*>(g_wc) + rank * 131072;
                mbar_expect(sb + BAR_WC + gi * 8, (wcfirst(gi + 1) - wcfirst(gi)) * 8192);
#pragma unroll
                for (int c = wcfirst(gi); c < wcfirst(gi + 1); c++) bulk(sb + wcslot(c), src + c * 8192, 8192, sb + BAR_WC + gi * 8);
            }
            __syncwarp();
        };
        if (warp == 8) {
            if (elect()) {
                mbar_init(sb + BAR_Z, 1);
                mbar_expect(sb + BAR_Z, 8192);
                tma2d(sb + ZOFF, &tm_bi, sb + BAR_Z, 32 * rank, 0);
            }
#pragma unroll
            for (int f = 0; f < 26; f++) {
                if (f == 2) {
                    if (elect()) {
#pragma unroll
                        for (int k = 2; k < 8; k++) mbar_init(sb + BAR_FULL + k * 8, 1);
                        asm volatile("fence.mbarrier_init.release.cluster;" ::: "memory");
                    }
                    __syncwarp();
                    asm volatile("barrier.cluster.arrive.relaxed.aligned;" ::: "memory");
                    mbar_wait(sb + BAR_Z);
#pragma unroll
                    for (int k = 0; k < 2; k++)
                        sts128(sb + ZOFF + (k * 32 + lane) * 128 + ((4 ^ (lane & 7)) << 4), 0x3c803c80u, 0x3c803c80u, 0x3c803c80u, 0x3c803c80u);
                    PROXY_FENCE();
                    asm volatile("bar.arrive 0, 384;" ::: "memory");
                    TS(31);
                }
                if (f == 5) asm volatile("barrier.cluster.wait.aligned;" ::: "memory");
                if (f >= 5) mbar_wait(sb + bdone(f - 5), bpar(f - 5));
                if (f >= 2 && f < 5)
                    while (clock32() - t_start < WDELAY + (f - 2) * WSTEP) {
                    }
                if (elect()) {
                    if (f < 2) mbar_init(sb + BAR_FULL + f * 8, 1);
                    mbar_expect(sb + bfull(f), 16384);
                    tma2d(sb + slot(2 * wl(f)), &tm_w1, sb + bfull(f), 128 * rank + 64 * (f & 1), fieldof(f) * 64);
                    tma2d(sb + slot(wl(f)), &tm_w1, sb + bfull(f), 128 * rank + 64 - 64 * (f & 1), fieldof(f) * 64);
                }
                TS(f);
            }
            if (elect()) mbar_arrive(sb + BAR_GO);
            TS_DUMP(2);
        } else if (warp == 9) {
            if (elect()) {
#pragma unroll
                for (int k = 0; k < 11; k++) mbar_init(sb + BAR_WC + k * 8, k < 10 ? 1 : 8);
                asm volatile("fence.mbarrier_init.release.cluster;" ::: "memory");
                mbar_expect(sb + BAR_FIN, 512);
            }
            __syncwarp();
            asm volatile("barrier.cluster.arrive.relaxed.aligned;" ::: "memory");
            asm volatile("bar.sync 0, 384;" ::: "memory");
            mbar_wait(sb + bdone(3), bpar(3));
            if (elect()) {
                unsigned v, it = 0;
                do {
                    asm volatile("ld.acquire.gpu.global.u32 %0, [%1];" : "=r"(v) : "l"(&g_ready) : "memory");
                } while (v < NPREP && ++it < 4000000u);
                asm volatile("fence.proxy.async.global;" ::: "memory");
                mbar_expect(sb + BAR_SE, 2048);
                bulk(sb + SEOFF, g_se, 2048, sb + BAR_SE);
                if (atomicAdd(&g_seen, 1u) == NMAIN - 1) {
                    g_seen = 0;
                    g_ready = 0;
                }
            }
            __syncwarp();
            TS(0);
            mbar_wait(sb + BAR_GO);
#pragma unroll
            for (int gi = 0; gi < 3; gi++) {
                mbar_wait(sb + bdone(21 + gi), bpar(21 + gi));
                load_wc(gi);
                TS(1 + gi);
            }
        } else if (warp == 10) {
            if (elect()) {
#pragma unroll
                for (int k = 0; k < 8; k++) mbar_init(sb + BAR_DONE + k * 8, 4);
                asm volatile("fence.mbarrier_init.release.cluster;" ::: "memory");
            }
            __syncwarp();
            asm volatile("barrier.cluster.arrive.relaxed.aligned;" ::: "memory");
            asm volatile("bar.arrive 0, 384;" ::: "memory");
#pragma unroll 1
            for (int k = 0; k < 7; k++) {
                while (clock32() - t_start < (uint32_t)(WPF_AT + k * WPF_STEP)) __nanosleep(20);
                if (lane < 6)
                    asm volatile("prefetch.global.L2 [%0];" ::"l"(w1 + (5 + k * 3 + (lane >> 1)) * 32768 + cta * 256 + (lane & 1) * 128));
            }
        } else {
            asm volatile("barrier.cluster.arrive.relaxed.aligned;" ::: "memory");
            asm volatile("bar.sync 0, 384;" ::: "memory");
            const uint2 v = __ldg(reinterpret_cast<const uint2*>(w2 + 128 * rank) + lane);
#pragma unroll
            for (int k = 0; k < 2; k++) {
                const uint32_t x = k ? v.y : v.x;
                sts64(sb + w2chunk((lane >> 2) * 4 + 2 * (lane & 1) + k) + (lane & 2) * 4,
                      __float_as_uint(0.5f * __uint_as_float(x << 16)), __float_as_uint(0.5f * __uint_as_float(x & 0xffff0000u)));
            }
            __syncwarp();
            if (lane == 0) mbar_arrive(sb + BAR_W2);
        }
        if (warp != 8) asm volatile("barrier.cluster.wait.aligned;" ::: "memory");
        {
            uint32_t bw[2][4], z0[4], z1[4];
            mbar_wait(sb + BAR_SE);
            lds128(bw[0], sb + SEOFF + lane * 16);
            lds128(bw[1], sb + SEOFF + 512 + lane * 16);
            asm volatile("bar.sync 2, 384;" ::: "memory");
            lds128(z0, sb + ZQOFF + (tid & 127) * 16);
            lds128(z1, sb + ZQOFF + 2048 + (tid & 127) * 16);
            TS(8);
            float s[2][4] = {};
#pragma unroll
            for (int n = 0; n < 2; n++) {
                mma16816(s[n], z0, bw[0][2 * n], bw[0][2 * n + 1]);
                mma16816(s[n], z1, bw[1][2 * n], bw[1][2 * n + 1]);
            }
            lds128(bw[0], sb + SEOFF + 1024 + lane * 16);
            lds128(bw[1], sb + SEOFF + 1536 + lane * 16);
            float th[8];
#pragma unroll
            for (int k = 0; k < 8; k++) th[k] = gelu_tanh(s[k >> 2][k & 3]);
            SCHED_FENCE();
            TS(9);
            uint32_t gq[4];
#pragma unroll
            for (int k = 0; k < 4; k++)
                gq[k] = pack(s[k >> 1][2 * (k & 1)] * ffma(th[2 * k], 0.5f, 0.5f), s[k >> 1][2 * (k & 1) + 1] * ffma(th[2 * k + 1], 0.5f, 0.5f));
            float a[4][4] = {};
#pragma unroll
            for (int n = 0; n < 4; n++) mma16816(a[n], gq, bw[n >> 1][2 * (n & 1)], bw[n >> 1][2 * (n & 1) + 1]);
#pragma unroll
            for (int k = 0; k < 16; k++)
                if (k < 13 || k == 14) a[k >> 2][k & 3] = tanh_fast(a[k >> 2][k & 3]);
            SCHED_FENCE();
            TS(10);
            uint32_t ap[8];
#pragma unroll
            for (int k = 0; k < 8; k++)
                ap[k] = pack(ffma(a[k >> 1][2 * (k & 1)], 0.5f, 0.5f), ffma(a[k >> 1][2 * (k & 1) + (k < 6)], 0.5f, 0.5f));
            sts128(sb + GOFF + (tid & 127) * 16, ap[0], ap[1], ap[2], ap[3]);
            sts128(sb + GOFF + 2048 + (tid & 127) * 16, ap[4], ap[5], ap[6], ap[7]);
            asm volatile("bar.arrive 3, 384;" ::: "memory");
            TS(11);
        }
        if (warp == 9) {
            load_wc(3);
            load_wc(4);
            mbar_wait(sb + BAR_TD);
            load_wc(5);
            if (lane < 16) TS_DUMP(3);
        } else if (warp == 10) {
            __nv_bfloat16* dst = out + cta * 32 + lane;
            asm volatile("" : "+l"(dst));
            asm volatile("bar.sync 4, 64;" ::: "memory");
            mbar_wait(sb + BAR_FIN);
            uint32_t p[4];
            lds128(p, sb + PARTOFF + lane * 16);
            *dst = __float2bfloat16((__uint_as_float(p[0]) + __uint_as_float(p[1])) + (__uint_as_float(p[2]) + __uint_as_float(p[3])));
        }
    } else {
        asm volatile("setmaxnreg.inc.sync.aligned.u32 232;");
        asm volatile("barrier.cluster.arrive.relaxed.aligned;" ::: "memory");
        const int g = lane >> 2, t = lane & 3, wq = warp & 3, t128 = tid & 127;
        gd0 = opaque(gd0);
        TS(28);
        float acc[84];
#pragma unroll
        for (int k = 0; k < 84; k++) asm volatile("mov.b32 %0, 0;" : "=f"(acc[k]));
        uint32_t e0[9], e1[9], e2[9];
        uint32_t X[13][2][4];
        uint32_t zq[4] = {0, 0, 0, 0};
        const uint64_t dA = mkdesc(sb + w * XDELTA, 16, 1024, 1);
        uint32_t dBlo = (uint32_t)mkdesc(sb + ZOFF, 0, 0, 0);
        const uint32_t xl0 = opaque(sb + (t & 1) * XDELTA + (16 * wq + g) * 128 + (((4 * rank + 2 * w) ^ (4 * (t & 1)) ^ g) << 4));
        const uint32_t hi_half = t >> 1;
        const uint32_t sa0 = opaque(sb + AOFF + t * 4096 + (t >> 1) * 16 + (wq * 32 + g * 4 + w) * 16);
        const uint32_t sa1 = opaque(((g & 2) << 4) | ((t & 1) << 3));
        const uint32_t zero = blockIdx.y;
        auto expand = [&](int k0, int k1) {
#pragma unroll
            for (int k = k0; k < k1; k++)
#pragma unroll
                for (int u = 0; u < 4; u++)
                    asm volatile("shfl.sync.idx.b32 %0, %1, %2, 31, 0xffffffff;"
                                 : "=r"(ids[k][u])
                                 : "r"(k < 12 ? cid[(k - 2) >> 2][k & 1] : w ? cid[2][1] : cid[2][0]),
                                   "r"(2 * (lane >> 3) + 8 * u + (((k - 2) >> 1) & 1)));
        };
        auto twarm = [&]() {
            float s1[8];
            WG_FENCE();
            wgmma_rs_n16_set(s1, zq, mkdesc(sb + AOFF, 16, 512, 2));
            WG_COMMIT();
            WG_WAIT0();
            pin(s1);
            asm volatile("{.reg .pred p; setp.ne.u32 p, %1, 0; @p st.shared.f32 [%1], %0;}" ::"f"(s1[0]), "r"(zero));
        };
        expand(2, 8);
        if (TWARM & 1) twarm();
        TS(26);
        while (clock32() - t_start < PACE1) {
        }
        gather(1);
        expand(8, 13);
        if (TWARM & 2) twarm();
        TS(30);
        while (clock32() - t_start < PACE2) {
        }
        gather(2);
        if (TWARM & 4) twarm();
        asm volatile("bar.sync 0, 384;" ::: "memory");
        auto lift = [&](int i) {
            const int m = 2 * (i >> 2) + (i & 1);
#pragma unroll
            for (int r = 0; r < (i < 12 ? 2 : 1); r++)
#pragma unroll
                for (int cc = 0; cc < 2; cc++) {
                    const uint32_t a = (xl0 ^ (cc * 16)) + xpair(i) + (i < 12 ? r : hi_half) * 1024;
                    if (i & 2) lds128_if(X[2 * m + r][cc], a, hi_half);
                    else lds128(X[2 * m + r][cc], a);
                }
        };
        auto store_pair = [&](int m, int half, const uint32_t (&ea)[9]) {
            uint32_t a;
            if (m < 4) a = sa0 + (sa1 ^ (((m & 1) << 5) | ((m >> 1) << 3)));
            else a = sb + BOFF + t * 2048 + (wq * 32 + g * 4 + ((2 * (m & 1) + w) ^ t)) * 8;
#pragma unroll
            for (int n = half; n < 4; n += 2)
#pragma unroll
                for (int u = 0; u < 2; u++)
                    sts64(a + (m < 4 ? (8 * n + u) * 2048 + n * 32 : (8 * n + u) * 1024),
                          __byte_perm(ea[2 * n], e1[2 * n], u ? 0x7632 : 0x5410),
                          __byte_perm(ea[2 * n + 1], e1[2 * n + 1], u ? 0x7632 : 0x5410));
        };
        auto z_pair = [&](int m, uint32_t a, uint32_t b) {
            asm volatile("{.reg .pred p; setp.eq.u32 p, %4, %5; @p prmt.b32 %0, %2, %3, 0x5410; @p prmt.b32 %1, %2, %3, 0x7632;}"
                         : "+r"(zq[2 * (m >> 2)]), "+r"(zq[2 * (m >> 2) + 1])
                         : "r"(a), "r"(b), "r"(t), "r"(m & 3));
        };

        TS(29);
        mbar_wait(sb + BAR_FULL + w * 8);
        CP_WAIT(2);
        while (clock32() - t_start < START_MIN) {
        }
        if (w == 1) {
            asm volatile("bar.arrive 6, 256;" ::: "memory");
            asm volatile("bar.sync 5, 256;" ::: "memory");
        }
#pragma unroll
        for (int i = 0; i < 13; i++) {
            const uint64_t da = dA + (xpair(i) >> 4) + ((uint64_t)i << 16);
            dBlo += (uint32_t)(w ? wl(2 * i + 1) - (i ? wl(2 * i - 1) : 0) : wl(2 * i) - (i ? wl(2 * i - 2) : 0)) *
                    (uint32_t)((SLOT << 12) - (SLOT >> 3));
            const uint64_t db = mkdesc(0, 0, 1024, 1) | dBlo;
            TS(i);
            WG_FENCE();
            wgmma_ss_n168_acc(acc, da, db + w * 256);
            wgmma_ss_n168_acc(acc, da + 2, db + w * 256 + 128);
            wgmma_ss_n168_acc(acc, da + 4, db + (w ^ 1) * 256);
            wgmma_ss_n168_acc(acc, da + 6, db + (w ^ 1) * 256 + 128);
            WG_COMMIT();
            if (i == 0) {
                if (w == 0) {
                    asm volatile("bar.arrive 5, 256;" ::: "memory");
                    asm volatile("bar.sync 6, 256;" ::: "memory");
                }
            } else {
                mbar_wait(sb + bdone(2 * i - 2) + (w ^ 1) * 8, bpar(2 * i - 2));
            }
            if (i < 10) gather(i + 3);
            if (i == 1) asm volatile("barrier.cluster.wait.aligned;" ::: "memory");
            if (i == 6) mbar_wait(sb + BAR_W2);
            lift(i);
            if (i == 10 || i == 11) mbar_wait(sb + bdone(2 * i - 2) + w * 8, bpar(2 * i - 2));
            if (i >= 2 && !(i & 1)) {
                z_pair((i - 2) >> 1, e0[8], e1[8]);
                store_pair((i - 2) >> 1, 0, e0);
#pragma unroll
                for (int k = 0; k < 8; k++) e2[k] = e0[k];
            } else if (i >= 3) {
                store_pair((i - 3) >> 1, 1, e2);
            }
            const uint32_t rdy = i < 12 ? mbar_test(sb + bfull(2 * i + 2) + w * 8, bpar(2 * i + 2)) : 0;
            WG_WAIT0();
            pin(acc);
            if (i == 12) TS(13);
            if (i == 0) TS(27);
            if (i < 10) CP_WAIT(2);
            else if (i == 10) CP_WAIT(1);
            else if (i == 11) CP_WAIT(0);
            if (i < 12 && lane == 0) mbar_arrive(sb + bdone(2 * i) + w * 8);
#pragma unroll
            for (int k = 0; k < 9; k++) {
                const int k0 = 64 + 2 * (k & 5) + ((k >> 1) & 1);
                const uint32_t v = k == 8 ? pack(acc[80], acc[82]) : i < 12 ? pack(acc[64 + 2 * k], acc[65 + 2 * k]) : pack(acc[k0], acc[k0 + 4]);
                if (i & 1) e1[k] = v;
                else e0[k] = v;
            }
            if (i < 12) {
#pragma unroll
                for (int k = 64; k < 83; k++)
                    if (k != 81) asm volatile("mov.b32 %0, %1;" : "+f"(acc[k]) : "r"(zero));
                mbar_wait_unless(rdy, sb + bfull(2 * i + 2) + w * 8, bpar(2 * i + 2));
            } else {
                z_pair(6, e0[8], 0);
                sts128(sb + ZQOFF + w * 2048 + t128 * 16, zq[0], zq[1], zq[2], zq[3]);
                asm volatile("bar.arrive 2, 384;" ::: "memory");
            }
        }
        TS(14);

        float aj[13];
        uint32_t ai[8];
        float sum0 = 0.f, sum1 = 0.f;
        float th[32];
        uint32_t hw[4][4];
        auto deep_issue = [&](int k2) {
            lds128(hw[k2], ((sb + w2chunk(w * 16 + t)) ^ ((k2 & 1) * 64)) + k2 * 512);
#pragma unroll
            for (int k = 8 * k2; k < 8 * k2 + 8; k++) th[k] = gelu_tanh(acc[k]);
        };
        auto deep_use = [&](int k2) {
#pragma unroll
            for (int k = 8 * k2; k < 8 * k2 + 8; k++) {
                const float h = __uint_as_float(hw[k2][((k >> 1) & 2) + (k & 1)]);
                const float y = ffma(th[k], h, h);
                if (k & 2) sum1 = ffma(acc[k], y, sum1);
                else sum0 = ffma(acc[k], y, sum0);
            }
        };
        auto deep_send = [&](int k0, int k1) {
#pragma unroll
            for (int k = k0; k < k1; k++)
                sts128(sb + EXOFF + w * SLOT + t128 * 16 + k * 2048, pack(acc[32 + 8 * k], acc[33 + 8 * k]),
                       pack(acc[34 + 8 * k], acc[35 + 8 * k]), pack(acc[36 + 8 * k], acc[37 + 8 * k]), pack(acc[38 + 8 * k], acc[39 + 8 * k]));
        };
        uint32_t o[4][4];
        auto deep_recv = [&](int k0, int k1) {
#pragma unroll
            for (int k = k0; k < k1; k++) lds128(o[k], sb + EXOFF + (w ^ 1) * SLOT + t128 * 16 + k * 2048);
        };
        auto deep_add = [&](int k0, int k1) {
            const uint32_t eye = (g >> 1) == t ? ((g & 1) ? 0x3f800000u : 0x3f80u) : 0u;
#pragma unroll
            for (int k = 2 * k0; k < 2 * k1; k++)
                asm volatile("mma.sync.aligned.m16n8k8.row.col.f32.bf16.bf16.f32 {%0,%1,%2,%3}, {%4,%5}, {%6}, {%0,%1,%2,%3};"
                             : "+f"(acc[4 * k]), "+f"(acc[4 * k + 1]), "+f"(acc[4 * k + 2]), "+f"(acc[4 * k + 3])
                             : "r"(o[k >> 1][2 * (k & 1)]), "r"(o[k >> 1][2 * (k & 1) + 1]), "r"(eye));
        };
        auto store_last = [&]() {
#pragma unroll
            for (int n = 0; n < 4; n++) sts64(sb + COFF + w * 4096 + n * 1024 + (t128 ^ w) * 8, e0[2 * n], e0[2 * n + 1]);
            store_pair(5, 1, e2);
        };
        const uint32_t la = sb + AOFF + w * (16 * 2048 + 64) + (wq * 32 + g * 4 + (t ^ (g & 2))) * 16;
        const uint32_t lb = sb + BOFF + w * (16 * 1024) + t128 * 8;
        const uint32_t lc0 = sb + COFF + (t & 1) * (4096 + 8) + w * 2048 + (wq * 8 + g) * 32, lc1 = lc0 ^ 8;
        uint32_t Ap[2][2][4];
        auto load_a = [&](int s) {
            const int e = estep(s);
            lds128(Ap[s & 1][0], la + e * 2048 + (e >> 2) * 16);
            lds64(Ap[s & 1][1][0], Ap[s & 1][1][1], (lb ^ ((e & 6) * 4)) + e * 1024);
            if (!(s & 2)) lds64(Ap[s & 1][1][2], Ap[s & 1][1][3], ((e & 2) ? lc1 : lc0) + (e & 1) * 1024 + (e & 4) * 4);
        };
        {
            deep_send(0, 2);
            asm volatile("bar.sync 1, 256;" ::: "memory");
            deep_recv(0, 2);
            deep_send(2, 4);
            TS(15);
            deep_add(0, 2);
            deep_issue(0);
            asm volatile("bar.sync 1, 256;" ::: "memory");
            deep_recv(2, 4);
            SCHED_FENCE();
            deep_add(2, 4);
            TS(16);
            deep_issue(1);
            deep_use(0);
            store_last();
            SCHED_FENCE();
            TS(17);
            deep_issue(2);
            deep_use(1);
            mbar_wait(sb + BAR_WC);
            deep_use(2);
            TS(18);
            asm volatile("bar.sync 3, 384;" ::: "memory");
            uint32_t v[2][4];
            lds128(v[0], sb + GOFF + t128 * 16);
            lds128(v[1], sb + GOFF + 2048 + t128 * 16);
            load_a(0);
            load_a(1);
            deep_issue(3);
#pragma unroll
            for (int k = 0; k < 8; k++) ai[k] = v[k >> 2][k & 3];
#pragma unroll
            for (int q = 0; q < 13; q++) {
                const uint32_t x = q < 12 ? ai[2 * (q >> 2) + (q & 1)] : hi_half ? ai[7] : ai[6];
                aj[q] = __uint_as_float((q & 2) ? x & 0xffff0000u : x << 16);
            }
        }
        TS(19);

        uint32_t fin_a, dsum[2];
        {
            uint64_t dW[4];
#pragma unroll
            for (int k = 0; k < 4; k++) dW[k] = mkdesc(sb + w * 4096, 16, 512, 2) + (wcslot(0) >> 4) + (k >> 1) * 128 + (k & 1) * 2;
            uint32_t Aq[2][2][4], hacc[2][4], hlast, V[13];
            float Sp[16], Sq[16], U[13];
            auto scale_a = [&](int s) {
#pragma unroll
                for (int k = 0; k < ((s & 2) ? 6 : 8); k++)
                    Aq[s & 1][k >> 2][k & 3] = hmul2(Ap[s & 1][k >> 2][k & 3], ai[k < 4 ? k ^ (estep(s) & 2) : k]);
            };
            auto dot = [&](int s) {
#pragma unroll
                for (int q = 0; q < 13; q++) {
                    const uint32_t x = X[q][(s >> 1) & 1][s >> 2];
                    if (q == 12) hlast = s == 1 ? hmul2(V[q], x) : hfma2(V[q], x, hlast);
                    else if ((s & 6) == 0 && q < 4) hacc[s >> 3][q] = hmul2(V[q], x);
                    else hacc[s >> 3][q & 3] = hfma2(V[q], x, hacc[s >> 3][q & 3]);
                }
            };
            scale_a(0);
#pragma unroll
            for (int e = 0; e < 16; e++) {
                WG_FENCE();
                if (e == 0) wgmma_rs_n32_set(Sp, Ap[e & 1][0], dW[0]);
                else wgmma_rs_n32_pred(Sp, Ap[e & 1][0], dW[0], zero);
                wgmma_rs_n32_acc(Sp, Ap[e & 1][1], dW[1]);
                if (e == 0) wgmma_rs_n32_set(Sq, Aq[e & 1][0], dW[2]);
                else wgmma_rs_n32_pred(Sq, Aq[e & 1][0], dW[2], zero);
                wgmma_rs_n32_acc(Sq, Aq[e & 1][1], dW[3]);
                WG_COMMIT();
                SCHED_FENCE();
                if (e < 15) {
#pragma unroll
                    for (int k = 0; k < 4; k++)
                        asm volatile("add.s64 %0, %0, %1;" : "+l"(dW[k]) : "l"((int64_t)((wcslot(e + 1) - wcslot(e)) / 16)));
                }
                if (e == 0) deep_use(3);
                if (e > 0 && !(e & 1)) dot(e - 1);
                if (e == 1) {
                    const float h0 = __uint_as_float(__float_as_uint(sum0) & 0xffff0000u);
                    const float h1 = __uint_as_float(__float_as_uint(sum1) & 0xffff0000u);
                    dsum[0] = pack(sum0 - h0, h0);
                    dsum[1] = pack(sum1 - h1, h1);
                }
                if (e == 13) {
                    asm("mapa.shared::cluster.u32 %0, %1, %2;"
                        : "=r"(fin_a)
                        : "r"(sb + PARTOFF + (((wq & 1) * 16 + t * 8 + g) * 4 + 2 * rank + w) * 4), "r"(wq >> 1));
                    fin_a = opaque(fin_a);
                }
                if (e == 15 && warp == 0) asm volatile("bar.arrive 4, 64;" ::: "memory");
                if (e + 1 < 16) scale_a(e + 1);
                if (e == 0 || e == 1 || e == 4 || e == 7 || e == 10)
                    mbar_wait(sb + BAR_WC + (e == 0 ? 1 : e == 1 ? 2 : e == 4 ? 3 : e == 7 ? 4 : 5) * 8);
                else if (e < 15)
                    SCHED_FENCE();
                WG_WAIT0();
                pin(Sp);
                pin(Sq);
                if (e == 0 && lane == 0) mbar_arrive(sb + BAR_TD);
                if (e == 0) TS(20);
                if (e + 2 < 16) load_a(e + 2);
#pragma unroll
                for (int q = 0; q < 13; q++) {
                    const int ix = 4 * (q >> 2) + 2 * (q & 1) + ((q >> 1) & 1);
                    float u = ffma(aj[q], Sq[ix], Sp[ix]);
                    if (q == 12)
                        asm volatile("{.reg .pred p; setp.ne.u32 p, %4, 0; @p fma.rn.f32 %0, %1, %2, %3;}"
                                     : "+f"(u)
                                     : "f"(aj[12]), "f"(Sq[14]), "f"(Sp[14]), "r"(hi_half));
                    if (!(e & 1)) U[q] = u;
                    else V[q] = pack(U[q], u);
                }
                if (e == 7) TS(21);
            }
            float r[4] = {0.f, 0.f, 0.f, 0.f}, r2[4] = {0.f, 0.f, 0.f, 0.f};
            mma16816(r, hacc[0], 0x3f803f80u, 0x3f803f80u);
            dot(15);
            const uint32_t rest[4] = {dsum[0], dsum[1], hi_half ? 0u : hlast, hi_half ? hlast : 0u};
            mma16816(r, hacc[1], 0x3f803f80u, 0x3f803f80u);
            mma16816(r2, rest, 0x3f803f80u, 0x3f803f80u);
            sum0 = r[0] + r2[0];
            sum1 = r[2] + r2[2];
        }
        TS(22);
        {
            const float v = (t & 1) ? sum1 : sum0;
            asm volatile(
                "{.reg .pred p; setp.lt.u32 p, %3, 2; @p st.async.shared::cluster.mbarrier::complete_tx::bytes.f32 [%0], %1, [%2];}" ::"r"(fin_a),
                "f"(v), "r"((fin_a & ~0x3ffu) + (BAR_FIN & 0x3ff)), "r"(t)
                : "memory");
            if (wq == 0) TS_DUMP(w);
        }
    }
}

typedef CUresult (*EncodeFn)(CUtensorMap*, CUtensorMapDataType, cuuint32_t, void*, const cuuint64_t*, const cuuint64_t*,
                             const cuuint32_t*, const cuuint32_t*, CUtensorMapInterleave, CUtensorMapSwizzle,
                             CUtensorMapL2promotion, CUtensorMapFloatOOBfill);

}

extern "C" void kernel_launch(void* const* d_in, const int* in_sizes, int n_in, void* d_out, int out_size) {
    static EncodeFn encode = nullptr;
    if (!encode) {
        void* fn = nullptr;
        cudaDriverEntryPointQueryResult qr;
        cudaGetDriverEntryPoint("cuTensorMapEncodeTiled", &fn, cudaEnableDefault, &qr);
        encode = (EncodeFn)fn;
        cudaFuncSetAttribute(fibinet_kernel, cudaFuncAttributeMaxDynamicSharedMemorySize, SMEM_BYTES);
    }
    CUtensorMap tm;
    const cuuint64_t gd[2] = {NH, NF * ND};
    const cuuint64_t gs[1] = {NH * 2};
    const cuuint32_t bd[2] = {64, 64}, es[2] = {1, 1};
    encode(&tm, CU_TENSOR_MAP_DATA_TYPE_BFLOAT16, 2, d_in[6], gd, gs, bd, es, CU_TENSOR_MAP_INTERLEAVE_NONE,
           CU_TENSOR_MAP_SWIZZLE_128B, CU_TENSOR_MAP_L2_PROMOTION_L2_256B, CU_TENSOR_MAP_FLOAT_OOB_FILL_NONE);
    CUtensorMap tb;
    const cuuint64_t gd2[2] = {ND, ND};
    const cuuint64_t gs2[1] = {ND * 2};
    encode(&tb, CU_TENSOR_MAP_DATA_TYPE_BFLOAT16, 2, d_in[4], gd2, gs2, bd, es, CU_TENSOR_MAP_INTERLEAVE_NONE,
           CU_TENSOR_MAP_SWIZZLE_128B, CU_TENSOR_MAP_L2_PROMOTION_L2_256B, CU_TENSOR_MAP_FLOAT_OOB_FILL_NONE);
    fibinet_kernel<<<NPREP + NMAIN, 384, SMEM_BYTES>>>(
        (const int*)d_in[0], (const uint4*)d_in[1], (const __nv_bfloat16*)d_in[2], (const __nv_bfloat16*)d_in[3],
        (const __nv_bfloat16*)d_in[5], (const unsigned char*)d_in[6], (const __nv_bfloat16*)d_in[7], (__nv_bfloat16*)d_out, tm, tb);
}
```

```cpp
#include <cuda_runtime.h>
#include <cuda_bf16.h>
#include <cuda.h>
#include <stdint.h>

namespace {

constexpr int NB = 4096, NF = 26, ND = 64, NH = 256, NR = 13;
constexpr int NPREP = 4;
constexpr int NMAIN = 128;

constexpr int SLOT = 8192;
constexpr int ZOFF = 15 * SLOT;
__host__ __device__ constexpr int slot(int s) { return ZOFF - s * SLOT; }
constexpr int BOFF = ZOFF + SLOT;
constexpr int AOFF = BOFF + 32768;
constexpr int COFF = slot(12);
constexpr int MOFF = AOFF + 65536 + 128;
constexpr int BAR_FULL = MOFF, BAR_DONE = MOFF + 64, BAR_WC = MOFF + 128, BAR_FIN = MOFF + 176,
              BAR_GO = MOFF + 184, BAR_SE = MOFF + 192, BAR_W2 = MOFF + 200, BAR_TD = MOFF + 208, BAR_Z = MOFF + 216;
__host__ __device__ constexpr int bfull(int f) { return BAR_FULL + (f & 7) * 8; }
__host__ __device__ constexpr int bdone(int f) { return BAR_DONE + (f & 7) * 8; }
__host__ __device__ constexpr int bpar(int f) { return (f >> 3) & 1; }
constexpr int PARTOFF = MOFF + 256, SEOFF = MOFF + 768;
constexpr int SMEM_BYTES = MOFF + 2944;
static_assert((BAR_FIN >> 10) == (PARTOFF >> 10) && (BAR_FIN >> 10) == ((PARTOFF + 511) >> 10), "same 1 KB block");
constexpr int XDELTA = 2 * SLOT;
__host__ __device__ constexpr int xpair(int i) {
    return (i & 3) == 0 ? slot(11) : (i & 3) == 1 ? BOFF : (i & 3) == 2 ? BOFF + SLOT : slot(15);
}
__host__ __device__ constexpr int wl(int f) { return f % 5 == 0 ? 1 : f % 5 == 4 ? 7 : f % 5 + 2; }
__host__ __device__ constexpr int wcslot(int c) {
    return c == 0 ? slot(3) : c == 1 ? slot(8) : c == 2 ? slot(10) : c == 3 ? slot(15) : c == 4 ? slot(13)
         : c == 5 ? slot(11) : c == 6 ? slot(9) : c == 7 ? slot(14) : c == 8 ? slot(7) : c == 9 ? slot(2)
         : c == 10 ? slot(1) : c == 11 ? slot(4) : c == 12 ? slot(5) : c == 13 ? slot(6) : c == 14 ? ZOFF : slot(3);
}
__host__ __device__ constexpr int wcfirst(int gi) { return gi < 3 ? gi : gi == 3 ? 5 : gi == 4 ? 8 : gi == 5 ? 11 : 16; }
constexpr int EXOFF = slot(5);
constexpr int ZQOFF = slot(6);
constexpr int GOFF = ZQOFF + 4096;
__host__ __device__ constexpr int w2chunk(int c) { return ZOFF + c * 128 + ((5 ^ (c & 7)) << 4); }

__device__ uint4 g_wc[2 * 16 * 8192 / 16];
__device__ uint4 g_se[2048 / 16];
__device__ unsigned g_ready;
__device__ unsigned g_seen;

__host__ __device__ constexpr int fieldof(int f) { return f < 24 ? 4 * (f >> 2) + 2 * (f & 1) + ((f >> 1) & 1) : f; }
__device__ __forceinline__ int fmap(int n) { return n < 24 ? n : 24 + ((n >> 1) & 1); }
__host__ __device__ constexpr int estep(int s) { return (s & 1) + 2 * (s >> 2) + 4 * (s & 2); }

__device__ __forceinline__ uint64_t mkdesc(uint32_t addr, uint32_t lbo, uint32_t sbo, int sw) {
    return (uint64_t)((addr & 0x3ffff) >> 4) | ((uint64_t)(lbo >> 4) << 16) | ((uint64_t)(sbo >> 4) << 32) |
           ((uint64_t)sw << 62);
}
__device__ __forceinline__ void mbar_init(uint32_t b, uint32_t n) {
    asm volatile("mbarrier.init.shared.b64 [%0], %1;" ::"r"(b), "r"(n) : "memory");
}
__device__ __forceinline__ void mbar_wait(uint32_t b, uint32_t par = 0) {
    asm volatile(
        "{\n.reg .pred p, q;\n.reg .u32 n;\n"
        "mbarrier.try_wait.parity.shared.b64 p, [%0], %1;\n@p bra.uni WD%=;\nmov.u32 n, 0;\n"
        "WL%=:\nmbarrier.try_wait.parity.shared.b64 p, [%0], %1;\n@p bra.uni WD%=;\n"
        "add.u32 n, n, 1;\nsetp.lt.u32 q, n, 4000000;\n@q bra.uni WL%=;\nWD%=:\n}\n" ::"r"(b), "r"(par)
        : "memory");
}
__device__ __forceinline__ uint32_t mbar_test(uint32_t b, uint32_t par) {
    uint32_t ok;
    asm volatile("{.reg .pred p; mbarrier.test_wait.parity.shared.b64 p, [%1], %2; selp.u32 %0, 1, 0, p;}"
                 : "=r"(ok)
                 : "r"(b), "r"(par)
                 : "memory");
    return ok;
}
__device__ __forceinline__ void mbar_wait_unless(uint32_t ok, uint32_t b, uint32_t par) {
    asm volatile(
        "{\n.reg .pred p, q;\n.reg .u32 n;\n"
        "setp.ne.u32 p, %1, 0;\n@p bra.uni WD%=;\nmov.u32 n, 0;\n"
        "WL%=:\nmbarrier.try_wait.parity.shared.b64 p, [%0], %2;\n@p bra.uni WD%=;\n"
        "add.u32 n, n, 1;\nsetp.lt.u32 q, n, 4000000;\n@q bra.uni WL%=;\nWD%=:\n}\n" ::"r"(b), "r"(ok), "r"(par)
        : "memory");
}
__device__ __forceinline__ void mbar_arrive(uint32_t b) {
    asm volatile("mbarrier.arrive.shared.b64 _, [%0];" ::"r"(b) : "memory");
}
__device__ __forceinline__ void mbar_expect(uint32_t b, uint32_t bytes) {
    asm volatile("mbarrier.arrive.expect_tx.shared.b64 _, [%0], %1;" ::"r"(b), "r"(bytes) : "memory");
}
__device__ __forceinline__ uint32_t opaque(uint32_t v) { return __shfl_sync(0xffffffffu, v, threadIdx.x); }
__device__ __forceinline__ bool elect() {
    uint32_t p;
    asm volatile("{.reg .pred q; elect.sync _|q, 0xffffffff; selp.u32 %0, 1, 0, q;}" : "=r"(p));
    return p;
}
__device__ __forceinline__ void tma2d(uint32_t dst, const CUtensorMap* m, uint32_t bar, int x, int y) {
    asm volatile(
        "cp.async.bulk.tensor.2d.shared::cluster.global.mbarrier::complete_tx::bytes [%0], [%1, {%3, %4}], [%2];" ::"r"(dst),
        "l"(m), "r"(bar), "r"(x), "r"(y)
        : "memory");
}
__device__ __forceinline__ void bulk(uint32_t dst, const void* src, uint32_t bytes, uint32_t bar) {
    asm volatile("cp.async.bulk.shared::cluster.global.mbarrier::complete_tx::bytes [%0], [%1], %2, [%3];" ::"r"(dst),
                 "l"(src), "r"(bytes), "r"(bar)
                 : "memory");
}
__device__ __forceinline__ void cp16(uint32_t dst, const void* src) {
    asm volatile("cp.async.cg.shared.global [%0], [%1], 16;" ::"r"(dst), "l"(src) : "memory");
}
__device__ __forceinline__ void lds128(uint32_t (&v)[4], uint32_t a) {
    asm volatile("ld.shared.v4.u32 {%0,%1,%2,%3}, [%4];" : "=r"(v[0]), "=r"(v[1]), "=r"(v[2]), "=r"(v[3]) : "r"(a) : "memory");
}
__device__ __forceinline__ void lds128_if(uint32_t (&v)[4], uint32_t a, uint32_t p) {
    asm volatile("{.reg .pred q; setp.ne.u32 q, %5, 0; @q ld.shared.v4.u32 {%0,%1,%2,%3}, [%4];}"
                 : "+r"(v[0]), "+r"(v[1]), "+r"(v[2]), "+r"(v[3])
                 : "r"(a), "r"(p)
                 : "memory");
}
__device__ __forceinline__ void lds64(uint32_t& x, uint32_t& y, uint32_t a) {
    asm volatile("ld.shared.v2.u32 {%0,%1}, [%2];" : "=r"(x), "=r"(y) : "r"(a) : "memory");
}
__device__ __forceinline__ void sts128(uint32_t a, uint32_t x, uint32_t y, uint32_t z, uint32_t w) {
    asm volatile("st.shared.v4.u32 [%0], {%1,%2,%3,%4};" ::"r"(a), "r"(x), "r"(y), "r"(z), "r"(w) : "memory");
}
__device__ __forceinline__ void sts64(uint32_t a, uint32_t x, uint32_t y) {
    asm volatile("st.shared.v2.u32 [%0], {%1,%2};" ::"r"(a), "r"(x), "r"(y) : "memory");
}
__device__ __forceinline__ uint32_t pack(float lo, float hi) {
    uint32_t r;
    asm volatile("cvt.rn.bf16x2.f32 %0, %1, %2;" : "=r"(r) : "f"(hi), "f"(lo));
    return r;
}
__device__ __forceinline__ uint32_t hmul2(uint32_t a, uint32_t b) {
    uint32_t r;
    asm volatile("mul.rn.bf16x2 %0, %1, %2;" : "=r"(r) : "r"(a), "r"(b));
    return r;
}
__device__ __forceinline__ uint32_t hfma2(uint32_t a, uint32_t b, uint32_t c) {
    uint32_t r;
    asm volatile("fma.rn.bf16x2 %0, %1, %2, %3;" : "=r"(r) : "r"(a), "r"(b), "r"(c));
    return r;
}
template <int H>
__device__ __forceinline__ uint32_t hfma2_bcast(uint32_t a, uint32_t x, uint32_t c) {
    uint32_t r;
    if (H)
        asm volatile("{.reg .b16 l, h; .reg .b32 s; mov.b32 {l, h}, %2; mov.b32 s, {h, h}; fma.rn.bf16x2 %0, %1, s, %3;}"
                     : "=r"(r)
                     : "r"(a), "r"(x), "r"(c));
    else
        asm volatile("{.reg .b16 l, h; .reg .b32 s; mov.b32 {l, h}, %2; mov.b32 s, {l, l}; fma.rn.bf16x2 %0, %1, s, %3;}"
                     : "=r"(r)
                     : "r"(a), "r"(x), "r"(c));
    return r;
}
__device__ __forceinline__ float ffma(float a, float b, float c) {
    float r;
    asm volatile("fma.rn.f32 %0, %1, %2, %3;" : "=f"(r) : "f"(a), "f"(b), "f"(c));
    return r;
}
__device__ __forceinline__ float tanh_fast(float x) {
    float r;
    asm volatile("tanh.approx.f32 %0, %1;" : "=f"(r) : "f"(x));
    return r;
}
__device__ __forceinline__ float gelu_tanh(float x) {
    float r;
    asm volatile(
        "{.reg .f32 a; mul.f32 a, %1, %1; fma.rn.f32 a, a, 0f3D122279, 0f3F4C422A; mul.f32 a, a, %1; tanh.approx.f32 %0, a;}"
        : "=f"(r)
        : "f"(x));
    return r;
}
__device__ __forceinline__ void mma16816(float (&d)[4], const uint32_t (&a)[4], uint32_t b0, uint32_t b1) {
    asm volatile("mma.sync.aligned.m16n8k16.row.col.f32.bf16.bf16.f32 {%0,%1,%2,%3}, {%4,%5,%6,%7}, {%8,%9}, {%0,%1,%2,%3};"
                 : "+f"(d[0]), "+f"(d[1]), "+f"(d[2]), "+f"(d[3])
                 : "r"(a[0]), "r"(a[1]), "r"(a[2]), "r"(a[3]), "r"(b0), "r"(b1));
}
__device__ __forceinline__ uint32_t clock32() {
    uint32_t c;
    asm volatile("mov.u32 %0, %%clock;" : "=r"(c)::"memory");
    return c;
}
#define WG_FENCE() asm volatile("wgmma.fence.sync.aligned;" ::: "memory")
#define WG_COMMIT() asm volatile("wgmma.commit_group.sync.aligned;" ::: "memory")
#define WG_WAIT0() asm volatile("wgmma.wait_group.sync.aligned 0;" ::: "memory")
#define WG_WAIT1() asm volatile("wgmma.wait_group.sync.aligned 1;" ::: "memory")
#define CP_COMMIT() asm volatile("cp.async.commit_group;" ::: "memory")
#define CP_WAIT(n) asm volatile("cp.async.wait_group %0;" ::"n"(n) : "memory")
#define SCHED_FENCE() asm volatile("pmevent 0;" ::: "memory")
#define PROXY_FENCE() asm volatile("fence.proxy.async.shared::cta;" ::: "memory")
template <int N>
__device__ __forceinline__ void pin(float (&d)[N]) {
#pragma unroll
    for (int i = 0; i < N; i++) asm volatile("" : "+f"(d[i])::"memory");
}
#define TS(k)
#define TS_DUMP(role)

__device__ __forceinline__ void wgmma_ss_n168_acc(float (&d)[84], uint64_t da, uint64_t db) {
    asm volatile(
        "wgmma.mma_async.sync.aligned.m64n168k16.f32.bf16.bf16 "
        "{%0,%1,%2,%3,%4,%5,%6,%7,%8,%9,%10,%11,%12,%13,%14,%15,"
        "%16,%17,%18,%19,%20,%21,%22,%23,%24,%25,%26,%27,%28,%29,%30,%31,"
        "%32,%33,%34,%35,%36,%37,%38,%39,%40,%41,%42,%43,%44,%45,%46,%47,"
        "%48,%49,%50,%51,%52,%53,%54,%55,%56,%57,%58,%59,%60,%61,%62,%63,"
        "%64,%65,%66,%67,%68,%69,%70,%71,%72,%73,%74,%75,%76,%77,%78,%79,"
        "%80,%81,%82,%83}, "
        "%84, %85, 1, 1, 1, 0, 1;"
        : "+f"(d[0]), "+f"(d[1]), "+f"(d[2]), "+f"(d[3]), "+f"(d[4]), "+f"(d[5]), "+f"(d[6]), "+f"(d[7]),
          "+f"(d[8]), "+f"(d[9]), "+f"(d[10]), "+f"(d[11]), "+f"(d[12]), "+f"(d[13]), "+f"(d[14]), "+f"(d[15]),
          "+f"(d[16]), "+f"(d[17]), "+f"(d[18]), "+f"(d[19]), "+f"(d[20]), "+f"(d[21]), "+f"(d[22]), "+f"(d[23]),
          "+f"(d[24]), "+f"(d[25]), "+f"(d[26]), "+f"(d[27]), "+f"(d[28]), "+f"(d[29]), "+f"(d[30]), "+f"(d[31]),
          "+f"(d[32]), "+f"(d[33]), "+f"(d[34]), "+f"(d[35]), "+f"(d[36]), "+f"(d[37]), "+f"(d[38]), "+f"(d[39]),
          "+f"(d[40]), "+f"(d[41]), "+f"(d[42]), "+f"(d[43]), "+f"(d[44]), "+f"(d[45]), "+f"(d[46]), "+f"(d[47]),
          "+f"(d[48]), "+f"(d[49]), "+f"(d[50]), "+f"(d[51]), "+f"(d[52]), "+f"(d[53]), "+f"(d[54]), "+f"(d[55]),
          "+f"(d[56]), "+f"(d[57]), "+f"(d[58]), "+f"(d[59]), "+f"(d[60]), "+f"(d[61]), "+f"(d[62]), "+f"(d[63]),
          "+f"(d[64]), "+f"(d[65]), "+f"(d[66]), "+f"(d[67]), "+f"(d[68]), "+f"(d[69]), "+f"(d[70]), "+f"(d[71]),
          "+f"(d[72]), "+f"(d[73]), "+f"(d[74]), "+f"(d[75]), "+f"(d[76]), "+f"(d[77]), "+f"(d[78]), "+f"(d[79]),
          "+f"(d[80]), "+f"(d[81]), "+f"(d[82]), "+f"(d[83])
        : "l"(da), "l"(db));
}

__device__ __forceinline__ void wgmma_rs_n32_set(float (&d)[16], const uint32_t (&a)[4], uint64_t db) {
    asm volatile(
        "wgmma.mma_async.sync.aligned.m64n32k16.f32.bf16.bf16 "
        "{%0,%1,%2,%3,%4,%5,%6,%7,%8,%9,%10,%11,%12,%13,%14,%15}, "
        "{%16,%17,%18,%19}, %20, 0, 1, 1, 0;"
        : "=f"(d[0]), "=f"(d[1]), "=f"(d[2]), "=f"(d[3]), "=f"(d[4]), "=f"(d[5]), "=f"(d[6]), "=f"(d[7]),
          "=f"(d[8]), "=f"(d[9]), "=f"(d[10]), "=f"(d[11]), "=f"(d[12]), "=f"(d[13]), "=f"(d[14]), "=f"(d[15])
        : "r"(a[0]), "r"(a[1]), "r"(a[2]), "r"(a[3]), "l"(db));
}

__device__ __forceinline__ void wgmma_rs_n32_acc(float (&d)[16], const uint32_t (&a)[4], uint64_t db) {
    asm volatile(
        "wgmma.mma_async.sync.aligned.m64n32k16.f32.bf16.bf16 "
        "{%0,%1,%2,%3,%4,%5,%6,%7,%8,%9,%10,%11,%12,%13,%14,%15}, "
        "{%16,%17,%18,%19}, %20, 1, 1, 1, 0;"
        : "+f"(d[0]), "+f"(d[1]), "+f"(d[2]), "+f"(d[3]), "+f"(d[4]), "+f"(d[5]), "+f"(d[6]), "+f"(d[7]),
          "+f"(d[8]), "+f"(d[9]), "+f"(d[10]), "+f"(d[11]), "+f"(d[12]), "+f"(d[13]), "+f"(d[14]), "+f"(d[15])
        : "r"(a[0]), "r"(a[1]), "r"(a[2]), "r"(a[3]), "l"(db));
}

__device__ __forceinline__ void wgmma_rs_n16_set(float (&d)[8], const uint32_t (&a)[4], uint64_t db) {
    asm volatile(
        "wgmma.mma_async.sync.aligned.m64n16k16.f32.bf16.bf16 "
        "{%0,%1,%2,%3,%4,%5,%6,%7}, "
        "{%8,%9,%10,%11}, %12, 0, 1, 1, 0;"
        : "=f"(d[0]), "=f"(d[1]), "=f"(d[2]), "=f"(d[3]), "=f"(d[4]), "=f"(d[5]), "=f"(d[6]), "=f"(d[7])
        : "r"(a[0]), "r"(a[1]), "r"(a[2]), "r"(a[3]), "l"(db));
}

__device__ __forceinline__ void wgmma_rs_n16_acc(float (&d)[8], const uint32_t (&a)[4], uint64_t db) {
    asm volatile(
        "wgmma.mma_async.sync.aligned.m64n16k16.f32.bf16.bf16 "
        "{%0,%1,%2,%3,%4,%5,%6,%7}, "
        "{%8,%9,%10,%11}, %12, 1, 1, 1, 0;"
        : "+f"(d[0]), "+f"(d[1]), "+f"(d[2]), "+f"(d[3]), "+f"(d[4]), "+f"(d[5]), "+f"(d[6]), "+f"(d[7])
        : "r"(a[0]), "r"(a[1]), "r"(a[2]), "r"(a[3]), "l"(db));
}

__device__ __forceinline__ void wgmma_rs_n32_pred(float (&d)[16], const uint32_t (&a)[4], uint64_t db, uint32_t scale_d) {
    asm volatile(
        "{.reg .pred p; setp.ne.u32 p, %21, 0; wgmma.mma_async.sync.aligned.m64n32k16.f32.bf16.bf16 "
        "{%0,%1,%2,%3,%4,%5,%6,%7,%8,%9,%10,%11,%12,%13,%14,%15}, "
        "{%16,%17,%18,%19}, %20, p, 1, 1, 0;}"
        : "+f"(d[0]), "+f"(d[1]), "+f"(d[2]), "+f"(d[3]), "+f"(d[4]), "+f"(d[5]), "+f"(d[6]), "+f"(d[7]),
          "+f"(d[8]), "+f"(d[9]), "+f"(d[10]), "+f"(d[11]), "+f"(d[12]), "+f"(d[13]), "+f"(d[14]), "+f"(d[15])
        : "r"(a[0]), "r"(a[1]), "r"(a[2]), "r"(a[3]), "l"(db), "r"(scale_d));
}

__device__ __forceinline__ void prep_cta(uint32_t sb, int c, const __nv_bfloat16* __restrict__ wc,
                                         const __nv_bfloat16* __restrict__ se1, const __nv_bfloat16* __restrict__ se2) {
    const int tid = threadIdx.x, lane = tid & 31, warp = tid >> 5;
    constexpr int NROW = 2 * NF * NF;
#pragma unroll
    for (int q = tid; q < NROW * 2; q += 384) cp16(sb + q * 16, wc + (q >> 1) * ND + c * 16 + (q & 1) * 8);
    if (tid == 0) sts128(sb + NROW * 32, 0, 0, 0, 0);
    if (tid < 256) {
        const int l2 = c >> 1, n = ((tid >> 2) & 1) * 8 + (tid >> 5) + (l2 ? (c & 1) * 16 : 0);
        const int k = ((tid >> 1) & 1) * 8 + ((tid >> 3) & 3) * 2 + (tid & 1), mm = k >> 1, u = k & 1;
        const int f = l2 ? fmap(n) : mm < 6 ? 4 * mm + 2 * c + u : (mm == 6 && u == 0) ? 24 + c : -1;
        float v = 0.f;
        if (f >= 0 && (l2 ? k : n) < NR) v = __bfloat162float(l2 ? se2[k * NF + f] : se1[f * NR + n]);
        reinterpret_cast<__nv_bfloat16*>(g_se)[c * 256 + tid] = __float2bfloat16(l2 ? 0.5f * v : v);
    }
    asm volatile("cp.async.wait_all;" ::: "memory");
    __syncthreads();
    const int k = 4 * (lane & 6) + 2 * (lane >> 3) + (lane & 1), i = fmap(k);
    const int g = lane >> 2, t = lane & 3;
#pragma unroll 4
    for (int task = warp; task < 128; task += 12) {
        const int eg = task & 1, n = (task >> 1) & 31, s = task >> 6;
        const int j = fmap(n ^ s);
        const uint32_t a = k < 28 ? sb + ((s * NF + i) * NF + j) * 32 + eg * 16 : sb + NROW * 32;
        uint4 v;
        asm volatile("ldmatrix.sync.aligned.m8n8.x4.trans.shared.b16 {%0,%1,%2,%3}, [%4];"
                     : "=r"(v.x), "=r"(v.y), "=r"(v.z), "=r"(v.w)
                     : "r"(a));
        const int e = eg * 8 + g;
        if (t == 3) {
            const uint32_t mask = eg ? 0xffff0000u : 0xffffu;
            v.x &= mask;
            v.y &= mask;
        }
        const int ch = (t < 2 ? t ^ ((e >> 1) & 1) : t) ^ ((n >> 1) & 3);
        g_wc[(c >> 1) * 8192 + ((g & 1) + 2 * eg + 2 * (g & 6)) * 512 + (c & 1) * 256 + s * 128 + n * 4 + ch] = v;
    }
    __threadfence();
    __syncthreads();
    if (tid == 0) atomicAdd(&g_ready, 1u);
}

#define TWARM 7
#define WPF_STEP 800
#define WDELAY 1600
#define WSTEP 500
#define START_MIN 3300
#define DB0 6
#define PACE1 2100
#define PACE2 2700
#define PF_START 2600
#define PF_PACE 550
#define WPF_AT 3000

__global__ void __cluster_dims__(2, 1, 1) __launch_bounds__(384, 1)
fibinet_kernel(const int* __restrict__ idx, const uint4* __restrict__ table,
               const __nv_bfloat16* __restrict__ se1, const __nv_bfloat16* __restrict__ se2,
               const __nv_bfloat16* __restrict__ wc,
               const unsigned char* __restrict__ w1, const __nv_bfloat16* __restrict__ w2, __nv_bfloat16* __restrict__ out,
               const __grid_constant__ CUtensorMap tm_w1, const __grid_constant__ CUtensorMap tm_bi) {
    extern __shared__ __align__(1024) unsigned char smem[];
    const uint32_t t_start = clock32();
    const int tid = threadIdx.x;
    const uint32_t sb = (uint32_t)__cvta_generic_to_shared(smem);
    if (blockIdx.x < NPREP) {
        prep_cta(sb, blockIdx.x, wc, se1, se2);
        return;
    }
    const int cta = blockIdx.x - NPREP, grp = cta >> 1, rank = cta & 1, lane = tid & 31;
    uint32_t ids[13][4], cid[3][2];
    uint32_t gd0 = 0;
    const uint4* tp = table + (lane & 7);
    auto gather = [&](int i) {
#pragma unroll
        for (int u = 0; u < 4; u++)
            asm volatile("{.reg .u64 a; mad.wide.u32 a, %2, 128, %1; cp.async.cg.shared.global [%0], [a], 16;}" ::"r"(
                             (gd0 ^ ((u & 1) * 64)) + xpair(i) + u * 512),
                         "l"(tp), "r"(ids[i][u])
                         : "memory");
        CP_COMMIT();
    };
    if (tid < 256) {
        const uint32_t w = tid >> 7, row = ((tid >> 5) & 3) * 16 + (lane >> 3);
        const int* ip = idx + ((grp * 64 + row) * NF + 2 * w);
#pragma unroll
        for (int u = 0; u < 4; u++)
            asm volatile("ld.global.nc.L2::128B.v2.u32 {%0,%1}, [%2];" : "=r"(ids[0][u]), "=r"(ids[1][u]) : "l"(ip + 4 * NF * u));
        const int* cp = idx + ((grp * 64 + ((tid & 127) >> 1)) * NF + 2 * w + 4 + 4 * (tid & 1));
#pragma unroll
        for (int k = 0; k < 3; k++)
            asm volatile("ld.global.nc.v2.u32 {%0,%1}, [%2];"
                         : "=r"(cid[k][0]), "=r"(cid[k][1])
                         : "l"(cp + 8 * k - (k == 2 ? 2 * (w & tid) : 0)));
        gd0 = sb + w * XDELTA + row * 128 + (((lane & 7) ^ (lane >> 3) ^ (4 * w)) << 4);
        gather(0);
    } else {
        if (tid == 256) asm volatile("prefetch.tensormap [%0];" ::"l"(&tm_w1));
        if (tid == 288) asm volatile("prefetch.tensormap [%0];" ::"l"(&tm_bi));
    }
    const int warp = __reduce_max_sync(0xffffffffu, tid >> 5);
    const int w = warp >> 2;

    if (w == 2) {
        asm volatile("setmaxnreg.dec.sync.aligned.u32 40;");
        auto load_wc = [&](int gi) {
            if (elect()) {
                const unsigned char* src = reinterpret_cast<const unsigned char*>(g_wc) + rank * 131072;
                mbar_expect(sb + BAR_WC + gi * 8, (wcfirst(gi + 1) - wcfirst(gi)) * 8192);
#pragma unroll
                for (int c = wcfirst(gi); c < wcfirst(gi + 1); c++) bulk(sb + wcslot(c), src + c * 8192, 8192, sb + BAR_WC + gi * 8);
            }
            __syncwarp();
        };
        if (warp == 8) {
            if (elect()) {
                mbar_init(sb + BAR_Z, 1);
                mbar_expect(sb + BAR_Z, 8192);
                tma2d(sb + ZOFF, &tm_bi, sb + BAR_Z, 32 * rank, 0);
            }
#pragma unroll
            for (int f = 0; f < 26; f++) {
                if (f == 2) {
                    if (elect()) {
#pragma unroll
                        for (int k = 2; k < 8; k++) mbar_init(sb + BAR_FULL + k * 8, 1);
                        asm volatile("fence.mbarrier_init.release.cluster;" ::: "memory");
                    }
                    __syncwarp();
                    asm volatile("barrier.cluster.arrive.relaxed.aligned;" ::: "memory");
                    mbar_wait(sb + BAR_Z);
#pragma unroll
                    for (int k = 0; k < 2; k++)
                        sts128(sb + ZOFF + (k * 32 + lane) * 128 + ((4 ^ (lane & 7)) << 4), 0x3c803c80u, 0x3c803c80u, 0x3c803c80u, 0x3c803c80u);
                    PROXY_FENCE();
                    asm volatile("bar.arrive 0, 384;" ::: "memory");
                    TS(31);
                }
                if (f == 5) asm volatile("barrier.cluster.wait.aligned;" ::: "memory");
                if (f >= 5) mbar_wait(sb + bdone(f - 5), bpar(f - 5));
                if (f >= 2 && f < 5)
                    while (clock32() - t_start < WDELAY + (f - 2) * WSTEP) {
                    }
                if (elect()) {
                    if (f < 2) mbar_init(sb + BAR_FULL + f * 8, 1);
                    mbar_expect(sb + bfull(f), 16384);
                    tma2d(sb + slot(2 * wl(f)), &tm_w1, sb + bfull(f), 128 * rank + 64 * (f & 1), fieldof(f) * 64);
                    tma2d(sb + slot(wl(f)), &tm_w1, sb + bfull(f), 128 * rank + 64 - 64 * (f & 1), fieldof(f) * 64);
                }
                TS(f);
            }
            if (elect()) mbar_arrive(sb + BAR_GO);
            TS_DUMP(2);
        } else if (warp == 9) {
            if (elect()) {
#pragma unroll
                for (int k = 0; k < 11; k++) mbar_init(sb + BAR_WC + k * 8, k < 10 ? 1 : 8);
                asm volatile("fence.mbarrier_init.release.cluster;" ::: "memory");
                mbar_expect(sb + BAR_FIN, 512);
            }
            __syncwarp();
            asm volatile("barrier.cluster.arrive.relaxed.aligned;" ::: "memory");
            asm volatile("bar.sync 0, 384;" ::: "memory");
            mbar_wait(sb + bdone(3), bpar(3));
            if (elect()) {
                unsigned v, it = 0;
                do {
                    asm volatile("ld.acquire.gpu.global.u32 %0, [%1];" : "=r"(v) : "l"(&g_ready) : "memory");
                } while (v < NPREP && ++it < 4000000u);
                asm volatile("fence.proxy.async.global;" ::: "memory");
                mbar_expect(sb + BAR_SE, 2048);
                bulk(sb + SEOFF, g_se, 2048, sb + BAR_SE);
                if (atomicAdd(&g_seen, 1u) == NMAIN - 1) {
                    g_seen = 0;
                    g_ready = 0;
                }
            }
            __syncwarp();
            TS(0);
            mbar_wait(sb + BAR_GO);
#pragma unroll
            for (int gi = 0; gi < 3; gi++) {
                mbar_wait(sb + bdone(21 + gi), bpar(21 + gi));
                load_wc(gi);
                TS(1 + gi);
            }
        } else if (warp == 10) {
            if (elect()) {
#pragma unroll
                for (int k = 0; k < 8; k++) mbar_init(sb + BAR_DONE + k * 8, 4);
                asm volatile("fence.mbarrier_init.release.cluster;" ::: "memory");
            }
            __syncwarp();
            asm volatile("barrier.cluster.arrive.relaxed.aligned;" ::: "memory");
            asm volatile("bar.arrive 0, 384;" ::: "memory");
#pragma unroll 1
            for (int k = 0; k < 7; k++) {
                while (clock32() - t_start < (uint32_t)(WPF_AT + k * WPF_STEP)) __nanosleep(20);
                if (lane < 6)
                    asm volatile("prefetch.global.L2 [%0];" ::"l"(w1 + (5 + k * 3 + (lane >> 1)) * 32768 + cta * 256 + (lane & 1) * 128));
            }
        } else {
            asm volatile("barrier.cluster.arrive.relaxed.aligned;" ::: "memory");
            asm volatile("bar.sync 0, 384;" ::: "memory");
            const uint2 v = __ldg(reinterpret_cast<const uint2*>(w2 + 128 * rank) + lane);
#pragma unroll
            for (int k = 0; k < 2; k++) {
                const uint32_t x = k ? v.y : v.x;
                sts64(sb + w2chunk((lane >> 2) * 4 + 2 * (lane & 1) + k) + (lane & 2) * 4,
                      __float_as_uint(0.5f * __uint_as_float(x << 16)), __float_as_uint(0.5f * __uint_as_float(x & 0xffff0000u)));
            }
            __syncwarp();
            if (lane == 0) mbar_arrive(sb + BAR_W2);
        }
        if (warp != 8) asm volatile("barrier.cluster.wait.aligned;" ::: "memory");
        {
            uint32_t bw[2][4], z0[4], z1[4];
            mbar_wait(sb + BAR_SE);
            lds128(bw[0], sb + SEOFF + lane * 16);
            lds128(bw[1], sb + SEOFF + 512 + lane * 16);
            asm volatile("bar.sync 2, 384;" ::: "memory");
            lds128(z0, sb + ZQOFF + (tid & 127) * 16);
            lds128(z1, sb + ZQOFF + 2048 + (tid & 127) * 16);
            TS(8);
            float s[2][4] = {};
#pragma unroll
            for (int n = 0; n < 2; n++) {
                mma16816(s[n], z0, bw[0][2 * n], bw[0][2 * n + 1]);
                mma16816(s[n], z1, bw[1][2 * n], bw[1][2 * n + 1]);
            }
            lds128(bw[0], sb + SEOFF + 1024 + lane * 16);
            lds128(bw[1], sb + SEOFF + 1536 + lane * 16);
            float th[8];
#pragma unroll
            for (int k = 0; k < 8; k++) th[k] = gelu_tanh(s[k >> 2][k & 3]);
            SCHED_FENCE();
            TS(9);
            uint32_t gq[4];
#pragma unroll
            for (int k = 0; k < 4; k++)
                gq[k] = pack(s[k >> 1][2 * (k & 1)] * ffma(th[2 * k], 0.5f, 0.5f), s[k >> 1][2 * (k & 1) + 1] * ffma(th[2 * k + 1], 0.5f, 0.5f));
            float a[4][4] = {};
#pragma unroll
            for (int n = 0; n < 4; n++) mma16816(a[n], gq, bw[n >> 1][2 * (n & 1)], bw[n >> 1][2 * (n & 1) + 1]);
#pragma unroll
            for (int k = 0; k < 16; k++)
                if (k < 13 || k == 14) a[k >> 2][k & 3] = tanh_fast(a[k >> 2][k & 3]);
            SCHED_FENCE();
            TS(10);
            uint32_t ap[8];
#pragma unroll
            for (int k = 0; k < 8; k++)
                ap[k] = pack(ffma(a[k >> 1][2 * (k & 1)], 0.5f, 0.5f), ffma(a[k >> 1][2 * (k & 1) + (k < 6)], 0.5f, 0.5f));
            sts128(sb + GOFF + (tid & 127) * 16, ap[0], ap[1], ap[2], ap[3]);
            sts128(sb + GOFF + 2048 + (tid & 127) * 16, ap[4], ap[5], ap[6], ap[7]);
            asm volatile("bar.arrive 3, 384;" ::: "memory");
            TS(11);
        }
        if (warp == 9) {
            load_wc(3);
            load_wc(4);
            mbar_wait(sb + BAR_TD);
            load_wc(5);
            if (lane < 16) TS_DUMP(3);
        } else if (warp == 10) {
            __nv_bfloat16* dst = out + cta * 32 + lane;
            asm volatile("" : "+l"(dst));
            asm volatile("bar.sync 4, 64;" ::: "memory");
            mbar_wait(sb + BAR_FIN);
            uint32_t p[4];
            lds128(p, sb + PARTOFF + lane * 16);
            *dst = __float2bfloat16((__uint_as_float(p[0]) + __uint_as_float(p[1])) + (__uint_as_float(p[2]) + __uint_as_float(p[3])));
        }
    } else {
        asm volatile("setmaxnreg.inc.sync.aligned.u32 232;");
        asm volatile("barrier.cluster.arrive.relaxed.aligned;" ::: "memory");
        const int g = lane >> 2, t = lane & 3, wq = warp & 3, t128 = tid & 127;
        gd0 = opaque(gd0);
        TS(28);
        float acc[84];
#pragma unroll
        for (int k = 0; k < 84; k++) asm volatile("mov.b32 %0, 0;" : "=f"(acc[k]));
        uint32_t e0[9], e1[9], e2[9];
        uint32_t X[13][2][4];
        uint32_t zq[4] = {0, 0, 0, 0};
        const uint64_t dA = mkdesc(sb + w * XDELTA, 16, 1024, 1);
        uint32_t dBlo = (uint32_t)mkdesc(sb + ZOFF, 0, 0, 0);
        const uint32_t xl0 = opaque(sb + (t & 1) * XDELTA + (16 * wq + g) * 128 + (((4 * rank + 2 * w) ^ (4 * (t & 1)) ^ g) << 4));
        const uint32_t hi_half = t >> 1;
        const uint32_t sa0 = opaque(sb + AOFF + t * 4096 + (t >> 1) * 16 + (wq * 32 + g * 4 + w) * 16);
        const uint32_t sa1 = opaque(((g & 2) << 4) | ((t & 1) << 3));
        const uint32_t zero = blockIdx.y;
        auto expand = [&](int k0, int k1) {
#pragma unroll
            for (int k = k0; k < k1; k++)
#pragma unroll
                for (int u = 0; u < 4; u++)
                    asm volatile("shfl.sync.idx.b32 %0, %1, %2, 31, 0xffffffff;"
                                 : "=r"(ids[k][u])
                                 : "r"(k < 12 ? cid[(k - 2) >> 2][k & 1] : w ? cid[2][1] : cid[2][0]),
                                   "r"(2 * (lane >> 3) + 8 * u + (((k - 2) >> 1) & 1)));
        };
        auto twarm = [&]() {
            float s1[8];
            WG_FENCE();
            wgmma_rs_n16_set(s1, zq, mkdesc(sb + AOFF, 16, 512, 2));
            WG_COMMIT();
            WG_WAIT0();
            pin(s1);
            asm volatile("{.reg .pred p; setp.ne.u32 p, %1, 0; @p st.shared.f32 [%1], %0;}" ::"f"(s1[0]), "r"(zero));
        };
        expand(2, 8);
        if (TWARM & 1) twarm();
        TS(26);
        while (clock32() - t_start < PACE1) {
        }
        gather(1);
        expand(8, 13);
        if (TWARM & 2) twarm();
        TS(30);
        while (clock32() - t_start < PACE2) {
        }
        gather(2);
        if (TWARM & 4) twarm();
        asm volatile("bar.sync 0, 384;" ::: "memory");
        auto lift = [&](int i) {
            const int m = 2 * (i >> 2) + (i & 1);
#pragma unroll
            for (int r = 0; r < (i < 12 ? 2 : 1); r++)
#pragma unroll
                for (int cc = 0; cc < 2; cc++) {
                    const uint32_t a = (xl0 ^ (cc * 16)) + xpair(i) + (i < 12 ? r : hi_half) * 1024;
                    if (i & 2) lds128_if(X[2 * m + r][cc], a, hi_half);
                    else lds128(X[2 * m + r][cc], a);
                }
        };
        auto store_pair = [&](int m, int half, const uint32_t (&ea)[9]) {
            uint32_t a;
            if (m < 4) a = sa0 + (sa1 ^ (((m & 1) << 5) | ((m >> 1) << 3)));
            else a = sb + BOFF + t * 2048 + (wq * 32 + g * 4 + ((2 * (m & 1) + w) ^ t)) * 8;
#pragma unroll
            for (int n = half; n < 4; n += 2)
#pragma unroll
                for (int u = 0; u < 2; u++)
                    sts64(a + (m < 4 ? (8 * n + u) * 2048 + n * 32 : (8 * n + u) * 1024),
                          __byte_perm(ea[2 * n], e1[2 * n], u ? 0x7632 : 0x5410),
                          __byte_perm(ea[2 * n + 1], e1[2 * n + 1], u ? 0x7632 : 0x5410));
        };
        auto z_pair = [&](int m, uint32_t a, uint32_t b) {
            asm volatile("{.reg .pred p; setp.eq.u32 p, %4, %5; @p prmt.b32 %0, %2, %3, 0x5410; @p prmt.b32 %1, %2, %3, 0x7632;}"
                         : "+r"(zq[2 * (m >> 2)]), "+r"(zq[2 * (m >> 2) + 1])
                         : "r"(a), "r"(b), "r"(t), "r"(m & 3));
        };

        TS(29);
        mbar_wait(sb + BAR_FULL + w * 8);
        CP_WAIT(2);
        while (clock32() - t_start < START_MIN) {
        }
        if (w == 1) {
            asm volatile("bar.arrive 6, 256;" ::: "memory");
            asm volatile("bar.sync 5, 256;" ::: "memory");
        }
#pragma unroll
        for (int i = 0; i < 13; i++) {
            const uint64_t da = dA + (xpair(i) >> 4) + ((uint64_t)i << 16);
            dBlo += (uint32_t)(w ? wl(2 * i + 1) - (i ? wl(2 * i - 1) : 0) : wl(2 * i) - (i ? wl(2 * i - 2) : 0)) *
                    (uint32_t)((SLOT << 12) - (SLOT >> 3));
            const uint64_t db = mkdesc(0, 0, 1024, 1) | dBlo;
            TS(i);
            WG_FENCE();
            wgmma_ss_n168_acc(acc, da, db + w * 256);
            wgmma_ss_n168_acc(acc, da + 2, db + w * 256 + 128);
            wgmma_ss_n168_acc(acc, da + 4, db + (w ^ 1) * 256);
            wgmma_ss_n168_acc(acc, da + 6, db + (w ^ 1) * 256 + 128);
            WG_COMMIT();
            if (i == 0) {
                if (w == 0) {
                    asm volatile("bar.arrive 5, 256;" ::: "memory");
                    asm volatile("bar.sync 6, 256;" ::: "memory");
                }
            } else {
                mbar_wait(sb + bdone(2 * i - 2) + (w ^ 1) * 8, bpar(2 * i - 2));
            }
            if (i < 10) gather(i + 3);
            if (i == 1) asm volatile("barrier.cluster.wait.aligned;" ::: "memory");
            if (i == 6) mbar_wait(sb + BAR_W2);
            lift(i);
            if (i == 10 || i == 11) mbar_wait(sb + bdone(2 * i - 2) + w * 8, bpar(2 * i - 2));
            if (i >= 2 && !(i & 1)) {
                z_pair((i - 2) >> 1, e0[8], e1[8]);
                store_pair((i - 2) >> 1, 0, e0);
#pragma unroll
                for (int k = 0; k < 8; k++) e2[k] = e0[k];
            } else if (i >= 3) {
                store_pair((i - 3) >> 1, 1, e2);
            }
            const uint32_t rdy = i < 12 ? mbar_test(sb + bfull(2 * i + 2) + w * 8, bpar(2 * i + 2)) : 0;
            WG_WAIT0();
            pin(acc);
            if (i == 12) TS(13);
            if (i == 0) TS(27);
            if (i < 10) CP_WAIT(2);
            else if (i == 10) CP_WAIT(1);
            else if (i == 11) CP_WAIT(0);
            if (i < 12 && lane == 0) mbar_arrive(sb + bdone(2 * i) + w * 8);
#pragma unroll
            for (int k = 0; k < 9; k++) {
                const int k0 = 64 + 2 * (k & 5) + ((k >> 1) & 1);
                const uint32_t v = k == 8 ? pack(acc[80], acc[82]) : i < 12 ? pack(acc[64 + 2 * k], acc[65 + 2 * k]) : pack(acc[k0], acc[k0 + 4]);
                if (i & 1) e1[k] = v;
                else e0[k] = v;
            }
            if (i < 12) {
#pragma unroll
                for (int k = 64; k < 83; k++)
                    if (k != 81) asm volatile("mov.b32 %0, %1;" : "+f"(acc[k]) : "r"(zero));
                mbar_wait_unless(rdy, sb + bfull(2 * i + 2) + w * 8, bpar(2 * i + 2));
            } else {
                z_pair(6, e0[8], 0);
                sts128(sb + ZQOFF + w * 2048 + t128 * 16, zq[0], zq[1], zq[2], zq[3]);
                asm volatile("bar.arrive 2, 384;" ::: "memory");
            }
        }
        TS(14);

        uint32_t ai[8];
        float sum0 = 0.f, sum1 = 0.f;
        float th[32];
        uint32_t hw[4][4];
        auto deep_issue = [&](int k2) {
            lds128(hw[k2], ((sb + w2chunk(w * 16 + t)) ^ ((k2 & 1) * 64)) + k2 * 512);
#pragma unroll
            for (int k = 8 * k2; k < 8 * k2 + 8; k++) th[k] = gelu_tanh(acc[k]);
        };
        auto deep_use = [&](int k2) {
#pragma unroll
            for (int k = 8 * k2; k < 8 * k2 + 8; k++) {
                const float h = __uint_as_float(hw[k2][((k >> 1) & 2) + (k & 1)]);
                const float y = ffma(th[k], h, h);
                if (k & 2) sum1 = ffma(acc[k], y, sum1);
                else sum0 = ffma(acc[k], y, sum0);
            }
        };
        auto deep_send = [&](int k0, int k1) {
#pragma unroll
            for (int k = k0; k < k1; k++)
                sts128(sb + EXOFF + w * SLOT + t128 * 16 + k * 2048, pack(acc[32 + 8 * k], acc[33 + 8 * k]),
                       pack(acc[34 + 8 * k], acc[35 + 8 * k]), pack(acc[36 + 8 * k], acc[37 + 8 * k]), pack(acc[38 + 8 * k], acc[39 + 8 * k]));
        };
        uint32_t o[4][4];
        auto deep_recv = [&](int k0, int k1) {
#pragma unroll
            for (int k = k0; k < k1; k++) lds128(o[k], sb + EXOFF + (w ^ 1) * SLOT + t128 * 16 + k * 2048);
        };
        auto deep_add = [&](int k0, int k1) {
            const uint32_t eye = (g >> 1) == t ? ((g & 1) ? 0x3f800000u : 0x3f80u) : 0u;
#pragma unroll
            for (int k = 2 * k0; k < 2 * k1; k++)
                asm volatile("mma.sync.aligned.m16n8k8.row.col.f32.bf16.bf16.f32 {%0,%1,%2,%3}, {%4,%5}, {%6}, {%0,%1,%2,%3};"
                             : "+f"(acc[4 * k]), "+f"(acc[4 * k + 1]), "+f"(acc[4 * k + 2]), "+f"(acc[4 * k + 3])
                             : "r"(o[k >> 1][2 * (k & 1)]), "r"(o[k >> 1][2 * (k & 1) + 1]), "r"(eye));
        };
        auto store_last = [&]() {
#pragma unroll
            for (int n = 0; n < 4; n++) sts64(sb + COFF + w * 4096 + n * 1024 + (t128 ^ w) * 8, e0[2 * n], e0[2 * n + 1]);
            store_pair(5, 1, e2);
        };
        const uint32_t la = sb + AOFF + w * (16 * 2048 + 64) + (wq * 32 + g * 4 + (t ^ (g & 2))) * 16;
        const uint32_t lb = sb + BOFF + w * (16 * 1024) + t128 * 8;
        const uint32_t lc0 = sb + COFF + (t & 1) * (4096 + 8) + w * 2048 + (wq * 8 + g) * 32, lc1 = lc0 ^ 8;
        uint32_t Ap[2][2][4];
        auto load_a = [&](int s) {
            const int e = estep(s);
            lds128(Ap[s & 1][0], la + e * 2048 + (e >> 2) * 16);
            lds64(Ap[s & 1][1][0], Ap[s & 1][1][1], (lb ^ ((e & 6) * 4)) + e * 1024);
            if (!(s & 2)) lds64(Ap[s & 1][1][2], Ap[s & 1][1][3], ((e & 2) ? lc1 : lc0) + (e & 1) * 1024 + (e & 4) * 4);
        };
        {
            uint32_t v[2][4];
            deep_send(0, 2);
            asm volatile("bar.sync 1, 256;" ::: "memory");
            deep_recv(0, 2);
            deep_send(2, 4);
            TS(15);
            deep_add(0, 2);
            deep_issue(0);
            asm volatile("bar.sync 1, 256;" ::: "memory");
            deep_recv(2, 4);
            SCHED_FENCE();
            deep_add(2, 4);
            TS(16);
            deep_issue(1);
            deep_use(0);
            store_last();
            SCHED_FENCE();
            TS(17);
            deep_issue(2);
            deep_use(1);
            mbar_wait(sb + BAR_WC);
            deep_use(2);
            TS(18);
            asm volatile("bar.sync 3, 384;" ::: "memory");
            lds128(v[0], sb + GOFF + t128 * 16);
            lds128(v[1], sb + GOFF + 2048 + t128 * 16);
            load_a(0);
            load_a(1);
            deep_issue(3);
#pragma unroll
            for (int k = 0; k < 8; k++) ai[k] = v[k >> 2][k & 3];
        }
        TS(19);

        uint32_t fin_a, dsum[2];
        {
            uint64_t dW[4];
#pragma unroll
            for (int k = 0; k < 4; k++) dW[k] = mkdesc(sb + w * 4096, 16, 512, 2) + (wcslot(0) >> 4) + (k >> 1) * 128 + (k & 1) * 2;
            uint32_t Aq[2][2][4], pq[13], gate[13];
            float S[2][2][16];
            auto scale_a = [&](int s) {
#pragma unroll
                for (int k = 0; k < ((s & 2) ? 6 : 8); k++)
                    Aq[s & 1][k >> 2][k & 3] = hmul2(Ap[s & 1][k >> 2][k & 3], ai[k < 4 ? k ^ (estep(s) & 2) : k]);
            };
            auto sbuf = [](int s) { return s <= DB0 ? 0 : (s - DB0) & 1; };
            auto issue = [&](int s) {
                const bool first = s == 0 || s == DB0 + 1;
                WG_FENCE();
                if (first) wgmma_rs_n32_set(S[sbuf(s)][0], Ap[s & 1][0], dW[0]);
                else wgmma_rs_n32_pred(S[sbuf(s)][0], Ap[s & 1][0], dW[0], zero);
                wgmma_rs_n32_acc(S[sbuf(s)][0], Ap[s & 1][1], dW[1]);
                if (first) wgmma_rs_n32_set(S[sbuf(s)][1], Aq[s & 1][0], dW[2]);
                else wgmma_rs_n32_pred(S[sbuf(s)][1], Aq[s & 1][0], dW[2], zero);
                wgmma_rs_n32_acc(S[sbuf(s)][1], Aq[s & 1][1], dW[3]);
                WG_COMMIT();
                if (s < 15) {
#pragma unroll
                    for (int k = 0; k < 4; k++)
                        asm volatile("add.s64 %0, %0, %1;" : "+l"(dW[k]) : "l"((int64_t)((wcslot(s + 1) - wcslot(s)) / 16)));
                }
            };
            scale_a(0);
            issue(0);
            SCHED_FENCE();
            deep_use(3);
            scale_a(1);
            mbar_wait(sb + BAR_WC + 8);
#pragma unroll
            for (int e = 0; e < 16; e++) {
                if (e >= DB0 && e < 15) {
                    issue(e + 1);
                    WG_WAIT1();
                } else {
                    WG_WAIT0();
                }
                pin(S[sbuf(e)][0]);
                pin(S[sbuf(e)][1]);
                if (e == 0 && lane == 0) mbar_arrive(sb + BAR_TD);
                if (e == 0) TS(20);
                if (e + 2 < 16) load_a(e + 2);
                uint32_t v[13];
                auto accum = [&](int q) {
                    const uint32_t x = X[q][(e >> 1) & 1][e >> 2];
                    pq[q] = (e & 1) ? hfma2_bcast<1>(v[q], x, pq[q]) : hfma2_bcast<0>(v[q], x, e ? pq[q] : 0u);
                };
#pragma unroll
                for (int q = 0; q < 13; q++) {
                    const int ix = 4 * (q >> 2) + 2 * (q & 1) + ((q >> 1) & 1);
                    v[q] = pack(S[sbuf(e)][0][ix], S[sbuf(e)][1][ix ^ 1]);
                    if (q == 12)
                        asm volatile("{.reg .pred p; setp.ne.u32 p, %3, 0; @p cvt.rn.bf16x2.f32 %0, %2, %1;}"
                                     : "+r"(v[q])
                                     : "f"(S[sbuf(e)][0][14]), "f"(S[sbuf(e)][1][15]), "r"(hi_half));
                    if (e >= DB0 || q < 7) accum(q);
                }
                if (e < DB0) {
                    issue(e + 1);
                    SCHED_FENCE();
#pragma unroll
                    for (int q = 7; q < 13; q++) accum(q);
                }
                if (e == 3) {
                    const float h0 = __uint_as_float(__float_as_uint(sum0) & 0xffff0000u);
                    const float h1 = __uint_as_float(__float_as_uint(sum1) & 0xffff0000u);
                    dsum[0] = pack(sum0 - h0, h0);
                    dsum[1] = pack(sum1 - h1, h1);
                }
                if (e == 13) {
                    asm("mapa.shared::cluster.u32 %0, %1, %2;"
                        : "=r"(fin_a)
                        : "r"(sb + PARTOFF + (((wq & 1) * 16 + g) * 4 + 2 * rank + w) * 4), "r"(wq >> 1));
                    fin_a = opaque(fin_a);
                }
                if (e == 14) {
                    if (warp == 0) asm volatile("bar.arrive 4, 64;" ::: "memory");
#pragma unroll
                    for (int q = 0; q < 13; q++)
                        asm volatile("prmt.b32 %0, %1, 0x3f80, %2;"
                                     : "=r"(gate[q])
                                     : "r"(q < 12 ? ai[2 * (q >> 2) + (q & 1)] : hi_half ? ai[7] : ai[6]), "r"((q & 2) ? 0x3254 : 0x1054));
                }
                if (e + 2 < 16) scale_a(e + 2);
                if (e == 0 || e == 3 || e == 6 || e == 9) mbar_wait(sb + BAR_WC + (e / 3 + 2) * 8);
                else if (e < 15) SCHED_FENCE();
                if (e == 7) TS(21);
            }
            float r0[4] = {0.f, 0.f, 0.f, 0.f}, r1[4] = {0.f, 0.f, 0.f, 0.f}, r2[4] = {0.f, 0.f, 0.f, 0.f};
#pragma unroll
            for (int c = 0; c < 3; c++) {
                const uint32_t a[4] = {pq[4 * c], pq[4 * c + 1], pq[4 * c + 2], pq[4 * c + 3]};
                mma16816(r0, a, gate[4 * c], gate[4 * c + 2]);
                mma16816(r1, a, gate[4 * c + 1], gate[4 * c + 3]);
            }
            const uint32_t rest[4] = {dsum[0], dsum[1], hi_half ? 0u : pq[12], hi_half ? pq[12] : 0u};
            mma16816(r2, rest, 0x3f803f80u, gate[12]);
            sum0 = (g & 1) ? r0[1] + r2[1] : r0[0] + r2[0];
            sum1 = (g & 1) ? r1[3] + r2[3] : r1[2] + r2[2];
        }
        TS(22);
        {
            asm volatile(
                "{.reg .pred p; setp.eq.u32 p, %4, %5;\n"
                "@p st.async.shared::cluster.mbarrier::complete_tx::bytes.f32 [%0], %1, [%3];\n"
                "@p st.async.shared::cluster.mbarrier::complete_tx::bytes.f32 [%0 + 128], %2, [%3];}" ::"r"(fin_a),
                "f"(sum0), "f"(sum1), "r"((fin_a & ~0x3ffu) + (BAR_FIN & 0x3ff)), "r"(t), "r"(g >> 1)
                : "memory");
            if (wq == 0) TS_DUMP(w);
        }
    }
}

typedef CUresult (*EncodeFn)(CUtensorMap*, CUtensorMapDataType, cuuint32_t, void*, const cuuint64_t*, const cuuint64_t*,
                             const cuuint32_t*, const cuuint32_t*, CUtensorMapInterleave, CUtensorMapSwizzle,
                             CUtensorMapL2promotion, CUtensorMapFloatOOBfill);

}

extern "C" void kernel_launch(void* const* d_in, const int* in_sizes, int n_in, void* d_out, int out_size) {
    static EncodeFn encode = nullptr;
    if (!encode) {
        void* fn = nullptr;
        cudaDriverEntryPointQueryResult qr;
        cudaGetDriverEntryPoint("cuTensorMapEncodeTiled", &fn, cudaEnableDefault, &qr);
        encode = (EncodeFn)fn;
        cudaFuncSetAttribute(fibinet_kernel, cudaFuncAttributeMaxDynamicSharedMemorySize, SMEM_BYTES);
    }
    CUtensorMap tm;
    const cuuint64_t gd[2] = {NH, NF * ND};
    const cuuint64_t gs[1] = {NH * 2};
    const cuuint32_t bd[2] = {64, 64}, es[2] = {1, 1};
    encode(&tm, CU_TENSOR_MAP_DATA_TYPE_BFLOAT16, 2, d_in[6], gd, gs, bd, es, CU_TENSOR_MAP_INTERLEAVE_NONE,
           CU_TENSOR_MAP_SWIZZLE_128B, CU_TENSOR_MAP_L2_PROMOTION_L2_256B, CU_TENSOR_MAP_FLOAT_OOB_FILL_NONE);
    CUtensorMap tb;
    const cuuint64_t gd2[2] = {ND, ND};
    const cuuint64_t gs2[1] = {ND * 2};
    encode(&tb, CU_TENSOR_MAP_DATA_TYPE_BFLOAT16, 2, d_in[4], gd2, gs2, bd, es, CU_TENSOR_MAP_INTERLEAVE_NONE,
           CU_TENSOR_MAP_SWIZZLE_128B, CU_TENSOR_MAP_L2_PROMOTION_L2_256B, CU_TENSOR_MAP_FLOAT_OOB_FILL_NONE);
    fibinet_kernel<<<NPREP + NMAIN, 384, SMEM_BYTES>>>(
        (const int*)d_in[0], (const uint4*)d_in[1], (const __nv_bfloat16*)d_in[2], (const __nv_bfloat16*)d_in[3],
        (const __nv_bfloat16*)d_in[5], (const unsigned char*)d_in[6], (const __nv_bfloat16*)d_in[7], (__nv_bfloat16*)d_out, tm, tb);
}
```

```cpp
#include <cuda_runtime.h>
#include <cuda_bf16.h>
#include <cuda.h>
#include <stdint.h>

namespace {

constexpr int NB = 4096, NF = 26, ND = 64, NH = 256, NR = 13;
constexpr int NPREP = 4;
constexpr int NMAIN = 128;

constexpr int SLOT = 8192;
constexpr int ZOFF = 15 * SLOT;
__host__ __device__ constexpr int slot(int s) { return ZOFF - s * SLOT; }
constexpr int BOFF = ZOFF + SLOT;
constexpr int AOFF = BOFF + 32768;
constexpr int COFF = slot(12);
constexpr int MOFF = AOFF + 65536 + 128;
constexpr int BAR_FULL = MOFF, BAR_DONE = MOFF + 64, BAR_WC = MOFF + 128, BAR_FIN = MOFF + 176,
              BAR_GO = MOFF + 184, BAR_SE = MOFF + 192, BAR_W2 = MOFF + 200, BAR_TD = MOFF + 208, BAR_Z = MOFF + 216;
__host__ __device__ constexpr int bfull(int f) { return BAR_FULL + (f & 7) * 8; }
__host__ __device__ constexpr int bdone(int f) { return BAR_DONE + (f & 7) * 8; }
__host__ __device__ constexpr int bpar(int f) { return (f >> 3) & 1; }
constexpr int PARTOFF = MOFF + 256, SEOFF = MOFF + 768;
constexpr int SMEM_BYTES = MOFF + 2944;
static_assert((BAR_FIN >> 10) == (PARTOFF >> 10) && (BAR_FIN >> 10) == ((PARTOFF + 511) >> 10), "same 1 KB block");
constexpr int XDELTA = 2 * SLOT;
__host__ __device__ constexpr int xpair(int i) {
    return (i & 3) == 0 ? slot(11) : (i & 3) == 1 ? BOFF : (i & 3) == 2 ? BOFF + SLOT : slot(15);
}
__host__ __device__ constexpr int wl(int f) { return f % 5 == 0 ? 1 : f % 5 == 4 ? 7 : f % 5 + 2; }
__host__ __device__ constexpr int wcslot(int c) {
    return c == 0 ? slot(3) : c == 1 ? slot(8) : c == 2 ? slot(10) : c == 3 ? slot(15) : c == 4 ? slot(13)
         : c == 5 ? slot(11) : c == 6 ? slot(9) : c == 7 ? slot(14) : c == 8 ? slot(7) : c == 9 ? slot(2)
         : c == 10 ? slot(1) : c == 11 ? slot(4) : c == 12 ? slot(5) : c == 13 ? slot(6) : c == 14 ? ZOFF : slot(3);
}
__host__ __device__ constexpr int wcfirst(int gi) { return gi < 3 ? gi : gi == 3 ? 5 : gi == 4 ? 8 : gi == 5 ? 11 : 16; }
constexpr int EXOFF = slot(5);
constexpr int ZQOFF = slot(6);
constexpr int GOFF = ZQOFF + 4096;
__host__ __device__ constexpr int w2chunk(int c) { return ZOFF + c * 128 + ((5 ^ (c & 7)) << 4); }

__device__ uint4 g_wc[2 * 16 * 8192 / 16];
__device__ uint4 g_se[2048 / 16];
__device__ unsigned g_ready;
__device__ unsigned g_seen;

__host__ __device__ constexpr int fieldof(int f) { return f < 24 ? 4 * (f >> 2) + 2 * (f & 1) + ((f >> 1) & 1) : f; }
__device__ __forceinline__ int fmap(int n) { return n < 24 ? n : 24 + ((n >> 1) & 1); }
__host__ __device__ constexpr int estep(int s) { return (s & 1) + 2 * (s >> 2) + 4 * (s & 2); }

__device__ __forceinline__ uint64_t mkdesc(uint32_t addr, uint32_t lbo, uint32_t sbo, int sw) {
    return (uint64_t)((addr & 0x3ffff) >> 4) | ((uint64_t)(lbo >> 4) << 16) | ((uint64_t)(sbo >> 4) << 32) |
           ((uint64_t)sw << 62);
}
__device__ __forceinline__ void mbar_init(uint32_t b, uint32_t n) {
    asm volatile("mbarrier.init.shared.b64 [%0], %1;" ::"r"(b), "r"(n) : "memory");
}
__device__ __forceinline__ void mbar_wait(uint32_t b, uint32_t par = 0) {
    asm volatile(
        "{\n.reg .pred p, q;\n.reg .u32 n;\n"
        "mbarrier.try_wait.parity.shared.b64 p, [%0], %1;\n@p bra.uni WD%=;\nmov.u32 n, 0;\n"
        "WL%=:\nmbarrier.try_wait.parity.shared.b64 p, [%0], %1;\n@p bra.uni WD%=;\n"
        "add.u32 n, n, 1;\nsetp.lt.u32 q, n, 4000000;\n@q bra.uni WL%=;\nWD%=:\n}\n" ::"r"(b), "r"(par)
        : "memory");
}
__device__ __forceinline__ uint32_t mbar_test(uint32_t b, uint32_t par) {
    uint32_t ok;
    asm volatile("{.reg .pred p; mbarrier.test_wait.parity.shared.b64 p, [%1], %2; selp.u32 %0, 1, 0, p;}"
                 : "=r"(ok)
                 : "r"(b), "r"(par)
                 : "memory");
    return ok;
}
__device__ __forceinline__ void mbar_wait_unless(uint32_t ok, uint32_t b, uint32_t par) {
    asm volatile(
        "{\n.reg .pred p, q;\n.reg .u32 n;\n"
        "setp.ne.u32 p, %1, 0;\n@p bra.uni WD%=;\nmov.u32 n, 0;\n"
        "WL%=:\nmbarrier.try_wait.parity.shared.b64 p, [%0], %2;\n@p bra.uni WD%=;\n"
        "add.u32 n, n, 1;\nsetp.lt.u32 q, n, 4000000;\n@q bra.uni WL%=;\nWD%=:\n}\n" ::"r"(b), "r"(ok), "r"(par)
        : "memory");
}
__device__ __forceinline__ void mbar_arrive(uint32_t b) {
    asm volatile("mbarrier.arrive.shared.b64 _, [%0];" ::"r"(b) : "memory");
}
__device__ __forceinline__ void mbar_expect(uint32_t b, uint32_t bytes) {
    asm volatile("mbarrier.arrive.expect_tx.shared.b64 _, [%0], %1;" ::"r"(b), "r"(bytes) : "memory");
}
__device__ __forceinline__ uint32_t opaque(uint32_t v) { return __shfl_sync(0xffffffffu, v, threadIdx.x); }
__device__ __forceinline__ bool elect() {
    uint32_t p;
    asm volatile("{.reg .pred q; elect.sync _|q, 0xffffffff; selp.u32 %0, 1, 0, q;}" : "=r"(p));
    return p;
}
__device__ __forceinline__ void tma2d(uint32_t dst, const CUtensorMap* m, uint32_t bar, int x, int y) {
    asm volatile(
        "cp.async.bulk.tensor.2d.shared::cluster.global.mbarrier::complete_tx::bytes [%0], [%1, {%3, %4}], [%2];" ::"r"(dst),
        "l"(m), "r"(bar), "r"(x), "r"(y)
        : "memory");
}
__device__ __forceinline__ void bulk(uint32_t dst, const void* src, uint32_t bytes, uint32_t bar) {
    asm volatile("cp.async.bulk.shared::cluster.global.mbarrier::complete_tx::bytes [%0], [%1], %2, [%3];" ::"r"(dst),
                 "l"(src), "r"(bytes), "r"(bar)
                 : "memory");
}
__device__ __forceinline__ void cp16(uint32_t dst, const void* src) {
    asm volatile("cp.async.cg.shared.global [%0], [%1], 16;" ::"r"(dst), "l"(src) : "memory");
}
__device__ __forceinline__ void lds128(uint32_t (&v)[4], uint32_t a) {
    asm volatile("ld.shared.v4.u32 {%0,%1,%2,%3}, [%4];" : "=r"(v[0]), "=r"(v[1]), "=r"(v[2]), "=r"(v[3]) : "r"(a) : "memory");
}
__device__ __forceinline__ void lds128_if(uint32_t (&v)[4], uint32_t a, uint32_t p) {
    asm volatile("{.reg .pred q; setp.ne.u32 q, %5, 0; @q ld.shared.v4.u32 {%0,%1,%2,%3}, [%4];}"
                 : "+r"(v[0]), "+r"(v[1]), "+r"(v[2]), "+r"(v[3])
                 : "r"(a), "r"(p)
                 : "memory");
}
__device__ __forceinline__ void lds64(uint32_t& x, uint32_t& y, uint32_t a) {
    asm volatile("ld.shared.v2.u32 {%0,%1}, [%2];" : "=r"(x), "=r"(y) : "r"(a) : "memory");
}
__device__ __forceinline__ void sts128(uint32_t a, uint32_t x, uint32_t y, uint32_t z, uint32_t w) {
    asm volatile("st.shared.v4.u32 [%0], {%1,%2,%3,%4};" ::"r"(a), "r"(x), "r"(y), "r"(z), "r"(w) : "memory");
}
__device__ __forceinline__ void sts64(uint32_t a, uint32_t x, uint32_t y) {
    asm volatile("st.shared.v2.u32 [%0], {%1,%2};" ::"r"(a), "r"(x), "r"(y) : "memory");
}
__device__ __forceinline__ uint32_t pack(float lo, float hi) {
    uint32_t r;
    asm volatile("cvt.rn.bf16x2.f32 %0, %1, %2;" : "=r"(r) : "f"(hi), "f"(lo));
    return r;
}
__device__ __forceinline__ uint32_t hmul2(uint32_t a, uint32_t b) {
    uint32_t r;
    asm volatile("mul.rn.bf16x2 %0, %1, %2;" : "=r"(r) : "r"(a), "r"(b));
    return r;
}
__device__ __forceinline__ uint32_t hfma2(uint32_t a, uint32_t b, uint32_t c) {
    uint32_t r;
    asm volatile("fma.rn.bf16x2 %0, %1, %2, %3;" : "=r"(r) : "r"(a), "r"(b), "r"(c));
    return r;
}
template <int H>
__device__ __forceinline__ uint32_t hfma2_bcast(uint32_t a, uint32_t x, uint32_t c) {
    uint32_t r;
    if (H)
        asm volatile("{.reg .b16 l, h; .reg .b32 s; mov.b32 {l, h}, %2; mov.b32 s, {h, h}; fma.rn.bf16x2 %0, %1, s, %3;}"
                     : "=r"(r)
                     : "r"(a), "r"(x), "r"(c));
    else
        asm volatile("{.reg .b16 l, h; .reg .b32 s; mov.b32 {l, h}, %2; mov.b32 s, {l, l}; fma.rn.bf16x2 %0, %1, s, %3;}"
                     : "=r"(r)
                     : "r"(a), "r"(x), "r"(c));
    return r;
}
__device__ __forceinline__ float ffma(float a, float b, float c) {
    float r;
    asm volatile("fma.rn.f32 %0, %1, %2, %3;" : "=f"(r) : "f"(a), "f"(b), "f"(c));
    return r;
}
__device__ __forceinline__ float tanh_fast(float x) {
    float r;
    asm volatile("tanh.approx.f32 %0, %1;" : "=f"(r) : "f"(x));
    return r;
}
__device__ __forceinline__ float gelu_tanh(float x) {
    float r;
    asm volatile(
        "{.reg .f32 a; mul.f32 a, %1, %1; fma.rn.f32 a, a, 0f3D122279, 0f3F4C422A; mul.f32 a, a, %1; tanh.approx.f32 %0, a;}"
        : "=f"(r)
        : "f"(x));
    return r;
}
__device__ __forceinline__ void mma16816(float (&d)[4], const uint32_t (&a)[4], uint32_t b0, uint32_t b1) {
    asm volatile("mma.sync.aligned.m16n8k16.row.col.f32.bf16.bf16.f32 {%0,%1,%2,%3}, {%4,%5,%6,%7}, {%8,%9}, {%0,%1,%2,%3};"
                 : "+f"(d[0]), "+f"(d[1]), "+f"(d[2]), "+f"(d[3])
                 : "r"(a[0]), "r"(a[1]), "r"(a[2]), "r"(a[3]), "r"(b0), "r"(b1));
}
__device__ __forceinline__ uint32_t clock32() {
    uint32_t c;
    asm volatile("mov.u32 %0, %%clock;" : "=r"(c)::"memory");
    return c;
}
#define WG_FENCE() asm volatile("wgmma.fence.sync.aligned;" ::: "memory")
#define WG_COMMIT() asm volatile("wgmma.commit_group.sync.aligned;" ::: "memory")
#define WG_WAIT0() asm volatile("wgmma.wait_group.sync.aligned 0;" ::: "memory")
#define WG_WAIT1() asm volatile("wgmma.wait_group.sync.aligned 1;" ::: "memory")
#define CP_COMMIT() asm volatile("cp.async.commit_group;" ::: "memory")
#define CP_WAIT(n) asm volatile("cp.async.wait_group %0;" ::"n"(n) : "memory")
#define SCHED_FENCE() asm volatile("pmevent 0;" ::: "memory")
#define PROXY_FENCE() asm volatile("fence.proxy.async.shared::cta;" ::: "memory")
template <int N>
__device__ __forceinline__ void pin(float (&d)[N]) {
#pragma unroll
    for (int i = 0; i < N; i++) asm volatile("" : "+f"(d[i])::"memory");
}
#define TS(k)
#define TS_DUMP(role)

__device__ __forceinline__ void wgmma_ss_n168_acc(float (&d)[84], uint64_t da, uint64_t db) {
    asm volatile(
        "wgmma.mma_async.sync.aligned.m64n168k16.f32.bf16.bf16 "
        "{%0,%1,%2,%3,%4,%5,%6,%7,%8,%9,%10,%11,%12,%13,%14,%15,"
        "%16,%17,%18,%19,%20,%21,%22,%23,%24,%25,%26,%27,%28,%29,%30,%31,"
        "%32,%33,%34,%35,%36,%37,%38,%39,%40,%41,%42,%43,%44,%45,%46,%47,"
        "%48,%49,%50,%51,%52,%53,%54,%55,%56,%57,%58,%59,%60,%61,%62,%63,"
        "%64,%65,%66,%67,%68,%69,%70,%71,%72,%73,%74,%75,%76,%77,%78,%79,"
        "%80,%81,%82,%83}, "
        "%84, %85, 1, 1, 1, 0, 1;"
        : "+f"(d[0]), "+f"(d[1]), "+f"(d[2]), "+f"(d[3]), "+f"(d[4]), "+f"(d[5]), "+f"(d[6]), "+f"(d[7]),
          "+f"(d[8]), "+f"(d[9]), "+f"(d[10]), "+f"(d[11]), "+f"(d[12]), "+f"(d[13]), "+f"(d[14]), "+f"(d[15]),
          "+f"(d[16]), "+f"(d[17]), "+f"(d[18]), "+f"(d[19]), "+f"(d[20]), "+f"(d[21]), "+f"(d[22]), "+f"(d[23]),
          "+f"(d[24]), "+f"(d[25]), "+f"(d[26]), "+f"(d[27]), "+f"(d[28]), "+f"(d[29]), "+f"(d[30]), "+f"(d[31]),
          "+f"(d[32]), "+f"(d[33]), "+f"(d[34]), "+f"(d[35]), "+f"(d[36]), "+f"(d[37]), "+f"(d[38]), "+f"(d[39]),
          "+f"(d[40]), "+f"(d[41]), "+f"(d[42]), "+f"(d[43]), "+f"(d[44]), "+f"(d[45]), "+f"(d[46]), "+f"(d[47]),
          "+f"(d[48]), "+f"(d[49]), "+f"(d[50]), "+f"(d[51]), "+f"(d[52]), "+f"(d[53]), "+f"(d[54]), "+f"(d[55]),
          "+f"(d[56]), "+f"(d[57]), "+f"(d[58]), "+f"(d[59]), "+f"(d[60]), "+f"(d[61]), "+f"(d[62]), "+f"(d[63]),
          "+f"(d[64]), "+f"(d[65]), "+f"(d[66]), "+f"(d[67]), "+f"(d[68]), "+f"(d[69]), "+f"(d[70]), "+f"(d[71]),
          "+f"(d[72]), "+f"(d[73]), "+f"(d[74]), "+f"(d[75]), "+f"(d[76]), "+f"(d[77]), "+f"(d[78]), "+f"(d[79]),
          "+f"(d[80]), "+f"(d[81]), "+f"(d[82]), "+f"(d[83])
        : "l"(da), "l"(db));
}

__device__ __forceinline__ void wgmma_rs_n32_set(float (&d)[16], const uint32_t (&a)[4], uint64_t db) {
    asm volatile(
        "wgmma.mma_async.sync.aligned.m64n32k16.f32.bf16.bf16 "
        "{%0,%1,%2,%3,%4,%5,%6,%7,%8,%9,%10,%11,%12,%13,%14,%15}, "
        "{%16,%17,%18,%19}, %20, 0, 1, 1, 0;"
        : "=f"(d[0]), "=f"(d[1]), "=f"(d[2]), "=f"(d[3]), "=f"(d[4]), "=f"(d[5]), "=f"(d[6]), "=f"(d[7]),
          "=f"(d[8]), "=f"(d[9]), "=f"(d[10]), "=f"(d[11]), "=f"(d[12]), "=f"(d[13]), "=f"(d[14]), "=f"(d[15])
        : "r"(a[0]), "r"(a[1]), "r"(a[2]), "r"(a[3]), "l"(db));
}

__device__ __forceinline__ void wgmma_rs_n32_acc(float (&d)[16], const uint32_t (&a)[4], uint64_t db) {
    asm volatile(
        "wgmma.mma_async.sync.aligned.m64n32k16.f32.bf16.bf16 "
        "{%0,%1,%2,%3,%4,%5,%6,%7,%8,%9,%10,%11,%12,%13,%14,%15}, "
        "{%16,%17,%18,%19}, %20, 1, 1, 1, 0;"
        : "+f"(d[0]), "+f"(d[1]), "+f"(d[2]), "+f"(d[3]), "+f"(d[4]), "+f"(d[5]), "+f"(d[6]), "+f"(d[7]),
          "+f"(d[8]), "+f"(d[9]), "+f"(d[10]), "+f"(d[11]), "+f"(d[12]), "+f"(d[13]), "+f"(d[14]), "+f"(d[15])
        : "r"(a[0]), "r"(a[1]), "r"(a[2]), "r"(a[3]), "l"(db));
}

__device__ __forceinline__ void wgmma_rs_n16_set(float (&d)[8], const uint32_t (&a)[4], uint64_t db) {
    asm volatile(
        "wgmma.mma_async.sync.aligned.m64n16k16.f32.bf16.bf16 "
        "{%0,%1,%2,%3,%4,%5,%6,%7}, "
        "{%8,%9,%10,%11}, %12, 0, 1, 1, 0;"
        : "=f"(d[0]), "=f"(d[1]), "=f"(d[2]), "=f"(d[3]), "=f"(d[4]), "=f"(d[5]), "=f"(d[6]), "=f"(d[7])
        : "r"(a[0]), "r"(a[1]), "r"(a[2]), "r"(a[3]), "l"(db));
}

__device__ __forceinline__ void wgmma_rs_n16_acc(float (&d)[8], const uint32_t (&a)[4], uint64_t db) {
    asm volatile(
        "wgmma.mma_async.sync.aligned.m64n16k16.f32.bf16.bf16 "
        "{%0,%1,%2,%3,%4,%5,%6,%7}, "
        "{%8,%9,%10,%11}, %12, 1, 1, 1, 0;"
        : "+f"(d[0]), "+f"(d[1]), "+f"(d[2]), "+f"(d[3]), "+f"(d[4]), "+f"(d[5]), "+f"(d[6]), "+f"(d[7])
        : "r"(a[0]), "r"(a[1]), "r"(a[2]), "r"(a[3]), "l"(db));
}

__device__ __forceinline__ void wgmma_rs_n32_pred(float (&d)[16], const uint32_t (&a)[4], uint64_t db, uint32_t scale_d) {
    asm volatile(
        "{.reg .pred p; setp.ne.u32 p, %21, 0; wgmma.mma_async.sync.aligned.m64n32k16.f32.bf16.bf16 "
        "{%0,%1,%2,%3,%4,%5,%6,%7,%8,%9,%10,%11,%12,%13,%14,%15}, "
        "{%16,%17,%18,%19}, %20, p, 1, 1, 0;}"
        : "+f"(d[0]), "+f"(d[1]), "+f"(d[2]), "+f"(d[3]), "+f"(d[4]), "+f"(d[5]), "+f"(d[6]), "+f"(d[7]),
          "+f"(d[8]), "+f"(d[9]), "+f"(d[10]), "+f"(d[11]), "+f"(d[12]), "+f"(d[13]), "+f"(d[14]), "+f"(d[15])
        : "r"(a[0]), "r"(a[1]), "r"(a[2]), "r"(a[3]), "l"(db), "r"(scale_d));
}

__device__ __forceinline__ void prep_cta(uint32_t sb, int c, const __nv_bfloat16* __restrict__ wc,
                                         const __nv_bfloat16* __restrict__ se1, const __nv_bfloat16* __restrict__ se2) {
    const int tid = threadIdx.x, lane = tid & 31, warp = tid >> 5;
    constexpr int NROW = 2 * NF * NF;
#pragma unroll
    for (int q = tid; q < NROW * 2; q += 384) cp16(sb + q * 16, wc + (q >> 1) * ND + c * 16 + (q & 1) * 8);
    if (tid == 0) sts128(sb + NROW * 32, 0, 0, 0, 0);
    if (tid < 256) {
        const int l2 = c >> 1, n = ((tid >> 2) & 1) * 8 + (tid >> 5) + (l2 ? (c & 1) * 16 : 0);
        const int k = ((tid >> 1) & 1) * 8 + ((tid >> 3) & 3) * 2 + (tid & 1), mm = k >> 1, u = k & 1;
        const int f = l2 ? fmap(n) : mm < 6 ? 4 * mm + 2 * c + u : (mm == 6 && u == 0) ? 24 + c : -1;
        float v = 0.f;
        if (f >= 0 && (l2 ? k : n) < NR) v = __bfloat162float(l2 ? se2[k * NF + f] : se1[f * NR + n]);
        reinterpret_cast<__nv_bfloat16*>(g_se)[c * 256 + tid] = __float2bfloat16(l2 ? 0.5f * v : v);
    }
    asm volatile("cp.async.wait_all;" ::: "memory");
    __syncthreads();
    const int k = 4 * (lane & 6) + 2 * (lane >> 3) + (lane & 1), i = fmap(k);
    const int g = lane >> 2, t = lane & 3;
#pragma unroll 4
    for (int task = warp; task < 128; task += 12) {
        const int eg = task & 1, n = (task >> 1) & 31, s = task >> 6;
        const int j = fmap(n ^ s);
        const uint32_t a = k < 28 ? sb + ((s * NF + i) * NF + j) * 32 + eg * 16 : sb + NROW * 32;
        uint4 v;
        asm volatile("ldmatrix.sync.aligned.m8n8.x4.trans.shared.b16 {%0,%1,%2,%3}, [%4];"
                     : "=r"(v.x), "=r"(v.y), "=r"(v.z), "=r"(v.w)
                     : "r"(a));
        const int e = eg * 8 + g;
        if (t == 3) {
            const uint32_t mask = eg ? 0xffff0000u : 0xffffu;
            v.x &= mask;
            v.y &= mask;
        }
        const int ch = (t < 2 ? t ^ ((e >> 1) & 1) : t) ^ ((n >> 1) & 3);
        g_wc[(c >> 1) * 8192 + ((g & 1) + 2 * eg + 2 * (g & 6)) * 512 + (c & 1) * 256 + s * 128 + n * 4 + ch] = v;
    }
    __threadfence();
    __syncthreads();
    if (tid == 0) atomicAdd(&g_ready, 1u);
}

#define TWARM 7
#define WPF_STEP 800
#define WDELAY 1600
#define WSTEP 500
#define START_MIN 3300
#define DB0 6
#define T_SHIFT 300
#define DBASE (mkdesc(sb + w * 4096, 16, 512, 2) + ((uint64_t)zero << 32))
#define PACE1 2100
#define PACE2 2700
#define PF_START 2600
#define PF_PACE 550
#define WPF_AT 3000

__global__ void __cluster_dims__(2, 1, 1) __launch_bounds__(384, 1)
fibinet_kernel(const int* __restrict__ idx, const uint4* __restrict__ table,
               const __nv_bfloat16* __restrict__ se1, const __nv_bfloat16* __restrict__ se2,
               const __nv_bfloat16* __restrict__ wc,
               const unsigned char* __restrict__ w1, const __nv_bfloat16* __restrict__ w2, __nv_bfloat16* __restrict__ out,
               const __grid_constant__ CUtensorMap tm_w1, const __grid_constant__ CUtensorMap tm_bi) {
    extern __shared__ __align__(1024) unsigned char smem[];
    const int tid = threadIdx.x;
    const int cta = blockIdx.x - NPREP, grp = cta >> 1, rank = cta & 1, lane = tid & 31;
    uint32_t ids[13][4], cid[3][2];
    const uint32_t idle = (tid >> 8) | (cta < 0);
    const uint32_t row = ((tid >> 5) & 3) * 16 + (lane >> 3);
    const unsigned char* ib = reinterpret_cast<const unsigned char*>(idx) + (int64_t)grp * (64 * NF * 4);
    {
        const unsigned char* ip = ib + (row * (NF * 4) + ((tid >> 4) & 8));
#pragma unroll
        for (int u = 0; u < 4; u++) {
            ids[0][u] = ids[1][u] = 0;
            asm volatile("{.reg .pred p; setp.eq.u32 p, %3, 0; @p ld.global.nc.L2::128B.v2.u32 {%0,%1}, [%2];}"
                         : "+r"(ids[0][u]), "+r"(ids[1][u])
                         : "l"(ip + 16 * NF * u), "r"(idle));
        }
    }
    const uint32_t t_0 = clock32();
    {
        const uint32_t co = ((tid & 127) >> 1) * (NF * 4) + ((tid >> 4) & 8) + 16 + 16 * (tid & 1);
#pragma unroll
        for (int k = 0; k < 3; k++) {
            cid[k][0] = cid[k][1] = 0;
            asm volatile("{.reg .pred p; setp.eq.u32 p, %3, 0; @p ld.global.nc.v2.u32 {%0,%1}, [%2];}"
                         : "+r"(cid[k][0]), "+r"(cid[k][1])
                         : "l"(ib + (co + 32 * k - (k == 2 ? 8 * ((tid >> 7) & tid & 1) : 0))), "r"(idle));
        }
    }
    const uint32_t t_start = (t_0 ^ (clock32() & blockIdx.y)) - T_SHIFT;
    const uint32_t sb = (uint32_t)__cvta_generic_to_shared(smem);
    uint32_t gd0 = sb + (tid >> 7) * XDELTA + row * 128 + (((lane & 7) ^ (lane >> 3) ^ ((tid >> 5) & 4)) << 4);
    const uint4* tp = table + (lane & 7);
    auto gather = [&](int i) {
#pragma unroll
        for (int u = 0; u < 4; u++)
            asm volatile(
                "{.reg .u64 a; .reg .pred p; setp.eq.u32 p, %3, 0; mad.wide.u32 a, %2, 128, %1; @p cp.async.cg.shared.global [%0], [a], 16;}" ::"r"(
                    (gd0 ^ ((u & 1) * 64)) + xpair(i) + u * 512),
                "l"(tp), "r"(ids[i][u]), "r"(i == 0 ? idle : 0u)
                : "memory");
        CP_COMMIT();
    };
    gather(0);
    if (cta < 0) {
        prep_cta(sb, blockIdx.x, wc, se1, se2);
        return;
    }
    if (tid == 288) asm volatile("prefetch.tensormap [%0];" ::"l"(&tm_w1));
    const int warp = __reduce_max_sync(0xffffffffu, tid >> 5);
    const int w = warp >> 2;

    if (w == 2) {
        asm volatile("setmaxnreg.dec.sync.aligned.u32 40;");
        auto load_wc = [&](int gi) {
            if (elect()) {
                const unsigned char* src = reinterpret_cast<const unsigned char*>(g_wc) + rank * 131072;
                mbar_expect(sb + BAR_WC + gi * 8, (wcfirst(gi + 1) - wcfirst(gi)) * 8192);
#pragma unroll
                for (int c = wcfirst(gi); c < wcfirst(gi + 1); c++) bulk(sb + wcslot(c), src + c * 8192, 8192, sb + BAR_WC + gi * 8);
            }
            __syncwarp();
        };
        if (warp == 8) {
            if (elect()) {
                mbar_init(sb + BAR_Z, 1);
                mbar_expect(sb + BAR_Z, 8192);
                tma2d(sb + ZOFF, &tm_bi, sb + BAR_Z, 32 * rank, 0);
            }
#pragma unroll
            for (int f = 0; f < 26; f++) {
                if (f == 2) {
                    if (elect()) {
#pragma unroll
                        for (int k = 2; k < 8; k++) mbar_init(sb + BAR_FULL + k * 8, 1);
                        asm volatile("fence.mbarrier_init.release.cluster;" ::: "memory");
                    }
                    __syncwarp();
                    asm volatile("barrier.cluster.arrive.relaxed.aligned;" ::: "memory");
                    mbar_wait(sb + BAR_Z);
#pragma unroll
                    for (int k = 0; k < 2; k++)
                        sts128(sb + ZOFF + (k * 32 + lane) * 128 + ((4 ^ (lane & 7)) << 4), 0x3c803c80u, 0x3c803c80u, 0x3c803c80u, 0x3c803c80u);
                    PROXY_FENCE();
                    asm volatile("bar.arrive 0, 384;" ::: "memory");
                    TS(31);
                }
                if (f == 5) asm volatile("barrier.cluster.wait.aligned;" ::: "memory");
                if (f >= 5) mbar_wait(sb + bdone(f - 5), bpar(f - 5));
                if (f >= 2 && f < 5)
                    while (clock32() - t_start < WDELAY + (f - 2) * WSTEP) {
                    }
                if (elect()) {
                    if (f < 2) mbar_init(sb + BAR_FULL + f * 8, 1);
                    mbar_expect(sb + bfull(f), 16384);
                    tma2d(sb + slot(2 * wl(f)), &tm_w1, sb + bfull(f), 128 * rank + 64 * (f & 1), fieldof(f) * 64);
                    tma2d(sb + slot(wl(f)), &tm_w1, sb + bfull(f), 128 * rank + 64 - 64 * (f & 1), fieldof(f) * 64);
                }
                TS(f);
            }
            if (elect()) mbar_arrive(sb + BAR_GO);
            TS_DUMP(2);
        } else if (warp == 9) {
            if (elect()) {
#pragma unroll
                for (int k = 0; k < 11; k++) mbar_init(sb + BAR_WC + k * 8, k < 10 ? 1 : 8);
                asm volatile("fence.mbarrier_init.release.cluster;" ::: "memory");
                mbar_expect(sb + BAR_FIN, 512);
            }
            __syncwarp();
            asm volatile("barrier.cluster.arrive.relaxed.aligned;" ::: "memory");
            asm volatile("bar.sync 0, 384;" ::: "memory");
            mbar_wait(sb + bdone(3), bpar(3));
            if (elect()) {
                unsigned v, it = 0;
                do {
                    asm volatile("ld.acquire.gpu.global.u32 %0, [%1];" : "=r"(v) : "l"(&g_ready) : "memory");
                } while (v < NPREP && ++it < 4000000u);
                asm volatile("fence.proxy.async.global;" ::: "memory");
                mbar_expect(sb + BAR_SE, 2048);
                bulk(sb + SEOFF, g_se, 2048, sb + BAR_SE);
                if (atomicAdd(&g_seen, 1u) == NMAIN - 1) {
                    g_seen = 0;
                    g_ready = 0;
                }
            }
            __syncwarp();
            TS(0);
            mbar_wait(sb + BAR_GO);
#pragma unroll
            for (int gi = 0; gi < 3; gi++) {
                mbar_wait(sb + bdone(21 + gi), bpar(21 + gi));
                load_wc(gi);
                TS(1 + gi);
            }
        } else if (warp == 10) {
            if (elect()) {
#pragma unroll
                for (int k = 0; k < 8; k++) mbar_init(sb + BAR_DONE + k * 8, 4);
                asm volatile("fence.mbarrier_init.release.cluster;" ::: "memory");
            }
            __syncwarp();
            asm volatile("barrier.cluster.arrive.relaxed.aligned;" ::: "memory");
            asm volatile("bar.arrive 0, 384;" ::: "memory");
#pragma unroll 1
            for (int k = 0; k < 7; k++) {
                while (clock32() - t_start < (uint32_t)(WPF_AT + k * WPF_STEP)) __nanosleep(20);
                if (lane < 6)
                    asm volatile("prefetch.global.L2 [%0];" ::"l"(w1 + (5 + k * 3 + (lane >> 1)) * 32768 + cta * 256 + (lane & 1) * 128));
            }
        } else {
            asm volatile("barrier.cluster.arrive.relaxed.aligned;" ::: "memory");
            asm volatile("bar.sync 0, 384;" ::: "memory");
            const uint2 v = __ldg(reinterpret_cast<const uint2*>(w2 + 128 * rank) + lane);
#pragma unroll
            for (int k = 0; k < 2; k++) {
                const uint32_t x = k ? v.y : v.x;
                sts64(sb + w2chunk((lane >> 2) * 4 + 2 * (lane & 1) + k) + (lane & 2) * 4,
                      __float_as_uint(0.5f * __uint_as_float(x << 16)), __float_as_uint(0.5f * __uint_as_float(x & 0xffff0000u)));
            }
            __syncwarp();
            if (lane == 0) mbar_arrive(sb + BAR_W2);
        }
        if (warp != 8) asm volatile("barrier.cluster.wait.aligned;" ::: "memory");
        {
            uint32_t bw[2][4], z0[4], z1[4];
            mbar_wait(sb + BAR_SE);
            lds128(bw[0], sb + SEOFF + lane * 16);
            lds128(bw[1], sb + SEOFF + 512 + lane * 16);
            asm volatile("bar.sync 2, 384;" ::: "memory");
            lds128(z0, sb + ZQOFF + (tid & 127) * 16);
            lds128(z1, sb + ZQOFF + 2048 + (tid & 127) * 16);
            TS(8);
            float s[2][4] = {};
#pragma unroll
            for (int n = 0; n < 2; n++) {
                mma16816(s[n], z0, bw[0][2 * n], bw[0][2 * n + 1]);
                mma16816(s[n], z1, bw[1][2 * n], bw[1][2 * n + 1]);
            }
            lds128(bw[0], sb + SEOFF + 1024 + lane * 16);
            lds128(bw[1], sb + SEOFF + 1536 + lane * 16);
            float th[8];
#pragma unroll
            for (int k = 0; k < 8; k++) th[k] = gelu_tanh(s[k >> 2][k & 3]);
            SCHED_FENCE();
            TS(9);
            uint32_t gq[4];
#pragma unroll
            for (int k = 0; k < 4; k++)
                gq[k] = pack(s[k >> 1][2 * (k & 1)] * ffma(th[2 * k], 0.5f, 0.5f), s[k >> 1][2 * (k & 1) + 1] * ffma(th[2 * k + 1], 0.5f, 0.5f));
            float a[4][4] = {};
#pragma unroll
            for (int n = 0; n < 4; n++) mma16816(a[n], gq, bw[n >> 1][2 * (n & 1)], bw[n >> 1][2 * (n & 1) + 1]);
#pragma unroll
            for (int k = 0; k < 16; k++)
                if (k < 13 || k == 14) a[k >> 2][k & 3] = tanh_fast(a[k >> 2][k & 3]);
            SCHED_FENCE();
            TS(10);
            uint32_t ap[8];
#pragma unroll
            for (int k = 0; k < 8; k++)
                ap[k] = pack(ffma(a[k >> 1][2 * (k & 1)], 0.5f, 0.5f), ffma(a[k >> 1][2 * (k & 1) + (k < 6)], 0.5f, 0.5f));
            sts128(sb + GOFF + (tid & 127) * 16, ap[0], ap[1], ap[2], ap[3]);
            sts128(sb + GOFF + 2048 + (tid & 127) * 16, ap[4], ap[5], ap[6], ap[7]);
            asm volatile("bar.arrive 3, 384;" ::: "memory");
            TS(11);
        }
        if (warp == 9) {
            load_wc(3);
            load_wc(4);
            mbar_wait(sb + BAR_TD);
            load_wc(5);
            if (lane < 16) TS_DUMP(3);
        } else if (warp == 10) {
            __nv_bfloat16* dst = out + cta * 32 + lane;
            asm volatile("" : "+l"(dst));
            asm volatile("bar.sync 4, 64;" ::: "memory");
            mbar_wait(sb + BAR_FIN);
            uint32_t p[4];
            lds128(p, sb + PARTOFF + lane * 16);
            *dst = __float2bfloat16((__uint_as_float(p[0]) + __uint_as_float(p[1])) + (__uint_as_float(p[2]) + __uint_as_float(p[3])));
        }
    } else {
        asm volatile("setmaxnreg.inc.sync.aligned.u32 232;");
        asm volatile("barrier.cluster.arrive.relaxed.aligned;" ::: "memory");
        const int g = lane >> 2, t = lane & 3, wq = warp & 3, t128 = tid & 127;
        gd0 = opaque(gd0);
        TS(28);
        float acc[84];
#pragma unroll
        for (int k = 0; k < 84; k++) asm volatile("mov.b32 %0, 0;" : "=f"(acc[k]));
        uint32_t e0[9], e1[9], e2[9];
        uint32_t X[13][2][4];
        uint32_t zq[4] = {0, 0, 0, 0};
        const uint64_t dA = mkdesc(sb + w * XDELTA, 16, 1024, 1);
        uint32_t dBlo = (uint32_t)mkdesc(sb + ZOFF, 0, 0, 0);
        const uint32_t xl0 = opaque(sb + (t & 1) * XDELTA + (16 * wq + g) * 128 + (((4 * rank + 2 * w) ^ (4 * (t & 1)) ^ g) << 4));
        const uint32_t hi_half = t >> 1;
        const uint32_t sa0 = opaque(sb + AOFF + t * 4096 + (t >> 1) * 16 + (wq * 32 + g * 4 + w) * 16);
        const uint32_t sa1 = opaque(((g & 2) << 4) | ((t & 1) << 3));
        const uint32_t zero = blockIdx.y;
        auto expand = [&](int k0, int k1) {
#pragma unroll
            for (int k = k0; k < k1; k++)
#pragma unroll
                for (int u = 0; u < 4; u++)
                    asm volatile("shfl.sync.idx.b32 %0, %1, %2, 31, 0xffffffff;"
                                 : "=r"(ids[k][u])
                                 : "r"(k < 12 ? cid[(k - 2) >> 2][k & 1] : w ? cid[2][1] : cid[2][0]),
                                   "r"(2 * (lane >> 3) + 8 * u + (((k - 2) >> 1) & 1)));
        };
        auto twarm = [&]() {
            float s1[8];
            WG_FENCE();
            wgmma_rs_n16_set(s1, zq, mkdesc(sb + AOFF, 16, 512, 2));
            WG_COMMIT();
            WG_WAIT0();
            pin(s1);
            asm volatile("{.reg .pred p; setp.ne.u32 p, %1, 0; @p st.shared.f32 [%1], %0;}" ::"f"(s1[0]), "r"(zero));
        };
        expand(2, 8);
        if (TWARM & 1) twarm();
        TS(26);
        while (clock32() - t_start < PACE1) {
        }
        gather(1);
        expand(8, 13);
        if (TWARM & 2) twarm();
        TS(30);
        while (clock32() - t_start < PACE2) {
        }
        gather(2);
        if (TWARM & 4) twarm();
        asm volatile("bar.sync 0, 384;" ::: "memory");
        auto lift = [&](int i) {
            const int m = 2 * (i >> 2) + (i & 1);
#pragma unroll
            for (int r = 0; r < (i < 12 ? 2 : 1); r++)
#pragma unroll
                for (int cc = 0; cc < 2; cc++) {
                    const uint32_t a = (xl0 ^ (cc * 16)) + xpair(i) + (i < 12 ? r : hi_half) * 1024;
                    if (i & 2) lds128_if(X[2 * m + r][cc], a, hi_half);
                    else lds128(X[2 * m + r][cc], a);
                }
        };
        auto store_pair = [&](int m, int half, const uint32_t (&ea)[9]) {
            uint32_t a;
            if (m < 4) a = sa0 + (sa1 ^ (((m & 1) << 5) | ((m >> 1) << 3)));
            else a = sb + BOFF + t * 2048 + (wq * 32 + g * 4 + ((2 * (m & 1) + w) ^ t)) * 8;
#pragma unroll
            for (int n = half; n < 4; n += 2)
#pragma unroll
                for (int u = 0; u < 2; u++)
                    sts64(a + (m < 4 ? (8 * n + u) * 2048 + n * 32 : (8 * n + u) * 1024),
                          __byte_perm(ea[2 * n], e1[2 * n], u ? 0x7632 : 0x5410),
                          __byte_perm(ea[2 * n + 1], e1[2 * n + 1], u ? 0x7632 : 0x5410));
        };
        auto z_pair = [&](int m, uint32_t a, uint32_t b) {
            asm volatile("{.reg .pred p; setp.eq.u32 p, %4, %5; @p prmt.b32 %0, %2, %3, 0x5410; @p prmt.b32 %1, %2, %3, 0x7632;}"
                         : "+r"(zq[2 * (m >> 2)]), "+r"(zq[2 * (m >> 2) + 1])
                         : "r"(a), "r"(b), "r"(t), "r"(m & 3));
        };

        TS(29);
        mbar_wait(sb + BAR_FULL + w * 8);
        CP_WAIT(2);
        while (clock32() - t_start < START_MIN) {
        }
        if (w == 1) {
            asm volatile("bar.arrive 6, 256;" ::: "memory");
            asm volatile("bar.sync 5, 256;" ::: "memory");
        }
#pragma unroll
        for (int i = 0; i < 13; i++) {
            const uint64_t da = dA + (xpair(i) >> 4) + ((uint64_t)i << 16);
            dBlo += (uint32_t)(w ? wl(2 * i + 1) - (i ? wl(2 * i - 1) : 0) : wl(2 * i) - (i ? wl(2 * i - 2) : 0)) *
                    (uint32_t)((SLOT << 12) - (SLOT >> 3));
            const uint64_t db = mkdesc(0, 0, 1024, 1) | dBlo;
            TS(i);
            WG_FENCE();
            wgmma_ss_n168_acc(acc, da, db + w * 256);
            wgmma_ss_n168_acc(acc, da + 2, db + w * 256 + 128);
            wgmma_ss_n168_acc(acc, da + 4, db + (w ^ 1) * 256);
            wgmma_ss_n168_acc(acc, da + 6, db + (w ^ 1) * 256 + 128);
            WG_COMMIT();
            if (i == 0) {
                if (w == 0) {
                    asm volatile("bar.arrive 5, 256;" ::: "memory");
                    asm volatile("bar.sync 6, 256;" ::: "memory");
                }
            } else {
                mbar_wait(sb + bdone(2 * i - 2) + (w ^ 1) * 8, bpar(2 * i - 2));
            }
            if (i < 10) gather(i + 3);
            if (i == 1) asm volatile("barrier.cluster.wait.aligned;" ::: "memory");
            if (i == 6) mbar_wait(sb + BAR_W2);
            lift(i);
            if (i == 10 || i == 11) mbar_wait(sb + bdone(2 * i - 2) + w * 8, bpar(2 * i - 2));
            if (i >= 2 && !(i & 1)) {
                z_pair((i - 2) >> 1, e0[8], e1[8]);
                store_pair((i - 2) >> 1, 0, e0);
#pragma unroll
                for (int k = 0; k < 8; k++) e2[k] = e0[k];
            } else if (i >= 3) {
                store_pair((i - 3) >> 1, 1, e2);
            }
            const uint32_t rdy = i < 12 ? mbar_test(sb + bfull(2 * i + 2) + w * 8, bpar(2 * i + 2)) : 0;
            WG_WAIT0();
            pin(acc);
            if (i == 12) TS(13);
            if (i == 0) TS(27);
            if (i < 10) CP_WAIT(2);
            else if (i == 10) CP_WAIT(1);
            else if (i == 11) CP_WAIT(0);
            if (i < 12 && lane == 0) mbar_arrive(sb + bdone(2 * i) + w * 8);
#pragma unroll
            for (int k = 0; k < 9; k++) {
                const int k0 = 64 + 2 * (k & 5) + ((k >> 1) & 1);
                const uint32_t v = k == 8 ? pack(acc[80], acc[82]) : i < 12 ? pack(acc[64 + 2 * k], acc[65 + 2 * k]) : pack(acc[k0], acc[k0 + 4]);
                if (i & 1) e1[k] = v;
                else e0[k] = v;
            }
            if (i < 12) {
#pragma unroll
                for (int k = 64; k < 83; k++)
                    if (k != 81) asm volatile("mov.b32 %0, %1;" : "+f"(acc[k]) : "r"(zero));
                mbar_wait_unless(rdy, sb + bfull(2 * i + 2) + w * 8, bpar(2 * i + 2));
            } else {
                z_pair(6, e0[8], 0);
                sts128(sb + ZQOFF + w * 2048 + t128 * 16, zq[0], zq[1], zq[2], zq[3]);
                asm volatile("bar.arrive 2, 384;" ::: "memory");
            }
        }
        TS(14);

        uint32_t ai[8];
        float sum0 = 0.f, sum1 = 0.f;
        float th[32];
        uint32_t hw[4][4];
        auto deep_issue = [&](int k2) {
            lds128(hw[k2], ((sb + w2chunk(w * 16 + t)) ^ ((k2 & 1) * 64)) + k2 * 512);
#pragma unroll
            for (int k = 8 * k2; k < 8 * k2 + 8; k++) th[k] = gelu_tanh(acc[k]);
        };
        auto deep_use = [&](int k2) {
#pragma unroll
            for (int k = 8 * k2; k < 8 * k2 + 8; k++) {
                const float h = __uint_as_float(hw[k2][((k >> 1) & 2) + (k & 1)]);
                const float y = ffma(th[k], h, h);
                if (k & 2) sum1 = ffma(acc[k], y, sum1);
                else sum0 = ffma(acc[k], y, sum0);
            }
        };
        auto deep_send = [&](int k0, int k1) {
#pragma unroll
            for (int k = k0; k < k1; k++)
                sts128(sb + EXOFF + w * SLOT + t128 * 16 + k * 2048, pack(acc[32 + 8 * k], acc[33 + 8 * k]),
                       pack(acc[34 + 8 * k], acc[35 + 8 * k]), pack(acc[36 + 8 * k], acc[37 + 8 * k]), pack(acc[38 + 8 * k], acc[39 + 8 * k]));
        };
        uint32_t o[4][4];
        auto deep_recv = [&](int k0, int k1) {
#pragma unroll
            for (int k = k0; k < k1; k++) lds128(o[k], sb + EXOFF + (w ^ 1) * SLOT + t128 * 16 + k * 2048);
        };
        auto deep_add = [&](int k0, int k1) {
            const uint32_t eye = (g >> 1) == t ? ((g & 1) ? 0x3f800000u : 0x3f80u) : 0u;
#pragma unroll
            for (int k = 2 * k0; k < 2 * k1; k++)
                asm volatile("mma.sync.aligned.m16n8k8.row.col.f32.bf16.bf16.f32 {%0,%1,%2,%3}, {%4,%5}, {%6}, {%0,%1,%2,%3};"
                             : "+f"(acc[4 * k]), "+f"(acc[4 * k + 1]), "+f"(acc[4 * k + 2]), "+f"(acc[4 * k + 3])
                             : "r"(o[k >> 1][2 * (k & 1)]), "r"(o[k >> 1][2 * (k & 1) + 1]), "r"(eye));
        };
        auto store_last = [&]() {
#pragma unroll
            for (int n = 0; n < 4; n++) sts64(sb + COFF + w * 4096 + n * 1024 + (t128 ^ w) * 8, e0[2 * n], e0[2 * n + 1]);
            store_pair(5, 1, e2);
        };
        const uint32_t la = sb + AOFF + w * (16 * 2048 + 64) + (wq * 32 + g * 4 + (t ^ (g & 2))) * 16;
        const uint32_t lb = sb + BOFF + w * (16 * 1024) + t128 * 8;
        const uint32_t lc0 = sb + COFF + (t & 1) * (4096 + 8) + w * 2048 + (wq * 8 + g) * 32, lc1 = lc0 ^ 8;
        uint32_t Ap[2][2][4];
        auto load_a = [&](int s) {
            const int e = estep(s);
            lds128(Ap[s & 1][0], la + e * 2048 + (e >> 2) * 16);
            lds64(Ap[s & 1][1][0], Ap[s & 1][1][1], (lb ^ ((e & 6) * 4)) + e * 1024);
            if (!(s & 2)) lds64(Ap[s & 1][1][2], Ap[s & 1][1][3], ((e & 2) ? lc1 : lc0) + (e & 1) * 1024 + (e & 4) * 4);
        };
        {
            uint32_t v[2][4];
            deep_send(0, 2);
            asm volatile("bar.sync 1, 256;" ::: "memory");
            deep_recv(0, 2);
            deep_send(2, 4);
            TS(15);
            deep_add(0, 2);
            deep_issue(0);
            asm volatile("bar.sync 1, 256;" ::: "memory");
            deep_recv(2, 4);
            SCHED_FENCE();
            deep_add(2, 4);
            TS(16);
            deep_issue(1);
            deep_use(0);
            store_last();
            SCHED_FENCE();
            TS(17);
            deep_issue(2);
            deep_use(1);
            mbar_wait(sb + BAR_WC);
            deep_use(2);
            TS(18);
            asm volatile("bar.sync 3, 384;" ::: "memory");
            lds128(v[0], sb + GOFF + t128 * 16);
            lds128(v[1], sb + GOFF + 2048 + t128 * 16);
            load_a(0);
            load_a(1);
            deep_issue(3);
#pragma unroll
            for (int k = 0; k < 8; k++) ai[k] = v[k >> 2][k & 3];
        }
        TS(19);

        uint32_t fin_a, dsum[2];
        {
            uint64_t dW[4];
#pragma unroll
            for (int k = 0; k < 4; k++) dW[k] = DBASE + (wcslot(0) >> 4) + (k >> 1) * 128 + (k & 1) * 2;
            uint32_t Aq[2][2][4], pq[13], gate[13];
            float S[2][2][16];
            auto scale_a = [&](int s) {
#pragma unroll
                for (int k = 0; k < ((s & 2) ? 6 : 8); k++)
                    Aq[s & 1][k >> 2][k & 3] = hmul2(Ap[s & 1][k >> 2][k & 3], ai[k < 4 ? k ^ (estep(s) & 2) : k]);
            };
            auto sbuf = [](int s) { return s <= DB0 ? 0 : (s - DB0) & 1; };
            auto issue = [&](int s) {
                const bool first = s == 0 || s == DB0 + 1;
                WG_FENCE();
                if (first) wgmma_rs_n32_set(S[sbuf(s)][0], Ap[s & 1][0], dW[0]);
                else wgmma_rs_n32_pred(S[sbuf(s)][0], Ap[s & 1][0], dW[0], zero);
                wgmma_rs_n32_acc(S[sbuf(s)][0], Ap[s & 1][1], dW[1]);
                if (first) wgmma_rs_n32_set(S[sbuf(s)][1], Aq[s & 1][0], dW[2]);
                else wgmma_rs_n32_pred(S[sbuf(s)][1], Aq[s & 1][0], dW[2], zero);
                wgmma_rs_n32_acc(S[sbuf(s)][1], Aq[s & 1][1], dW[3]);
                WG_COMMIT();
                if (s < 15) {
#pragma unroll
                    for (int k = 0; k < 4; k++)
                        asm volatile("add.s64 %0, %0, %1;" : "+l"(dW[k]) : "l"((int64_t)((wcslot(s + 1) - wcslot(s)) / 16)));
                }
            };
            scale_a(0);
            issue(0);
            SCHED_FENCE();
            deep_use(3);
            scale_a(1);
            mbar_wait(sb + BAR_WC + 8);
#pragma unroll
            for (int e = 0; e < 16; e++) {
                if (e >= DB0 && e < 15) {
                    issue(e + 1);
                    WG_WAIT1();
                } else {
                    WG_WAIT0();
                }
                pin(S[sbuf(e)][0]);
                pin(S[sbuf(e)][1]);
                if (e == 0 && lane == 0) mbar_arrive(sb + BAR_TD);
                if (e == 0) TS(20);
                if (e + 2 < 16) load_a(e + 2);
                uint32_t v[13];
                auto accum = [&](int q) {
                    const uint32_t x = X[q][(e >> 1) & 1][e >> 2];
                    pq[q] = (e & 1) ? hfma2_bcast<1>(v[q], x, pq[q]) : hfma2_bcast<0>(v[q], x, e ? pq[q] : 0u);
                };
#pragma unroll
                for (int q = 0; q < 13; q++) {
                    const int ix = 4 * (q >> 2) + 2 * (q & 1) + ((q >> 1) & 1);
                    v[q] = pack(S[sbuf(e)][0][ix], S[sbuf(e)][1][ix ^ 1]);
                    if (q == 12)
                        asm volatile("{.reg .pred p; setp.ne.u32 p, %3, 0; @p cvt.rn.bf16x2.f32 %0, %2, %1;}"
                                     : "+r"(v[q])
                                     : "f"(S[sbuf(e)][0][14]), "f"(S[sbuf(e)][1][15]), "r"(hi_half));
                    if (e >= DB0 || q < 7) accum(q);
                }
                if (e < DB0) {
                    issue(e + 1);
                    SCHED_FENCE();
#pragma unroll
                    for (int q = 7; q < 13; q++) accum(q);
                }
                if (e == 3) {
                    const float h0 = __uint_as_float(__float_as_uint(sum0) & 0xffff0000u);
                    const float h1 = __uint_as_float(__float_as_uint(sum1) & 0xffff0000u);
                    dsum[0] = pack(sum0 - h0, h0);
                    dsum[1] = pack(sum1 - h1, h1);
                }
                if (e == 13) {
                    asm("mapa.shared::cluster.u32 %0, %1, %2;"
                        : "=r"(fin_a)
                        : "r"(sb + PARTOFF + (((wq & 1) * 16 + g) * 4 + 2 * rank + w) * 4), "r"(wq >> 1));
                    fin_a = opaque(fin_a);
                }
                if (e == 14) {
                    if (warp == 0) asm volatile("bar.arrive 4, 64;" ::: "memory");
#pragma unroll
                    for (int q = 0; q < 13; q++)
                        asm volatile("prmt.b32 %0, %1, 0x3f80, %2;"
                                     : "=r"(gate[q])
                                     : "r"(q < 12 ? ai[2 * (q >> 2) + (q & 1)] : hi_half ? ai[7] : ai[6]), "r"((q & 2) ? 0x3254 : 0x1054));
                }
                if (e + 2 < 16) scale_a(e + 2);
                if (e == 0 || e == 3 || e == 6 || e == 9) mbar_wait(sb + BAR_WC + (e / 3 + 2) * 8);
                else if (e < 15) SCHED_FENCE();
                if (e == 7) TS(21);
            }
            float r0[4] = {0.f, 0.f, 0.f, 0.f}, r1[4] = {0.f, 0.f, 0.f, 0.f}, r2[4] = {0.f, 0.f, 0.f, 0.f};
#pragma unroll
            for (int c = 0; c < 3; c++) {
                const uint32_t a[4] = {pq[4 * c], pq[4 * c + 1], pq[4 * c + 2], pq[4 * c + 3]};
                mma16816(r0, a, gate[4 * c], gate[4 * c + 2]);
                mma16816(r1, a, gate[4 * c + 1], gate[4 * c + 3]);
            }
            const uint32_t rest[4] = {dsum[0], dsum[1], hi_half ? 0u : pq[12], hi_half ? pq[12] : 0u};
            mma16816(r2, rest, 0x3f803f80u, gate[12]);
            sum0 = (g & 1) ? r0[1] + r2[1] : r0[0] + r2[0];
            sum1 = (g & 1) ? r1[3] + r2[3] : r1[2] + r2[2];
        }
        TS(22);
        {
            asm volatile(
                "{.reg .pred p; setp.eq.u32 p, %4, %5;\n"
                "@p st.async.shared::cluster.mbarrier::complete_tx::bytes.f32 [%0], %1, [%3];\n"
                "@p st.async.shared::cluster.mbarrier::complete_tx::bytes.f32 [%0 + 128], %2, [%3];}" ::"r"(fin_a),
                "f"(sum0), "f"(sum1), "r"((fin_a & ~0x3ffu) + (BAR_FIN & 0x3ff)), "r"(t), "r"(g >> 1)
                : "memory");
            if (wq == 0) TS_DUMP(w);
        }
    }
}

typedef CUresult (*EncodeFn)(CUtensorMap*, CUtensorMapDataType, cuuint32_t, void*, const cuuint64_t*, const cuuint64_t*,
                             const cuuint32_t*, const cuuint32_t*, CUtensorMapInterleave, CUtensorMapSwizzle,
                             CUtensorMapL2promotion, CUtensorMapFloatOOBfill);

}

extern "C" void kernel_launch(void* const* d_in, const int* in_sizes, int n_in, void* d_out, int out_size) {
    static EncodeFn encode = nullptr;
    if (!encode) {
        void* fn = nullptr;
        cudaDriverEntryPointQueryResult qr;
        cudaGetDriverEntryPoint("cuTensorMapEncodeTiled", &fn, cudaEnableDefault, &qr);
        encode = (EncodeFn)fn;
        cudaFuncSetAttribute(fibinet_kernel, cudaFuncAttributeMaxDynamicSharedMemorySize, SMEM_BYTES);
    }
    CUtensorMap tm;
    const cuuint64_t gd[2] = {NH, NF * ND};
    const cuuint64_t gs[1] = {NH * 2};
    const cuuint32_t bd[2] = {64, 64}, es[2] = {1, 1};
    encode(&tm, CU_TENSOR_MAP_DATA_TYPE_BFLOAT16, 2, d_in[6], gd, gs, bd, es, CU_TENSOR_MAP_INTERLEAVE_NONE,
           CU_TENSOR_MAP_SWIZZLE_128B, CU_TENSOR_MAP_L2_PROMOTION_L2_256B, CU_TENSOR_MAP_FLOAT_OOB_FILL_NONE);
    CUtensorMap tb;
    const cuuint64_t gd2[2] = {ND, ND};
    const cuuint64_t gs2[1] = {ND * 2};
    encode(&tb, CU_TENSOR_MAP_DATA_TYPE_BFLOAT16, 2, d_in[4], gd2, gs2, bd, es, CU_TENSOR_MAP_INTERLEAVE_NONE,
           CU_TENSOR_MAP_SWIZZLE_128B, CU_TENSOR_MAP_L2_PROMOTION_L2_256B, CU_TENSOR_MAP_FLOAT_OOB_FILL_NONE);
    fibinet_kernel<<<NPREP + NMAIN, 384, SMEM_BYTES>>>(
        (const int*)d_in[0], (const uint4*)d_in[1], (const __nv_bfloat16*)d_in[2], (const __nv_bfloat16*)d_in[3],
        (const __nv_bfloat16*)d_in[5], (const unsigned char*)d_in[6], (const __nv_bfloat16*)d_in[7], (__nv_bfloat16*)d_out, tm, tb);
}
```

```cpp
#include <cuda_runtime.h>
#include <cuda_bf16.h>
#include <cuda.h>
#include <stdint.h>

namespace {

constexpr int NB = 4096, NF = 26, ND = 64, NH = 256, NR = 13;
constexpr int NPREP = 4;
constexpr int NMAIN = 128;

constexpr int SLOT = 8192;
constexpr int ZOFF = 15 * SLOT;
__host__ __device__ constexpr int slot(int s) { return ZOFF - s * SLOT; }
constexpr int BOFF = ZOFF + SLOT;
constexpr int AOFF = BOFF + 32768;
constexpr int COFF = slot(12);
constexpr int MOFF = AOFF + 65536 + 128;
constexpr int BAR_FULL = MOFF, BAR_DONE = MOFF + 64, BAR_WC = MOFF + 128, BAR_FIN = MOFF + 176,
              BAR_GO = MOFF + 184, BAR_SE = MOFF + 192, BAR_W2 = MOFF + 200, BAR_TD = MOFF + 208, BAR_Z = MOFF + 216;
__host__ __device__ constexpr int bfull(int f) { return BAR_FULL + (f & 7) * 8; }
__host__ __device__ constexpr int bdone(int f) { return BAR_DONE + (f & 7) * 8; }
__host__ __device__ constexpr int bpar(int f) { return (f >> 3) & 1; }
constexpr int PARTOFF = MOFF + 256, SEOFF = MOFF + 768;
constexpr int SMEM_BYTES = MOFF + 2944;
constexpr int XDELTA = 2 * SLOT;
__host__ __device__ constexpr int xpair(int i) {
    return (i & 3) == 0 ? slot(11) : (i & 3) == 1 ? BOFF : (i & 3) == 2 ? BOFF + SLOT : slot(15);
}
__host__ __device__ constexpr int wl(int f) { return f % 5 == 0 ? 1 : f % 5 == 4 ? 7 : f % 5 + 2; }
__host__ __device__ constexpr int wcslot(int c) {
    return c == 0 ? slot(3) : c == 1 ? slot(8) : c == 2 ? slot(10) : c == 3 ? slot(15) : c == 4 ? slot(13)
         : c == 5 ? slot(11) : c == 6 ? slot(9) : c == 7 ? slot(14) : c == 8 ? slot(7) : c == 9 ? slot(2)
         : c == 10 ? slot(1) : c == 11 ? slot(4) : c == 12 ? slot(5) : c == 13 ? slot(6) : c == 14 ? ZOFF : slot(3);
}
__host__ __device__ constexpr int wcfirst(int gi) { return gi < 3 ? gi : gi == 3 ? 5 : gi == 4 ? 8 : gi == 5 ? 11 : 16; }
constexpr int EXOFF = slot(5);
constexpr int ZQOFF = slot(6);
constexpr int GOFF = ZQOFF + 4096;
__host__ __device__ constexpr int w2chunk(int c) { return ZOFF + c * 128 + ((5 ^ (c & 7)) << 4); }

__device__ uint4 g_wc[2 * 16 * 8192 / 16];
__device__ uint4 g_se[2048 / 16];
__device__ unsigned g_ready;
__device__ unsigned g_seen;

__host__ __device__ constexpr int fieldof(int f) { return f < 24 ? 4 * (f >> 2) + 2 * (f & 1) + ((f >> 1) & 1) : f; }
__device__ __forceinline__ int fmap(int n) { return n < 24 ? n : 24 + ((n >> 1) & 1); }
__host__ __device__ constexpr int estep(int s) { return (s & 1) + 2 * (s >> 2) + 4 * (s & 2); }

__device__ __forceinline__ uint64_t mkdesc(uint32_t addr, uint32_t lbo, uint32_t sbo, int sw) {
    return (uint64_t)((addr & 0x3ffff) >> 4) | ((uint64_t)(lbo >> 4) << 16) | ((uint64_t)(sbo >> 4) << 32) |
           ((uint64_t)sw << 62);
}
__device__ __forceinline__ void mbar_init(uint32_t b, uint32_t n) {
    asm volatile("mbarrier.init.shared.b64 [%0], %1;" ::"r"(b), "r"(n) : "memory");
}
__device__ __forceinline__ void mbar_wait(uint32_t b, uint32_t par = 0) {
    asm volatile(
        "{\n.reg .pred p, q;\n.reg .u32 n;\n"
        "mbarrier.try_wait.parity.shared.b64 p, [%0], %1;\n@p bra.uni WD%=;\nmov.u32 n, 0;\n"
        "WL%=:\nmbarrier.try_wait.parity.shared.b64 p, [%0], %1;\n@p bra.uni WD%=;\n"
        "add.u32 n, n, 1;\nsetp.lt.u32 q, n, 4000000;\n@q bra.uni WL%=;\nWD%=:\n}\n" ::"r"(b), "r"(par)
        : "memory");
}
__device__ __forceinline__ uint32_t mbar_test(uint32_t b, uint32_t par) {
    uint32_t ok;
    asm volatile("{.reg .pred p; mbarrier.test_wait.parity.shared.b64 p, [%1], %2; selp.u32 %0, 1, 0, p;}"
                 : "=r"(ok)
                 : "r"(b), "r"(par)
                 : "memory");
    return ok;
}
__device__ __forceinline__ void mbar_wait_unless(uint32_t ok, uint32_t b, uint32_t par) {
    asm volatile(
        "{\n.reg .pred p, q;\n.reg .u32 n;\n"
        "setp.ne.u32 p, %1, 0;\n@p bra.uni WD%=;\nmov.u32 n, 0;\n"
        "WL%=:\nmbarrier.try_wait.parity.shared.b64 p, [%0], %2;\n@p bra.uni WD%=;\n"
        "add.u32 n, n, 1;\nsetp.lt.u32 q, n, 4000000;\n@q bra.uni WL%=;\nWD%=:\n}\n" ::"r"(b), "r"(ok), "r"(par)
        : "memory");
}
__device__ __forceinline__ void mbar_arrive(uint32_t b) {
    asm volatile("mbarrier.arrive.shared.b64 _, [%0];" ::"r"(b) : "memory");
}
__device__ __forceinline__ void mbar_expect(uint32_t b, uint32_t bytes) {
    asm volatile("mbarrier.arrive.expect_tx.shared.b64 _, [%0], %1;" ::"r"(b), "r"(bytes) : "memory");
}
__device__ __forceinline__ uint32_t opaque(uint32_t v) { return __shfl_sync(0xffffffffu, v, threadIdx.x); }
__device__ __forceinline__ bool elect() {
    uint32_t p;
    asm volatile("{.reg .pred q; elect.sync _|q, 0xffffffff; selp.u32 %0, 1, 0, q;}" : "=r"(p));
    return p;
}
__device__ __forceinline__ void tma2d(uint32_t dst, const CUtensorMap* m, uint32_t bar, int x, int y) {
    asm volatile(
        "cp.async.bulk.tensor.2d.shared::cluster.global.mbarrier::complete_tx::bytes [%0], [%1, {%3, %4}], [%2];" ::"r"(dst),
        "l"(m), "r"(bar), "r"(x), "r"(y)
        : "memory");
}
__device__ __forceinline__ void bulk(uint32_t dst, const void* src, uint32_t bytes, uint32_t bar) {
    asm volatile("cp.async.bulk.shared::cluster.global.mbarrier::complete_tx::bytes [%0], [%1], %2, [%3];" ::"r"(dst),
                 "l"(src), "r"(bytes), "r"(bar)
                 : "memory");
}
__device__ __forceinline__ void cp16(uint32_t dst, const void* src) {
    asm volatile("cp.async.cg.shared.global [%0], [%1], 16;" ::"r"(dst), "l"(src) : "memory");
}
__device__ __forceinline__ void lds128(uint32_t (&v)[4], uint32_t a) {
    asm volatile("ld.shared.v4.u32 {%0,%1,%2,%3}, [%4];" : "=r"(v[0]), "=r"(v[1]), "=r"(v[2]), "=r"(v[3]) : "r"(a) : "memory");
}
__device__ __forceinline__ void lds128_if(uint32_t (&v)[4], uint32_t a, uint32_t p) {
    asm volatile("{.reg .pred q; setp.ne.u32 q, %5, 0; @q ld.shared.v4.u32 {%0,%1,%2,%3}, [%4];}"
                 : "+r"(v[0]), "+r"(v[1]), "+r"(v[2]), "+r"(v[3])
                 : "r"(a), "r"(p)
                 : "memory");
}
__device__ __forceinline__ void lds64(uint32_t& x, uint32_t& y, uint32_t a) {
    asm volatile("ld.shared.v2.u32 {%0,%1}, [%2];" : "=r"(x), "=r"(y) : "r"(a) : "memory");
}
__device__ __forceinline__ void sts128(uint32_t a, uint32_t x, uint32_t y, uint32_t z, uint32_t w) {
    asm volatile("st.shared.v4.u32 [%0], {%1,%2,%3,%4};" ::"r"(a), "r"(x), "r"(y), "r"(z), "r"(w) : "memory");
}
__device__ __forceinline__ void sts64(uint32_t a, uint32_t x, uint32_t y) {
    asm volatile("st.shared.v2.u32 [%0], {%1,%2};" ::"r"(a), "r"(x), "r"(y) : "memory");
}
__device__ __forceinline__ uint32_t pack(float lo, float hi) {
    uint32_t r;
    asm volatile("cvt.rn.bf16x2.f32 %0, %1, %2;" : "=r"(r) : "f"(hi), "f"(lo));
    return r;
}
__device__ __forceinline__ uint32_t hmul2(uint32_t a, uint32_t b) {
    uint32_t r;
    asm volatile("mul.rn.bf16x2 %0, %1, %2;" : "=r"(r) : "r"(a), "r"(b));
    return r;
}
__device__ __forceinline__ uint32_t hfma2(uint32_t a, uint32_t b, uint32_t c) {
    uint32_t r;
    asm volatile("fma.rn.bf16x2 %0, %1, %2, %3;" : "=r"(r) : "r"(a), "r"(b), "r"(c));
    return r;
}
template <int H>
__device__ __forceinline__ uint32_t hfma2_bcast(uint32_t a, uint32_t x, uint32_t c) {
    uint32_t r;
    if (H)
        asm volatile("{.reg .b16 l, h; .reg .b32 s; mov.b32 {l, h}, %2; mov.b32 s, {h, h}; fma.rn.bf16x2 %0, %1, s, %3;}"
                     : "=r"(r)
                     : "r"(a), "r"(x), "r"(c));
    else
        asm volatile("{.reg .b16 l, h; .reg .b32 s; mov.b32 {l, h}, %2; mov.b32 s, {l, l}; fma.rn.bf16x2 %0, %1, s, %3;}"
                     : "=r"(r)
                     : "r"(a), "r"(x), "r"(c));
    return r;
}
__device__ __forceinline__ float ffma(float a, float b, float c) {
    float r;
    asm volatile("fma.rn.f32 %0, %1, %2, %3;" : "=f"(r) : "f"(a), "f"(b), "f"(c));
    return r;
}
__device__ __forceinline__ float tanh_fast(float x) {
    float r;
    asm volatile("tanh.approx.f32 %0, %1;" : "=f"(r) : "f"(x));
    return r;
}
__device__ __forceinline__ float gelu_tanh(float x) {
    float r;
    asm volatile(
        "{.reg .f32 a; mul.f32 a, %1, %1; fma.rn.f32 a, a, 0f3D122279, 0f3F4C422A; mul.f32 a, a, %1; tanh.approx.f32 %0, a;}"
        : "=f"(r)
        : "f"(x));
    return r;
}
__device__ __forceinline__ void mma16816(float (&d)[4], const uint32_t (&a)[4], uint32_t b0, uint32_t b1) {
    asm volatile("mma.sync.aligned.m16n8k16.row.col.f32.bf16.bf16.f32 {%0,%1,%2,%3}, {%4,%5,%6,%7}, {%8,%9}, {%0,%1,%2,%3};"
                 : "+f"(d[0]), "+f"(d[1]), "+f"(d[2]), "+f"(d[3])
                 : "r"(a[0]), "r"(a[1]), "r"(a[2]), "r"(a[3]), "r"(b0), "r"(b1));
}
__device__ __forceinline__ uint32_t clock32() {
    uint32_t c;
    asm volatile("mov.u32 %0, %%clock;" : "=r"(c)::"memory");
    return c;
}
#define WG_FENCE() asm volatile("wgmma.fence.sync.aligned;" ::: "memory")
#define WG_COMMIT() asm volatile("wgmma.commit_group.sync.aligned;" ::: "memory")
#define WG_WAIT0() asm volatile("wgmma.wait_group.sync.aligned 0;" ::: "memory")
#define WG_WAIT1() asm volatile("wgmma.wait_group.sync.aligned 1;" ::: "memory")
#define CP_COMMIT() asm volatile("cp.async.commit_group;" ::: "memory")
#define CP_WAIT(n) asm volatile("cp.async.wait_group %0;" ::"n"(n) : "memory")
#define SCHED_FENCE() asm volatile("pmevent 0;" ::: "memory")
#define PROXY_FENCE() asm volatile("fence.proxy.async.shared::cta;" ::: "memory")
template <int N>
__device__ __forceinline__ void pin(float (&d)[N]) {
#pragma unroll
    for (int i = 0; i < N; i++) asm volatile("" : "+f"(d[i])::"memory");
}
#define TS(k)
#define TS_DUMP(role)

__device__ __forceinline__ void wgmma_ss_n168_acc(float (&d)[84], uint64_t da, uint64_t db) {
    asm volatile(
        "wgmma.mma_async.sync.aligned.m64n168k16.f32.bf16.bf16 "
        "{%0,%1,%2,%3,%4,%5,%6,%7,%8,%9,%10,%11,%12,%13,%14,%15,"
        "%16,%17,%18,%19,%20,%21,%22,%23,%24,%25,%26,%27,%28,%29,%30,%31,"
        "%32,%33,%34,%35,%36,%37,%38,%39,%40,%41,%42,%43,%44,%45,%46,%47,"
        "%48,%49,%50,%51,%52,%53,%54,%55,%56,%57,%58,%59,%60,%61,%62,%63,"
        "%64,%65,%66,%67,%68,%69,%70,%71,%72,%73,%74,%75,%76,%77,%78,%79,"
        "%80,%81,%82,%83}, "
        "%84, %85, 1, 1, 1, 0, 1;"
        : "+f"(d[0]), "+f"(d[1]), "+f"(d[2]), "+f"(d[3]), "+f"(d[4]), "+f"(d[5]), "+f"(d[6]), "+f"(d[7]),
          "+f"(d[8]), "+f"(d[9]), "+f"(d[10]), "+f"(d[11]), "+f"(d[12]), "+f"(d[13]), "+f"(d[14]), "+f"(d[15]),
          "+f"(d[16]), "+f"(d[17]), "+f"(d[18]), "+f"(d[19]), "+f"(d[20]), "+f"(d[21]), "+f"(d[22]), "+f"(d[23]),
          "+f"(d[24]), "+f"(d[25]), "+f"(d[26]), "+f"(d[27]), "+f"(d[28]), "+f"(d[29]), "+f"(d[30]), "+f"(d[31]),
          "+f"(d[32]), "+f"(d[33]), "+f"(d[34]), "+f"(d[35]), "+f"(d[36]), "+f"(d[37]), "+f"(d[38]), "+f"(d[39]),
          "+f"(d[40]), "+f"(d[41]), "+f"(d[42]), "+f"(d[43]), "+f"(d[44]), "+f"(d[45]), "+f"(d[46]), "+f"(d[47]),
          "+f"(d[48]), "+f"(d[49]), "+f"(d[50]), "+f"(d[51]), "+f"(d[52]), "+f"(d[53]), "+f"(d[54]), "+f"(d[55]),
          "+f"(d[56]), "+f"(d[57]), "+f"(d[58]), "+f"(d[59]), "+f"(d[60]), "+f"(d[61]), "+f"(d[62]), "+f"(d[63]),
          "+f"(d[64]), "+f"(d[65]), "+f"(d[66]), "+f"(d[67]), "+f"(d[68]), "+f"(d[69]), "+f"(d[70]), "+f"(d[71]),
          "+f"(d[72]), "+f"(d[73]), "+f"(d[74]), "+f"(d[75]), "+f"(d[76]), "+f"(d[77]), "+f"(d[78]), "+f"(d[79]),
          "+f"(d[80]), "+f"(d[81]), "+f"(d[82]), "+f"(d[83])
        : "l"(da), "l"(db));
}

__device__ __forceinline__ void wgmma_rs_n32_set(float (&d)[16], const uint32_t (&a)[4], uint64_t db) {
    asm volatile(
        "wgmma.mma_async.sync.aligned.m64n32k16.f32.bf16.bf16 "
        "{%0,%1,%2,%3,%4,%5,%6,%7,%8,%9,%10,%11,%12,%13,%14,%15}, "
        "{%16,%17,%18,%19}, %20, 0, 1, 1, 0;"
        : "=f"(d[0]), "=f"(d[1]), "=f"(d[2]), "=f"(d[3]), "=f"(d[4]), "=f"(d[5]), "=f"(d[6]), "=f"(d[7]),
          "=f"(d[8]), "=f"(d[9]), "=f"(d[10]), "=f"(d[11]), "=f"(d[12]), "=f"(d[13]), "=f"(d[14]), "=f"(d[15])
        : "r"(a[0]), "r"(a[1]), "r"(a[2]), "r"(a[3]), "l"(db));
}

__device__ __forceinline__ void wgmma_rs_n32_acc(float (&d)[16], const uint32_t (&a)[4], uint64_t db) {
    asm volatile(
        "wgmma.mma_async.sync.aligned.m64n32k16.f32.bf16.bf16 "
        "{%0,%1,%2,%3,%4,%5,%6,%7,%8,%9,%10,%11,%12,%13,%14,%15}, "
        "{%16,%17,%18,%19}, %20, 1, 1, 1, 0;"
        : "+f"(d[0]), "+f"(d[1]), "+f"(d[2]), "+f"(d[3]), "+f"(d[4]), "+f"(d[5]), "+f"(d[6]), "+f"(d[7]),
          "+f"(d[8]), "+f"(d[9]), "+f"(d[10]), "+f"(d[11]), "+f"(d[12]), "+f"(d[13]), "+f"(d[14]), "+f"(d[15])
        : "r"(a[0]), "r"(a[1]), "r"(a[2]), "r"(a[3]), "l"(db));
}

__device__ __forceinline__ void wgmma_rs_n16_set(float (&d)[8], const uint32_t (&a)[4], uint64_t db) {
    asm volatile(
        "wgmma.mma_async.sync.aligned.m64n16k16.f32.bf16.bf16 "
        "{%0,%1,%2,%3,%4,%5,%6,%7}, "
        "{%8,%9,%10,%11}, %12, 0, 1, 1, 0;"
        : "=f"(d[0]), "=f"(d[1]), "=f"(d[2]), "=f"(d[3]), "=f"(d[4]), "=f"(d[5]), "=f"(d[6]), "=f"(d[7])
        : "r"(a[0]), "r"(a[1]), "r"(a[2]), "r"(a[3]), "l"(db));
}

__device__ __forceinline__ void wgmma_rs_n16_acc(float (&d)[8], const uint32_t (&a)[4], uint64_t db) {
    asm volatile(
        "wgmma.mma_async.sync.aligned.m64n16k16.f32.bf16.bf16 "
        "{%0,%1,%2,%3,%4,%5,%6,%7}, "
        "{%8,%9,%10,%11}, %12, 1, 1, 1, 0;"
        : "+f"(d[0]), "+f"(d[1]), "+f"(d[2]), "+f"(d[3]), "+f"(d[4]), "+f"(d[5]), "+f"(d[6]), "+f"(d[7])
        : "r"(a[0]), "r"(a[1]), "r"(a[2]), "r"(a[3]), "l"(db));
}

__device__ __forceinline__ void wgmma_rs_n32_pred(float (&d)[16], const uint32_t (&a)[4], uint64_t db, uint32_t scale_d) {
    asm volatile(
        "{.reg .pred p; setp.ne.u32 p, %21, 0; wgmma.mma_async.sync.aligned.m64n32k16.f32.bf16.bf16 "
        "{%0,%1,%2,%3,%4,%5,%6,%7,%8,%9,%10,%11,%12,%13,%14,%15}, "
        "{%16,%17,%18,%19}, %20, p, 1, 1, 0;}"
        : "+f"(d[0]), "+f"(d[1]), "+f"(d[2]), "+f"(d[3]), "+f"(d[4]), "+f"(d[5]), "+f"(d[6]), "+f"(d[7]),
          "+f"(d[8]), "+f"(d[9]), "+f"(d[10]), "+f"(d[11]), "+f"(d[12]), "+f"(d[13]), "+f"(d[14]), "+f"(d[15])
        : "r"(a[0]), "r"(a[1]), "r"(a[2]), "r"(a[3]), "l"(db), "r"(scale_d));
}

__device__ __forceinline__ void prep_cta(uint32_t sb, int c, const __nv_bfloat16* __restrict__ wc,
                                         const __nv_bfloat16* __restrict__ se1, const __nv_bfloat16* __restrict__ se2) {
    const int tid = threadIdx.x, lane = tid & 31, warp = tid >> 5;
    constexpr int NROW = 2 * NF * NF;
#pragma unroll
    for (int q = tid; q < NROW * 2; q += 384) cp16(sb + q * 16, wc + (q >> 1) * ND + c * 16 + (q & 1) * 8);
    if (tid == 0) sts128(sb + NROW * 32, 0, 0, 0, 0);
    if (tid < 256) {
        const int l2 = c >> 1, n = ((tid >> 2) & 1) * 8 + (tid >> 5) + (l2 ? (c & 1) * 16 : 0);
        const int k = ((tid >> 1) & 1) * 8 + ((tid >> 3) & 3) * 2 + (tid & 1), mm = k >> 1, u = k & 1;
        const int f = l2 ? fmap(n) : mm < 6 ? 4 * mm + 2 * c + u : (mm == 6 && u == 0) ? 24 + c : -1;
        float v = 0.f;
        if (f >= 0 && (l2 ? k : n) < NR) v = __bfloat162float(l2 ? se2[k * NF + f] : se1[f * NR + n]);
        reinterpret_cast<__nv_bfloat16*>(g_se)[c * 256 + tid] = __float2bfloat16(l2 ? 0.5f * v : v);
    }
    asm volatile("cp.async.wait_all;" ::: "memory");
    __syncthreads();
    const int k = 4 * (lane & 6) + 2 * (lane >> 3) + (lane & 1), i = fmap(k);
    const int g = lane >> 2, t = lane & 3;
#pragma unroll 4
    for (int task = warp; task < 128; task += 12) {
        const int eg = task & 1, n = (task >> 1) & 31, s = task >> 6;
        const int j = fmap(n ^ s);
        const uint32_t a = k < 28 ? sb + ((s * NF + i) * NF + j) * 32 + eg * 16 : sb + NROW * 32;
        uint4 v;
        asm volatile("ldmatrix.sync.aligned.m8n8.x4.trans.shared.b16 {%0,%1,%2,%3}, [%4];"
                     : "=r"(v.x), "=r"(v.y), "=r"(v.z), "=r"(v.w)
                     : "r"(a));
        const int e = eg * 8 + g;
        if (t == 3) {
            const uint32_t mask = eg ? 0xffff0000u : 0xffffu;
            v.x &= mask;
            v.y &= mask;
        }
        const int ch = (t < 2 ? t ^ ((e >> 1) & 1) : t) ^ ((n >> 1) & 3);
        g_wc[(c >> 1) * 8192 + ((g & 1) + 2 * eg + 2 * (g & 6)) * 512 + (c & 1) * 256 + s * 128 + n * 4 + ch] = v;
    }
    __threadfence();
    __syncthreads();
    if (tid == 0) atomicAdd(&g_ready, 1u);
}

#define TWARM 7
#define WPF_STEP 800
#define WDELAY 1600
#define WSTEP 500
#define START_MIN 3300
#define DB0 6
#define T_SHIFT 300
#define DBASE (mkdesc(sb + w * 4096, 16, 512, 2) + ((uint64_t)zero << 32))
#define PACE1 2100
#define PACE2 2700
#define PF_START 2600
#define PF_PACE 550
#define WPF_AT 3000

__global__ void __cluster_dims__(2, 1, 1) __launch_bounds__(384, 1)
fibinet_kernel(const int* __restrict__ idx, const uint4* __restrict__ table,
               const __nv_bfloat16* __restrict__ se1, const __nv_bfloat16* __restrict__ se2,
               const __nv_bfloat16* __restrict__ wc,
               const unsigned char* __restrict__ w1, const __nv_bfloat16* __restrict__ w2, __nv_bfloat16* __restrict__ out,
               const __grid_constant__ CUtensorMap tm_w1, const __grid_constant__ CUtensorMap tm_bi) {
    extern __shared__ __align__(1024) unsigned char smem[];
    const int tid = threadIdx.x;
    const int cta = blockIdx.x - NPREP, grp = cta >> 1, rank = cta & 1, lane = tid & 31;
    uint32_t ids[13][4], cid[3][2];
    const uint32_t idle = (tid >> 8) | (cta < 0);
    const uint32_t row = ((tid >> 5) & 3) * 16 + (lane >> 3);
    const unsigned char* ib = reinterpret_cast<const unsigned char*>(idx) + (int64_t)grp * (64 * NF * 4);
    {
        const unsigned char* ip = ib + (row * (NF * 4) + ((tid >> 4) & 8));
#pragma unroll
        for (int u = 0; u < 4; u++) {
            ids[0][u] = ids[1][u] = 0;
            asm volatile("{.reg .pred p; setp.eq.u32 p, %3, 0; @p ld.global.nc.L2::128B.v2.u32 {%0,%1}, [%2];}"
                         : "+r"(ids[0][u]), "+r"(ids[1][u])
                         : "l"(ip + 16 * NF * u), "r"(idle));
        }
    }
    const uint32_t t_0 = clock32();
    {
        const uint32_t co = ((tid & 127) >> 1) * (NF * 4) + ((tid >> 4) & 8) + 16 + 16 * (tid & 1);
#pragma unroll
        for (int k = 0; k < 3; k++) {
            cid[k][0] = cid[k][1] = 0;
            asm volatile("{.reg .pred p; setp.eq.u32 p, %3, 0; @p ld.global.nc.v2.u32 {%0,%1}, [%2];}"
                         : "+r"(cid[k][0]), "+r"(cid[k][1])
                         : "l"(ib + (co + 32 * k - (k == 2 ? 8 * ((tid >> 7) & tid & 1) : 0))), "r"(idle));
        }
    }
    const uint32_t t_start = (t_0 ^ (clock32() & blockIdx.y)) - T_SHIFT;
    const uint32_t sb = (uint32_t)__cvta_generic_to_shared(smem);
    uint32_t gd0 = sb + (tid >> 7) * XDELTA + row * 128 + (((lane & 7) ^ (lane >> 3) ^ ((tid >> 5) & 4)) << 4);
    const uint4* tp = table + (lane & 7);
    auto gather = [&](int i) {
#pragma unroll
        for (int u = 0; u < 4; u++)
            asm volatile(
                "{.reg .u64 a; .reg .pred p; setp.eq.u32 p, %3, 0; mad.wide.u32 a, %2, 128, %1; @p cp.async.cg.shared.global [%0], [a], 16;}" ::"r"(
                    (gd0 ^ ((u & 1) * 64)) + xpair(i) + u * 512),
                "l"(tp), "r"(ids[i][u]), "r"(i == 0 ? idle : 0u)
                : "memory");
        CP_COMMIT();
    };
    gather(0);
    if (cta < 0) {
        prep_cta(sb, blockIdx.x, wc, se1, se2);
        return;
    }
    if (tid == 288) asm volatile("prefetch.tensormap [%0];" ::"l"(&tm_w1));
    const int warp = __reduce_max_sync(0xffffffffu, tid >> 5);
    const int w = warp >> 2;

    if (w == 2) {
        asm volatile("setmaxnreg.dec.sync.aligned.u32 40;");
        auto load_wc = [&](int gi) {
            if (elect()) {
                const unsigned char* src = reinterpret_cast<const unsigned char*>(g_wc) + rank * 131072;
                mbar_expect(sb + BAR_WC + gi * 8, (wcfirst(gi + 1) - wcfirst(gi)) * 8192);
#pragma unroll
                for (int c = wcfirst(gi); c < wcfirst(gi + 1); c++) bulk(sb + wcslot(c), src + c * 8192, 8192, sb + BAR_WC + gi * 8);
            }
            __syncwarp();
        };
        if (warp == 8) {
            if (elect()) {
                mbar_init(sb + BAR_Z, 1);
                mbar_expect(sb + BAR_Z, 8192);
                tma2d(sb + ZOFF, &tm_bi, sb + BAR_Z, 32 * rank, 0);
            }
#pragma unroll
            for (int f = 0; f < 26; f++) {
                if (f == 2) {
                    if (elect()) {
#pragma unroll
                        for (int k = 2; k < 8; k++) mbar_init(sb + BAR_FULL + k * 8, 1);
                        asm volatile("fence.mbarrier_init.release.cluster;" ::: "memory");
                    }
                    __syncwarp();
                    asm volatile("barrier.cluster.arrive.relaxed.aligned;" ::: "memory");
                    mbar_wait(sb + BAR_Z);
#pragma unroll
                    for (int k = 0; k < 2; k++)
                        sts128(sb + ZOFF + (k * 32 + lane) * 128 + ((4 ^ (lane & 7)) << 4), 0x3c803c80u, 0x3c803c80u, 0x3c803c80u, 0x3c803c80u);
                    PROXY_FENCE();
                    asm volatile("bar.arrive 0, 384;" ::: "memory");
                    TS(31);
                }
                if (f == 5) asm volatile("bar.sync 7, 64;" ::: "memory");
                if (f >= 5) mbar_wait(sb + bdone(f - 5), bpar(f - 5));
                if (f >= 2 && f < 5)
                    while (clock32() - t_start < WDELAY + (f - 2) * WSTEP) {
                    }
                if (elect()) {
                    if (f < 2) mbar_init(sb + BAR_FULL + f * 8, 1);
                    mbar_expect(sb + bfull(f), 16384);
                    tma2d(sb + slot(2 * wl(f)), &tm_w1, sb + bfull(f), 128 * rank + 64 * (f & 1), fieldof(f) * 64);
                    tma2d(sb + slot(wl(f)), &tm_w1, sb + bfull(f), 128 * rank + 64 - 64 * (f & 1), fieldof(f) * 64);
                }
                TS(f);
            }
            if (elect()) mbar_arrive(sb + BAR_GO);
            TS_DUMP(2);
        } else if (warp == 9) {
            if (elect()) {
#pragma unroll
                for (int k = 0; k < 11; k++) mbar_init(sb + BAR_WC + k * 8, k < 10 ? 1 : 8);
                asm volatile("fence.mbarrier_init.release.cluster;" ::: "memory");
            }
            __syncwarp();
            asm volatile("barrier.cluster.arrive.relaxed.aligned;" ::: "memory");
            asm volatile("bar.sync 0, 384;" ::: "memory");
            mbar_wait(sb + bdone(3), bpar(3));
            if (elect()) {
                unsigned v, it = 0;
                do {
                    asm volatile("ld.acquire.gpu.global.u32 %0, [%1];" : "=r"(v) : "l"(&g_ready) : "memory");
                } while (v < NPREP && ++it < 4000000u);
                asm volatile("fence.proxy.async.global;" ::: "memory");
                mbar_expect(sb + BAR_SE, 2048);
                bulk(sb + SEOFF, g_se, 2048, sb + BAR_SE);
                if (atomicAdd(&g_seen, 1u) == NMAIN - 1) {
                    g_seen = 0;
                    g_ready = 0;
                }
            }
            __syncwarp();
            TS(0);
            mbar_wait(sb + BAR_GO);
#pragma unroll
            for (int gi = 0; gi < 3; gi++) {
                mbar_wait(sb + bdone(21 + gi), bpar(21 + gi));
                load_wc(gi);
                TS(1 + gi);
            }
        } else if (warp == 10) {
            if (elect()) {
#pragma unroll
                for (int k = 0; k < 8; k++) mbar_init(sb + BAR_DONE + k * 8, 4);
                asm volatile("fence.mbarrier_init.release.cluster;" ::: "memory");
            }
            __syncwarp();
            asm volatile("barrier.cluster.arrive.relaxed.aligned;" ::: "memory");
            asm volatile("bar.arrive 7, 64;" ::: "memory");
            asm volatile("bar.sync 0, 384;" ::: "memory");
#pragma unroll 1
            for (int k = 0; k < 7; k++) {
                while (clock32() - t_start < (uint32_t)(WPF_AT + k * WPF_STEP)) __nanosleep(20);
                if (lane < 6)
                    asm volatile("prefetch.global.L2 [%0];" ::"l"(w1 + (5 + k * 3 + (lane >> 1)) * 32768 + cta * 256 + (lane & 1) * 128));
            }
        } else {
            asm volatile("bar.sync 0, 384;" ::: "memory");
            const uint2 v = __ldg(reinterpret_cast<const uint2*>(w2 + 128 * rank) + lane);
#pragma unroll
            for (int k = 0; k < 2; k++) {
                const uint32_t x = k ? v.y : v.x;
                sts64(sb + w2chunk((lane >> 2) * 4 + 2 * (lane & 1) + k) + (lane & 2) * 4,
                      __float_as_uint(0.5f * __uint_as_float(x << 16)), __float_as_uint(0.5f * __uint_as_float(x & 0xffff0000u)));
            }
            __syncwarp();
            if (lane == 0) mbar_arrive(sb + BAR_W2);
            if (lane < 16) reinterpret_cast<uint32_t*>(out)[cta * 16 + lane] = 0;
            asm volatile("barrier.cluster.arrive.release.aligned;" ::: "memory");
        }
        {
            uint32_t bw[2][4], z0[4], z1[4];
            mbar_wait(sb + BAR_SE);
            lds128(bw[0], sb + SEOFF + lane * 16);
            lds128(bw[1], sb + SEOFF + 512 + lane * 16);
            asm volatile("bar.sync 2, 384;" ::: "memory");
            lds128(z0, sb + ZQOFF + (tid & 127) * 16);
            lds128(z1, sb + ZQOFF + 2048 + (tid & 127) * 16);
            TS(8);
            float s[2][4] = {};
#pragma unroll
            for (int n = 0; n < 2; n++) {
                mma16816(s[n], z0, bw[0][2 * n], bw[0][2 * n + 1]);
                mma16816(s[n], z1, bw[1][2 * n], bw[1][2 * n + 1]);
            }
            lds128(bw[0], sb + SEOFF + 1024 + lane * 16);
            lds128(bw[1], sb + SEOFF + 1536 + lane * 16);
            float th[8];
#pragma unroll
            for (int k = 0; k < 8; k++) th[k] = gelu_tanh(s[k >> 2][k & 3]);
            SCHED_FENCE();
            TS(9);
            uint32_t gq[4];
#pragma unroll
            for (int k = 0; k < 4; k++)
                gq[k] = pack(s[k >> 1][2 * (k & 1)] * ffma(th[2 * k], 0.5f, 0.5f), s[k >> 1][2 * (k & 1) + 1] * ffma(th[2 * k + 1], 0.5f, 0.5f));
            float a[4][4] = {};
#pragma unroll
            for (int n = 0; n < 4; n++) mma16816(a[n], gq, bw[n >> 1][2 * (n & 1)], bw[n >> 1][2 * (n & 1) + 1]);
#pragma unroll
            for (int k = 0; k < 16; k++)
                if (k < 13 || k == 14) a[k >> 2][k & 3] = tanh_fast(a[k >> 2][k & 3]);
            SCHED_FENCE();
            TS(10);
            uint32_t ap[8];
#pragma unroll
            for (int k = 0; k < 8; k++)
                ap[k] = pack(ffma(a[k >> 1][2 * (k & 1)], 0.5f, 0.5f), ffma(a[k >> 1][2 * (k & 1) + (k < 6)], 0.5f, 0.5f));
            sts128(sb + GOFF + (tid & 127) * 16, ap[0], ap[1], ap[2], ap[3]);
            sts128(sb + GOFF + 2048 + (tid & 127) * 16, ap[4], ap[5], ap[6], ap[7]);
            asm volatile("bar.arrive 3, 384;" ::: "memory");
            TS(11);
        }
        if (warp == 9) {
            load_wc(3);
            load_wc(4);
            mbar_wait(sb + BAR_TD);
            load_wc(5);
            if (lane < 16) TS_DUMP(3);
        } else if (warp == 10) {
            uint32_t* dst = reinterpret_cast<uint32_t*>(out) + grp * 32 + lane;
            asm volatile("barrier.cluster.wait.acquire.aligned;" : "+l"(dst)::"memory");
            SCHED_FENCE();
            asm volatile("bar.sync 4, 288;" ::: "memory");
            uint32_t p[4];
            lds64(p[0], p[1], sb + PARTOFF + lane * 8);
            lds64(p[2], p[3], sb + PARTOFF + 256 + lane * 8);
            asm volatile("red.relaxed.gpu.global.add.noftz.bf16x2 [%0], %1;" ::"l"(dst),
                         "r"(pack(__uint_as_float(p[0]) + __uint_as_float(p[2]), __uint_as_float(p[1]) + __uint_as_float(p[3])))
                         : "memory");
        }
    } else {
        asm volatile("setmaxnreg.inc.sync.aligned.u32 232;");
        asm volatile("barrier.cluster.arrive.relaxed.aligned;" ::: "memory");
        const int g = lane >> 2, t = lane & 3, wq = warp & 3, t128 = tid & 127;
        gd0 = opaque(gd0);
        TS(28);
        float acc[84];
#pragma unroll
        for (int k = 0; k < 84; k++) asm volatile("mov.b32 %0, 0;" : "=f"(acc[k]));
        uint32_t e0[9], e1[9], e2[9];
        uint32_t X[13][2][4];
        uint32_t zq[4] = {0, 0, 0, 0};
        const uint64_t dA = mkdesc(sb + w * XDELTA, 16, 1024, 1);
        uint32_t dBlo = (uint32_t)mkdesc(sb + ZOFF, 0, 0, 0);
        const uint32_t xl0 = opaque(sb + (t & 1) * XDELTA + (16 * wq + g) * 128 + (((4 * rank + 2 * w) ^ (4 * (t & 1)) ^ g) << 4));
        const uint32_t hi_half = t >> 1;
        const uint32_t sa0 = opaque(sb + AOFF + t * 4096 + (t >> 1) * 16 + (wq * 32 + g * 4 + w) * 16);
        const uint32_t sa1 = opaque(((g & 2) << 4) | ((t & 1) << 3));
        const uint32_t zero = blockIdx.y;
        auto expand = [&](int k0, int k1) {
#pragma unroll
            for (int k = k0; k < k1; k++)
#pragma unroll
                for (int u = 0; u < 4; u++)
                    asm volatile("shfl.sync.idx.b32 %0, %1, %2, 31, 0xffffffff;"
                                 : "=r"(ids[k][u])
                                 : "r"(k < 12 ? cid[(k - 2) >> 2][k & 1] : w ? cid[2][1] : cid[2][0]),
                                   "r"(2 * (lane >> 3) + 8 * u + (((k - 2) >> 1) & 1)));
        };
        auto twarm = [&]() {
            float s1[8];
            WG_FENCE();
            wgmma_rs_n16_set(s1, zq, mkdesc(sb + AOFF, 16, 512, 2));
            WG_COMMIT();
            WG_WAIT0();
            pin(s1);
            asm volatile("{.reg .pred p; setp.ne.u32 p, %1, 0; @p st.shared.f32 [%1], %0;}" ::"f"(s1[0]), "r"(zero));
        };
        expand(2, 8);
        if (TWARM & 1) twarm();
        TS(26);
        while (clock32() - t_start < PACE1) {
        }
        gather(1);
        expand(8, 13);
        if (TWARM & 2) twarm();
        TS(30);
        while (clock32() - t_start < PACE2) {
        }
        gather(2);
        if (TWARM & 4) twarm();
        asm volatile("bar.sync 0, 384;" ::: "memory");
        auto lift = [&](int i) {
            const int m = 2 * (i >> 2) + (i & 1);
#pragma unroll
            for (int r = 0; r < (i < 12 ? 2 : 1); r++)
#pragma unroll
                for (int cc = 0; cc < 2; cc++) {
                    const uint32_t a = (xl0 ^ (cc * 16)) + xpair(i) + (i < 12 ? r : hi_half) * 1024;
                    if (i & 2) lds128_if(X[2 * m + r][cc], a, hi_half);
                    else lds128(X[2 * m + r][cc], a);
                }
        };
        auto store_pair = [&](int m, int half, const uint32_t (&ea)[9]) {
            uint32_t a;
            if (m < 4) a = sa0 + (sa1 ^ (((m & 1) << 5) | ((m >> 1) << 3)));
            else a = sb + BOFF + t * 2048 + (wq * 32 + g * 4 + ((2 * (m & 1) + w) ^ t)) * 8;
#pragma unroll
            for (int n = half; n < 4; n += 2)
#pragma unroll
                for (int u = 0; u < 2; u++)
                    sts64(a + (m < 4 ? (8 * n + u) * 2048 + n * 32 : (8 * n + u) * 1024),
                          __byte_perm(ea[2 * n], e1[2 * n], u ? 0x7632 : 0x5410),
                          __byte_perm(ea[2 * n + 1], e1[2 * n + 1], u ? 0x7632 : 0x5410));
        };
        auto z_pair = [&](int m, uint32_t a, uint32_t b) {
            asm volatile("{.reg .pred p; setp.eq.u32 p, %4, %5; @p prmt.b32 %0, %2, %3, 0x5410; @p prmt.b32 %1, %2, %3, 0x7632;}"
                         : "+r"(zq[2 * (m >> 2)]), "+r"(zq[2 * (m >> 2) + 1])
                         : "r"(a), "r"(b), "r"(t), "r"(m & 3));
        };

        TS(29);
        mbar_wait(sb + BAR_FULL + w * 8);
        CP_WAIT(2);
        while (clock32() - t_start < START_MIN) {
        }
        if (w == 1) {
            asm volatile("bar.arrive 6, 256;" ::: "memory");
            asm volatile("bar.sync 5, 256;" ::: "memory");
        }
#pragma unroll
        for (int i = 0; i < 13; i++) {
            const uint64_t da = dA + (xpair(i) >> 4) + ((uint64_t)i << 16);
            dBlo += (uint32_t)(w ? wl(2 * i + 1) - (i ? wl(2 * i - 1) : 0) : wl(2 * i) - (i ? wl(2 * i - 2) : 0)) *
                    (uint32_t)((SLOT << 12) - (SLOT >> 3));
            const uint64_t db = mkdesc(0, 0, 1024, 1) | dBlo;
            TS(i);
            WG_FENCE();
            wgmma_ss_n168_acc(acc, da, db + w * 256);
            wgmma_ss_n168_acc(acc, da + 2, db + w * 256 + 128);
            wgmma_ss_n168_acc(acc, da + 4, db + (w ^ 1) * 256);
            wgmma_ss_n168_acc(acc, da + 6, db + (w ^ 1) * 256 + 128);
            WG_COMMIT();
            if (i == 0) {
                if (w == 0) {
                    asm volatile("bar.arrive 5, 256;" ::: "memory");
                    asm volatile("bar.sync 6, 256;" ::: "memory");
                }
            } else {
                mbar_wait(sb + bdone(2 * i - 2) + (w ^ 1) * 8, bpar(2 * i - 2));
            }
            if (i < 10) gather(i + 3);
            if (i == 6) mbar_wait(sb + BAR_W2);
            lift(i);
            if (i == 10 || i == 11) mbar_wait(sb + bdone(2 * i - 2) + w * 8, bpar(2 * i - 2));
            if (i >= 2 && !(i & 1)) {
                z_pair((i - 2) >> 1, e0[8], e1[8]);
                store_pair((i - 2) >> 1, 0, e0);
#pragma unroll
                for (int k = 0; k < 8; k++) e2[k] = e0[k];
            } else if (i >= 3) {
                store_pair((i - 3) >> 1, 1, e2);
            }
            const uint32_t rdy = i < 12 ? mbar_test(sb + bfull(2 * i + 2) + w * 8, bpar(2 * i + 2)) : 0;
            WG_WAIT0();
            pin(acc);
            if (i == 12) TS(13);
            if (i == 0) TS(27);
            if (i < 10) CP_WAIT(2);
            else if (i == 10) CP_WAIT(1);
            else if (i == 11) CP_WAIT(0);
            if (i < 12 && lane == 0) mbar_arrive(sb + bdone(2 * i) + w * 8);
#pragma unroll
            for (int k = 0; k < 9; k++) {
                const int k0 = 64 + 2 * (k & 5) + ((k >> 1) & 1);
                const uint32_t v = k == 8 ? pack(acc[80], acc[82]) : i < 12 ? pack(acc[64 + 2 * k], acc[65 + 2 * k]) : pack(acc[k0], acc[k0 + 4]);
                if (i & 1) e1[k] = v;
                else e0[k] = v;
            }
            if (i < 12) {
#pragma unroll
                for (int k = 64; k < 83; k++)
                    if (k != 81) asm volatile("mov.b32 %0, %1;" : "+f"(acc[k]) : "r"(zero));
                mbar_wait_unless(rdy, sb + bfull(2 * i + 2) + w * 8, bpar(2 * i + 2));
            } else {
                z_pair(6, e0[8], 0);
                sts128(sb + ZQOFF + w * 2048 + t128 * 16, zq[0], zq[1], zq[2], zq[3]);
                asm volatile("bar.arrive 2, 384;" ::: "memory");
            }
        }
        TS(14);

        uint32_t ai[8];
        float sum0 = 0.f, sum1 = 0.f;
        float th[32];
        uint32_t hw[4][4];
        auto deep_issue = [&](int k2) {
            lds128(hw[k2], ((sb + w2chunk(w * 16 + t)) ^ ((k2 & 1) * 64)) + k2 * 512);
#pragma unroll
            for (int k = 8 * k2; k < 8 * k2 + 8; k++) th[k] = gelu_tanh(acc[k]);
        };
        auto deep_use = [&](int k2) {
#pragma unroll
            for (int k = 8 * k2; k < 8 * k2 + 8; k++) {
                const float h = __uint_as_float(hw[k2][((k >> 1) & 2) + (k & 1)]);
                const float y = ffma(th[k], h, h);
                if (k & 2) sum1 = ffma(acc[k], y, sum1);
                else sum0 = ffma(acc[k], y, sum0);
            }
        };
        auto deep_send = [&](int k0, int k1) {
#pragma unroll
            for (int k = k0; k < k1; k++)
                sts128(sb + EXOFF + w * SLOT + t128 * 16 + k * 2048, pack(acc[32 + 8 * k], acc[33 + 8 * k]),
                       pack(acc[34 + 8 * k], acc[35 + 8 * k]), pack(acc[36 + 8 * k], acc[37 + 8 * k]), pack(acc[38 + 8 * k], acc[39 + 8 * k]));
        };
        uint32_t o[4][4];
        auto deep_recv = [&](int k0, int k1) {
#pragma unroll
            for (int k = k0; k < k1; k++) lds128(o[k], sb + EXOFF + (w ^ 1) * SLOT + t128 * 16 + k * 2048);
        };
        auto deep_add = [&](int k0, int k1) {
            const uint32_t eye = (g >> 1) == t ? ((g & 1) ? 0x3f800000u : 0x3f80u) : 0u;
#pragma unroll
            for (int k = 2 * k0; k < 2 * k1; k++)
                asm volatile("mma.sync.aligned.m16n8k8.row.col.f32.bf16.bf16.f32 {%0,%1,%2,%3}, {%4,%5}, {%6}, {%0,%1,%2,%3};"
                             : "+f"(acc[4 * k]), "+f"(acc[4 * k + 1]), "+f"(acc[4 * k + 2]), "+f"(acc[4 * k + 3])
                             : "r"(o[k >> 1][2 * (k & 1)]), "r"(o[k >> 1][2 * (k & 1) + 1]), "r"(eye));
        };
        auto store_last = [&]() {
#pragma unroll
            for (int n = 0; n < 4; n++) sts64(sb + COFF + w * 4096 + n * 1024 + (t128 ^ w) * 8, e0[2 * n], e0[2 * n + 1]);
            store_pair(5, 1, e2);
        };
        const uint32_t la = sb + AOFF + w * (16 * 2048 + 64) + (wq * 32 + g * 4 + (t ^ (g & 2))) * 16;
        const uint32_t lb = sb + BOFF + w * (16 * 1024) + t128 * 8;
        const uint32_t lc0 = sb + COFF + (t & 1) * (4096 + 8) + w * 2048 + (wq * 8 + g) * 32, lc1 = lc0 ^ 8;
        uint32_t Ap[2][2][4];
        auto load_a = [&](int s) {
            const int e = estep(s);
            lds128(Ap[s & 1][0], la + e * 2048 + (e >> 2) * 16);
            lds64(Ap[s & 1][1][0], Ap[s & 1][1][1], (lb ^ ((e & 6) * 4)) + e * 1024);
            if (!(s & 2)) lds64(Ap[s & 1][1][2], Ap[s & 1][1][3], ((e & 2) ? lc1 : lc0) + (e & 1) * 1024 + (e & 4) * 4);
        };
        {
            uint32_t v[2][4];
            deep_send(0, 2);
            asm volatile("bar.sync 1, 256;" ::: "memory");
            deep_recv(0, 2);
            deep_send(2, 4);
            TS(15);
            deep_add(0, 2);
            deep_issue(0);
            asm volatile("bar.sync 1, 256;" ::: "memory");
            deep_recv(2, 4);
            SCHED_FENCE();
            deep_add(2, 4);
            TS(16);
            deep_issue(1);
            deep_use(0);
            store_last();
            SCHED_FENCE();
            TS(17);
            deep_issue(2);
            deep_use(1);
            mbar_wait(sb + BAR_WC);
            deep_use(2);
            TS(18);
            asm volatile("bar.sync 3, 384;" ::: "memory");
            lds128(v[0], sb + GOFF + t128 * 16);
            lds128(v[1], sb + GOFF + 2048 + t128 * 16);
            load_a(0);
            load_a(1);
            deep_issue(3);
#pragma unroll
            for (int k = 0; k < 8; k++) ai[k] = v[k >> 2][k & 3];
        }
        TS(19);

        uint32_t fin_a, dsum[2];
        {
            uint64_t dW[4];
#pragma unroll
            for (int k = 0; k < 4; k++) dW[k] = DBASE + (wcslot(0) >> 4) + (k >> 1) * 128 + (k & 1) * 2;
            uint32_t Aq[2][2][4], pq[13], gate[13];
            float S[2][2][16];
            auto scale_a = [&](int s) {
#pragma unroll
                for (int k = 0; k < ((s & 2) ? 6 : 8); k++)
                    Aq[s & 1][k >> 2][k & 3] = hmul2(Ap[s & 1][k >> 2][k & 3], ai[k < 4 ? k ^ (estep(s) & 2) : k]);
            };
            auto sbuf = [](int s) { return s <= DB0 ? 0 : (s - DB0) & 1; };
            auto issue = [&](int s) {
                const bool first = s == 0 || s == DB0 + 1;
                WG_FENCE();
                if (first) wgmma_rs_n32_set(S[sbuf(s)][0], Ap[s & 1][0], dW[0]);
                else wgmma_rs_n32_pred(S[sbuf(s)][0], Ap[s & 1][0], dW[0], zero);
                wgmma_rs_n32_acc(S[sbuf(s)][0], Ap[s & 1][1], dW[1]);
                if (first) wgmma_rs_n32_set(S[sbuf(s)][1], Aq[s & 1][0], dW[2]);
                else wgmma_rs_n32_pred(S[sbuf(s)][1], Aq[s & 1][0], dW[2], zero);
                wgmma_rs_n32_acc(S[sbuf(s)][1], Aq[s & 1][1], dW[3]);
                WG_COMMIT();
                if (s < 15) {
#pragma unroll
                    for (int k = 0; k < 4; k++)
                        asm volatile("add.s64 %0, %0, %1;" : "+l"(dW[k]) : "l"((int64_t)((wcslot(s + 1) - wcslot(s)) / 16)));
                }
            };
            scale_a(0);
            issue(0);
            SCHED_FENCE();
            deep_use(3);
            scale_a(1);
            mbar_wait(sb + BAR_WC + 8);
#pragma unroll
            for (int e = 0; e < 16; e++) {
                if (e >= DB0 && e < 15) {
                    issue(e + 1);
                    WG_WAIT1();
                } else {
                    WG_WAIT0();
                }
                pin(S[sbuf(e)][0]);
                pin(S[sbuf(e)][1]);
                if (e == 0 && lane == 0) mbar_arrive(sb + BAR_TD);
                if (e == 0) TS(20);
                if (e + 2 < 16) load_a(e + 2);
                uint32_t v[13];
                auto accum = [&](int q) {
                    const uint32_t x = X[q][(e >> 1) & 1][e >> 2];
                    pq[q] = (e & 1) ? hfma2_bcast<1>(v[q], x, pq[q]) : hfma2_bcast<0>(v[q], x, e ? pq[q] : 0u);
                };
#pragma unroll
                for (int q = 0; q < 13; q++) {
                    const int ix = 4 * (q >> 2) + 2 * (q & 1) + ((q >> 1) & 1);
                    v[q] = pack(S[sbuf(e)][0][ix], S[sbuf(e)][1][ix ^ 1]);
                    if (q == 12)
                        asm volatile("{.reg .pred p; setp.ne.u32 p, %3, 0; @p cvt.rn.bf16x2.f32 %0, %2, %1;}"
                                     : "+r"(v[q])
                                     : "f"(S[sbuf(e)][0][14]), "f"(S[sbuf(e)][1][15]), "r"(hi_half));
                    if (e >= DB0 || q < 7) accum(q);
                }
                if (e < DB0) {
                    issue(e + 1);
                    SCHED_FENCE();
#pragma unroll
                    for (int q = 7; q < 13; q++) accum(q);
                }
                if (e == 3) {
                    const float h0 = __uint_as_float(__float_as_uint(sum0) & 0xffff0000u);
                    const float h1 = __uint_as_float(__float_as_uint(sum1) & 0xffff0000u);
                    dsum[0] = pack(sum0 - h0, h0);
                    dsum[1] = pack(sum1 - h1, h1);
                }
                if (e == 13) {
                    fin_a = opaque(sb + PARTOFF + (warp * 16 + g) * 4);
                }
                if (e == 14) {
#pragma unroll
                    for (int q = 0; q < 13; q++)
                        asm volatile("prmt.b32 %0, %1, 0x3f80, %2;"
                                     : "=r"(gate[q])
                                     : "r"(q < 12 ? ai[2 * (q >> 2) + (q & 1)] : hi_half ? ai[7] : ai[6]), "r"((q & 2) ? 0x3254 : 0x1054));
                }
                if (e + 2 < 16) scale_a(e + 2);
                if (e == 0 || e == 3 || e == 6 || e == 9) mbar_wait(sb + BAR_WC + (e / 3 + 2) * 8);
                else if (e < 15) SCHED_FENCE();
                if (e == 7) TS(21);
            }
            float r0[4] = {0.f, 0.f, 0.f, 0.f}, r1[4] = {0.f, 0.f, 0.f, 0.f}, r2[4] = {0.f, 0.f, 0.f, 0.f};
#pragma unroll
            for (int c = 0; c < 3; c++) {
                const uint32_t a[4] = {pq[4 * c], pq[4 * c + 1], pq[4 * c + 2], pq[4 * c + 3]};
                mma16816(r0, a, gate[4 * c], gate[4 * c + 2]);
                mma16816(r1, a, gate[4 * c + 1], gate[4 * c + 3]);
            }
            const uint32_t rest[4] = {dsum[0], dsum[1], hi_half ? 0u : pq[12], hi_half ? pq[12] : 0u};
            mma16816(r2, rest, 0x3f803f80u, gate[12]);
            sum0 = (g & 1) ? r0[1] + r2[1] : r0[0] + r2[0];
            sum1 = (g & 1) ? r1[3] + r2[3] : r1[2] + r2[2];
        }
        TS(22);
        {
            asm volatile("{.reg .pred p; setp.eq.u32 p, %3, %4; @p st.shared.f32 [%0], %1; @p st.shared.f32 [%0 + 32], %2;}" ::"r"(fin_a),
                         "f"(sum0), "f"(sum1), "r"(t), "r"(g >> 1)
                         : "memory");
            asm volatile("bar.arrive 4, 288;" ::: "memory");
            if (wq == 0) TS_DUMP(w);
        }
    }
}

typedef CUresult (*EncodeFn)(CUtensorMap*, CUtensorMapDataType, cuuint32_t, void*, const cuuint64_t*, const cuuint64_t*,
                             const cuuint32_t*, const cuuint32_t*, CUtensorMapInterleave, CUtensorMapSwizzle,
                             CUtensorMapL2promotion, CUtensorMapFloatOOBfill);

}

extern "C" void kernel_launch(void* const* d_in, const int* in_sizes, int n_in, void* d_out, int out_size) {
    static EncodeFn encode = nullptr;
    if (!encode) {
        void* fn = nullptr;
        cudaDriverEntryPointQueryResult qr;
        cudaGetDriverEntryPoint("cuTensorMapEncodeTiled", &fn, cudaEnableDefault, &qr);
        encode = (EncodeFn)fn;
        cudaFuncSetAttribute(fibinet_kernel, cudaFuncAttributeMaxDynamicSharedMemorySize, SMEM_BYTES);
    }
    CUtensorMap tm;
    const cuuint64_t gd[2] = {NH, NF * ND};
    const cuuint64_t gs[1] = {NH * 2};
    const cuuint32_t bd[2] = {64, 64}, es[2] = {1, 1};
    encode(&tm, CU_TENSOR_MAP_DATA_TYPE_BFLOAT16, 2, d_in[6], gd, gs, bd, es, CU_TENSOR_MAP_INTERLEAVE_NONE,
           CU_TENSOR_MAP_SWIZZLE_128B, CU_TENSOR_MAP_L2_PROMOTION_L2_256B, CU_TENSOR_MAP_FLOAT_OOB_FILL_NONE);
    CUtensorMap tb;
    const cuuint64_t gd2[2] = {ND, ND};
    const cuuint64_t gs2[1] = {ND * 2};
    encode(&tb, CU_TENSOR_MAP_DATA_TYPE_BFLOAT16, 2, d_in[4], gd2, gs2, bd, es, CU_TENSOR_MAP_INTERLEAVE_NONE,
           CU_TENSOR_MAP_SWIZZLE_128B, CU_TENSOR_MAP_L2_PROMOTION_L2_256B, CU_TENSOR_MAP_FLOAT_OOB_FILL_NONE);
    fibinet_kernel<<<NPREP + NMAIN, 384, SMEM_BYTES>>>(
        (const int*)d_in[0], (const uint4*)d_in[1], (const __nv_bfloat16*)d_in[2], (const __nv_bfloat16*)d_in[3],
        (const __nv_bfloat16*)d_in[5], (const unsigned char*)d_in[6], (const __nv_bfloat16*)d_in[7], (__nv_bfloat16*)d_out, tm, tb);
}
```

```cpp
#include <cuda_runtime.h>
#include <cuda_bf16.h>
#include <cuda.h>
#include <stdint.h>

namespace {

constexpr int NB = 4096, NF = 26, ND = 64, NH = 256, NR = 13;
constexpr int NPREP = 4;
constexpr int NMAIN = 128;

constexpr int SLOT = 8192;
constexpr int ZOFF = 15 * SLOT;
__host__ __device__ constexpr int slot(int s) { return ZOFF - s * SLOT; }
constexpr int BOFF = ZOFF + SLOT;
constexpr int AOFF = BOFF + 32768;
constexpr int COFF = slot(12);
constexpr int MOFF = AOFF + 65536 + 128;
constexpr int BAR_FULL = MOFF, BAR_DONE = MOFF + 64, BAR_WC = MOFF + 128, BAR_FIN = MOFF + 176,
              BAR_GO = MOFF + 184, BAR_SE = MOFF + 192, BAR_W2 = MOFF + 200, BAR_TD = MOFF + 208, BAR_Z = MOFF + 216;
__host__ __device__ constexpr int bfull(int f) { return BAR_FULL + (f & 7) * 8; }
__host__ __device__ constexpr int bdone(int f) { return BAR_DONE + (f & 7) * 8; }
__host__ __device__ constexpr int bpar(int f) { return (f >> 3) & 1; }
constexpr int PARTOFF = MOFF + 256, SEOFF = MOFF + 768;
constexpr int SMEM_BYTES = MOFF + 2944;
constexpr int XDELTA = 2 * SLOT;
__host__ __device__ constexpr int xpair(int i) {
    return (i & 3) == 0 ? slot(11) : (i & 3) == 1 ? BOFF : (i & 3) == 2 ? BOFF + SLOT : slot(15);
}
__host__ __device__ constexpr int wl(int f) { return f % 5 == 0 ? 1 : f % 5 == 4 ? 7 : f % 5 + 2; }
__host__ __device__ constexpr int wcslot(int c) {
    return c == 0 ? slot(3) : c == 1 ? slot(8) : c == 2 ? slot(10) : c == 3 ? slot(15) : c == 4 ? slot(13)
         : c == 5 ? slot(11) : c == 6 ? slot(9) : c == 7 ? slot(14) : c == 8 ? slot(7) : c == 9 ? slot(2)
         : c == 10 ? slot(1) : c == 11 ? slot(4) : c == 12 ? slot(5) : c == 13 ? slot(6) : c == 14 ? ZOFF : slot(3);
}
__host__ __device__ constexpr int wcfirst(int gi) { return gi < 3 ? gi : gi == 3 ? 5 : gi == 4 ? 8 : gi == 5 ? 11 : 16; }
constexpr int EXOFF = slot(5);
constexpr int ZQOFF = slot(6);
constexpr int GOFF = ZQOFF + 4096;
__host__ __device__ constexpr int w2chunk(int c) { return ZOFF + c * 128 + ((5 ^ (c & 7)) << 4); }

__device__ uint4 g_wc[2 * 16 * 8192 / 16];
__device__ uint4 g_se[2048 / 16];
__device__ unsigned g_ready;
__device__ unsigned g_seen;

__host__ __device__ constexpr int fieldof(int f) { return f < 24 ? 4 * (f >> 2) + 2 * (f & 1) + ((f >> 1) & 1) : f; }
__device__ __forceinline__ int fmap(int n) { return n < 24 ? n : 24 + ((n >> 1) & 1); }
__host__ __device__ constexpr int estep(int s) { return (s & 1) + 2 * (s >> 2) + 4 * (s & 2); }

__device__ __forceinline__ uint64_t mkdesc(uint32_t addr, uint32_t lbo, uint32_t sbo, int sw) {
    return (uint64_t)((addr & 0x3ffff) >> 4) | ((uint64_t)(lbo >> 4) << 16) | ((uint64_t)(sbo >> 4) << 32) |
           ((uint64_t)sw << 62);
}
__device__ __forceinline__ void mbar_init(uint32_t b, uint32_t n) {
    asm volatile("mbarrier.init.shared.b64 [%0], %1;" ::"r"(b), "r"(n) : "memory");
}
__device__ __forceinline__ void mbar_wait(uint32_t b, uint32_t par = 0) {
    asm volatile(
        "{\n.reg .pred p, q;\n.reg .u32 n;\n"
        "mbarrier.try_wait.parity.shared.b64 p, [%0], %1;\n@p bra.uni WD%=;\nmov.u32 n, 0;\n"
        "WL%=:\nmbarrier.try_wait.parity.shared.b64 p, [%0], %1;\n@p bra.uni WD%=;\n"
        "add.u32 n, n, 1;\nsetp.lt.u32 q, n, 4000000;\n@q bra.uni WL%=;\nWD%=:\n}\n" ::"r"(b), "r"(par)
        : "memory");
}
__device__ __forceinline__ uint32_t mbar_test(uint32_t b, uint32_t par) {
    uint32_t ok;
    asm volatile("{.reg .pred p; mbarrier.test_wait.parity.shared.b64 p, [%1], %2; selp.u32 %0, 1, 0, p;}"
                 : "=r"(ok)
                 : "r"(b), "r"(par)
                 : "memory");
    return ok;
}
__device__ __forceinline__ void mbar_wait_unless(uint32_t ok, uint32_t b, uint32_t par) {
    asm volatile(
        "{\n.reg .pred p, q;\n.reg .u32 n;\n"
        "setp.ne.u32 p, %1, 0;\n@p bra.uni WD%=;\nmov.u32 n, 0;\n"
        "WL%=:\nmbarrier.try_wait.parity.shared.b64 p, [%0], %2;\n@p bra.uni WD%=;\n"
        "add.u32 n, n, 1;\nsetp.lt.u32 q, n, 4000000;\n@q bra.uni WL%=;\nWD%=:\n}\n" ::"r"(b), "r"(ok), "r"(par)
        : "memory");
}
__device__ __forceinline__ void mbar_arrive(uint32_t b) {
    asm volatile("mbarrier.arrive.shared.b64 _, [%0];" ::"r"(b) : "memory");
}
__device__ __forceinline__ void mbar_expect(uint32_t b, uint32_t bytes) {
    asm volatile("mbarrier.arrive.expect_tx.shared.b64 _, [%0], %1;" ::"r"(b), "r"(bytes) : "memory");
}
__device__ __forceinline__ uint32_t opaque(uint32_t v) { return __shfl_sync(0xffffffffu, v, threadIdx.x); }
__device__ __forceinline__ bool elect() {
    uint32_t p;
    asm volatile("{.reg .pred q; elect.sync _|q, 0xffffffff; selp.u32 %0, 1, 0, q;}" : "=r"(p));
    return p;
}
__device__ __forceinline__ void tma2d(uint32_t dst, const CUtensorMap* m, uint32_t bar, int x, int y) {
    asm volatile(
        "cp.async.bulk.tensor.2d.shared::cluster.global.mbarrier::complete_tx::bytes [%0], [%1, {%3, %4}], [%2];" ::"r"(dst),
        "l"(m), "r"(bar), "r"(x), "r"(y)
        : "memory");
}
__device__ __forceinline__ void bulk(uint32_t dst, const void* src, uint32_t bytes, uint32_t bar) {
    asm volatile("cp.async.bulk.shared::cluster.global.mbarrier::complete_tx::bytes [%0], [%1], %2, [%3];" ::"r"(dst),
                 "l"(src), "r"(bytes), "r"(bar)
                 : "memory");
}
__device__ __forceinline__ void cp16(uint32_t dst, const void* src) {
    asm volatile("cp.async.cg.shared.global [%0], [%1], 16;" ::"r"(dst), "l"(src) : "memory");
}
__device__ __forceinline__ void lds128(uint32_t (&v)[4], uint32_t a) {
    asm volatile("ld.shared.v4.u32 {%0,%1,%2,%3}, [%4];" : "=r"(v[0]), "=r"(v[1]), "=r"(v[2]), "=r"(v[3]) : "r"(a) : "memory");
}
__device__ __forceinline__ void lds128_if(uint32_t (&v)[4], uint32_t a, uint32_t p) {
    asm volatile("{.reg .pred q; setp.ne.u32 q, %5, 0; @q ld.shared.v4.u32 {%0,%1,%2,%3}, [%4];}"
                 : "+r"(v[0]), "+r"(v[1]), "+r"(v[2]), "+r"(v[3])
                 : "r"(a), "r"(p)
                 : "memory");
}
__device__ __forceinline__ void lds64(uint32_t& x, uint32_t& y, uint32_t a) {
    asm volatile("ld.shared.v2.u32 {%0,%1}, [%2];" : "=r"(x), "=r"(y) : "r"(a) : "memory");
}
__device__ __forceinline__ void sts128(uint32_t a, uint32_t x, uint32_t y, uint32_t z, uint32_t w) {
    asm volatile("st.shared.v4.u32 [%0], {%1,%2,%3,%4};" ::"r"(a), "r"(x), "r"(y), "r"(z), "r"(w) : "memory");
}
__device__ __forceinline__ void sts64(uint32_t a, uint32_t x, uint32_t y) {
    asm volatile("st.shared.v2.u32 [%0], {%1,%2};" ::"r"(a), "r"(x), "r"(y) : "memory");
}
__device__ __forceinline__ uint32_t pack(float lo, float hi) {
    uint32_t r;
    asm volatile("cvt.rn.bf16x2.f32 %0, %1, %2;" : "=r"(r) : "f"(hi), "f"(lo));
    return r;
}
__device__ __forceinline__ uint32_t hmul2(uint32_t a, uint32_t b) {
    uint32_t r;
    asm volatile("mul.rn.bf16x2 %0, %1, %2;" : "=r"(r) : "r"(a), "r"(b));
    return r;
}
__device__ __forceinline__ uint32_t hfma2(uint32_t a, uint32_t b, uint32_t c) {
    uint32_t r;
    asm volatile("fma.rn.bf16x2 %0, %1, %2, %3;" : "=r"(r) : "r"(a), "r"(b), "r"(c));
    return r;
}
template <int H>
__device__ __forceinline__ uint32_t hfma2_bcast(uint32_t a, uint32_t x, uint32_t c) {
    uint32_t r;
    if (H)
        asm volatile("{.reg .b16 l, h; .reg .b32 s; mov.b32 {l, h}, %2; mov.b32 s, {h, h}; fma.rn.bf16x2 %0, %1, s, %3;}"
                     : "=r"(r)
                     : "r"(a), "r"(x), "r"(c));
    else
        asm volatile("{.reg .b16 l, h; .reg .b32 s; mov.b32 {l, h}, %2; mov.b32 s, {l, l}; fma.rn.bf16x2 %0, %1, s, %3;}"
                     : "=r"(r)
                     : "r"(a), "r"(x), "r"(c));
    return r;
}
__device__ __forceinline__ float ffma(float a, float b, float c) {
    float r;
    asm volatile("fma.rn.f32 %0, %1, %2, %3;" : "=f"(r) : "f"(a), "f"(b), "f"(c));
    return r;
}
__device__ __forceinline__ float tanh_fast(float x) {
    float r;
    asm volatile("tanh.approx.f32 %0, %1;" : "=f"(r) : "f"(x));
    return r;
}
__device__ __forceinline__ float gelu_tanh(float x) {
    float r;
    asm volatile(
        "{.reg .f32 a; mul.f32 a, %1, %1; fma.rn.f32 a, a, 0f3D122279, 0f3F4C422A; mul.f32 a, a, %1; tanh.approx.f32 %0, a;}"
        : "=f"(r)
        : "f"(x));
    return r;
}
__device__ __forceinline__ void mma16816(float (&d)[4], const uint32_t (&a)[4], uint32_t b0, uint32_t b1) {
    asm volatile("mma.sync.aligned.m16n8k16.row.col.f32.bf16.bf16.f32 {%0,%1,%2,%3}, {%4,%5,%6,%7}, {%8,%9}, {%0,%1,%2,%3};"
                 : "+f"(d[0]), "+f"(d[1]), "+f"(d[2]), "+f"(d[3])
                 : "r"(a[0]), "r"(a[1]), "r"(a[2]), "r"(a[3]), "r"(b0), "r"(b1));
}
__device__ __forceinline__ uint32_t clock32() {
    uint32_t c;
    asm volatile("mov.u32 %0, %%clock;" : "=r"(c)::"memory");
    return c;
}
#define WG_FENCE() asm volatile("wgmma.fence.sync.aligned;" ::: "memory")
#define WG_COMMIT() asm volatile("wgmma.commit_group.sync.aligned;" ::: "memory")
#define WG_WAIT0() asm volatile("wgmma.wait_group.sync.aligned 0;" ::: "memory")
#define WG_WAIT1() asm volatile("wgmma.wait_group.sync.aligned 1;" ::: "memory")
#define CP_COMMIT() asm volatile("cp.async.commit_group;" ::: "memory")
#define CP_WAIT(n) asm volatile("cp.async.wait_group %0;" ::"n"(n) : "memory")
#define SCHED_FENCE() asm volatile("pmevent 0;" ::: "memory")
#define PROXY_FENCE() asm volatile("fence.proxy.async.shared::cta;" ::: "memory")
template <int N>
__device__ __forceinline__ void pin(float (&d)[N]) {
#pragma unroll
    for (int i = 0; i < N; i++) asm volatile("" : "+f"(d[i])::"memory");
}
#define TS(k)
#define TS_DUMP(role)

__device__ __forceinline__ void wgmma_ss_n168_acc(float (&d)[84], uint64_t da, uint64_t db) {
    asm volatile(
        "wgmma.mma_async.sync.aligned.m64n168k16.f32.bf16.bf16 "
        "{%0,%1,%2,%3,%4,%5,%6,%7,%8,%9,%10,%11,%12,%13,%14,%15,"
        "%16,%17,%18,%19,%20,%21,%22,%23,%24,%25,%26,%27,%28,%29,%30,%31,"
        "%32,%33,%34,%35,%36,%37,%38,%39,%40,%41,%42,%43,%44,%45,%46,%47,"
        "%48,%49,%50,%51,%52,%53,%54,%55,%56,%57,%58,%59,%60,%61,%62,%63,"
        "%64,%65,%66,%67,%68,%69,%70,%71,%72,%73,%74,%75,%76,%77,%78,%79,"
        "%80,%81,%82,%83}, "
        "%84, %85, 1, 1, 1, 0, 1;"
        : "+f"(d[0]), "+f"(d[1]), "+f"(d[2]), "+f"(d[3]), "+f"(d[4]), "+f"(d[5]), "+f"(d[6]), "+f"(d[7]),
          "+f"(d[8]), "+f"(d[9]), "+f"(d[10]), "+f"(d[11]), "+f"(d[12]), "+f"(d[13]), "+f"(d[14]), "+f"(d[15]),
          "+f"(d[16]), "+f"(d[17]), "+f"(d[18]), "+f"(d[19]), "+f"(d[20]), "+f"(d[21]), "+f"(d[22]), "+f"(d[23]),
          "+f"(d[24]), "+f"(d[25]), "+f"(d[26]), "+f"(d[27]), "+f"(d[28]), "+f"(d[29]), "+f"(d[30]), "+f"(d[31]),
          "+f"(d[32]), "+f"(d[33]), "+f"(d[34]), "+f"(d[35]), "+f"(d[36]), "+f"(d[37]), "+f"(d[38]), "+f"(d[39]),
          "+f"(d[40]), "+f"(d[41]), "+f"(d[42]), "+f"(d[43]), "+f"(d[44]), "+f"(d[45]), "+f"(d[46]), "+f"(d[47]),
          "+f"(d[48]), "+f"(d[49]), "+f"(d[50]), "+f"(d[51]), "+f"(d[52]), "+f"(d[53]), "+f"(d[54]), "+f"(d[55]),
          "+f"(d[56]), "+f"(d[57]), "+f"(d[58]), "+f"(d[59]), "+f"(d[60]), "+f"(d[61]), "+f"(d[62]), "+f"(d[63]),
          "+f"(d[64]), "+f"(d[65]), "+f"(d[66]), "+f"(d[67]), "+f"(d[68]), "+f"(d[69]), "+f"(d[70]), "+f"(d[71]),
          "+f"(d[72]), "+f"(d[73]), "+f"(d[74]), "+f"(d[75]), "+f"(d[76]), "+f"(d[77]), "+f"(d[78]), "+f"(d[79]),
          "+f"(d[80]), "+f"(d[81]), "+f"(d[82]), "+f"(d[83])
        : "l"(da), "l"(db));
}

__device__ __forceinline__ void wgmma_rs_n32_set(float (&d)[16], const uint32_t (&a)[4], uint64_t db) {
    asm volatile(
        "wgmma.mma_async.sync.aligned.m64n32k16.f32.bf16.bf16 "
        "{%0,%1,%2,%3,%4,%5,%6,%7,%8,%9,%10,%11,%12,%13,%14,%15}, "
        "{%16,%17,%18,%19}, %20, 0, 1, 1, 0;"
        : "=f"(d[0]), "=f"(d[1]), "=f"(d[2]), "=f"(d[3]), "=f"(d[4]), "=f"(d[5]), "=f"(d[6]), "=f"(d[7]),
          "=f"(d[8]), "=f"(d[9]), "=f"(d[10]), "=f"(d[11]), "=f"(d[12]), "=f"(d[13]), "=f"(d[14]), "=f"(d[15])
        : "r"(a[0]), "r"(a[1]), "r"(a[2]), "r"(a[3]), "l"(db));
}

__device__ __forceinline__ void wgmma_rs_n32_acc(float (&d)[16], const uint32_t (&a)[4], uint64_t db) {
    asm volatile(
        "wgmma.mma_async.sync.aligned.m64n32k16.f32.bf16.bf16 "
        "{%0,%1,%2,%3,%4,%5,%6,%7,%8,%9,%10,%11,%12,%13,%14,%15}, "
        "{%16,%17,%18,%19}, %20, 1, 1, 1, 0;"
        : "+f"(d[0]), "+f"(d[1]), "+f"(d[2]), "+f"(d[3]), "+f"(d[4]), "+f"(d[5]), "+f"(d[6]), "+f"(d[7]),
          "+f"(d[8]), "+f"(d[9]), "+f"(d[10]), "+f"(d[11]), "+f"(d[12]), "+f"(d[13]), "+f"(d[14]), "+f"(d[15])
        : "r"(a[0]), "r"(a[1]), "r"(a[2]), "r"(a[3]), "l"(db));
}

__device__ __forceinline__ void wgmma_rs_n16_set(float (&d)[8], const uint32_t (&a)[4], uint64_t db) {
    asm volatile(
        "wgmma.mma_async.sync.aligned.m64n16k16.f32.bf16.bf16 "
        "{%0,%1,%2,%3,%4,%5,%6,%7}, "
        "{%8,%9,%10,%11}, %12, 0, 1, 1, 0;"
        : "=f"(d[0]), "=f"(d[1]), "=f"(d[2]), "=f"(d[3]), "=f"(d[4]), "=f"(d[5]), "=f"(d[6]), "=f"(d[7])
        : "r"(a[0]), "r"(a[1]), "r"(a[2]), "r"(a[3]), "l"(db));
}

__device__ __forceinline__ void wgmma_rs_n16_acc(float (&d)[8], const uint32_t (&a)[4], uint64_t db) {
    asm volatile(
        "wgmma.mma_async.sync.aligned.m64n16k16.f32.bf16.bf16 "
        "{%0,%1,%2,%3,%4,%5,%6,%7}, "
        "{%8,%9,%10,%11}, %12, 1, 1, 1, 0;"
        : "+f"(d[0]), "+f"(d[1]), "+f"(d[2]), "+f"(d[3]), "+f"(d[4]), "+f"(d[5]), "+f"(d[6]), "+f"(d[7])
        : "r"(a[0]), "r"(a[1]), "r"(a[2]), "r"(a[3]), "l"(db));
}

__device__ __forceinline__ void wgmma_rs_n32_pred(float (&d)[16], const uint32_t (&a)[4], uint64_t db, uint32_t scale_d) {
    asm volatile(
        "{.reg .pred p; setp.ne.u32 p, %21, 0; wgmma.mma_async.sync.aligned.m64n32k16.f32.bf16.bf16 "
        "{%0,%1,%2,%3,%4,%5,%6,%7,%8,%9,%10,%11,%12,%13,%14,%15}, "
        "{%16,%17,%18,%19}, %20, p, 1, 1, 0;}"
        : "+f"(d[0]), "+f"(d[1]), "+f"(d[2]), "+f"(d[3]), "+f"(d[4]), "+f"(d[5]), "+f"(d[6]), "+f"(d[7]),
          "+f"(d[8]), "+f"(d[9]), "+f"(d[10]), "+f"(d[11]), "+f"(d[12]), "+f"(d[13]), "+f"(d[14]), "+f"(d[15])
        : "r"(a[0]), "r"(a[1]), "r"(a[2]), "r"(a[3]), "l"(db), "r"(scale_d));
}

__device__ __forceinline__ void prep_cta(uint32_t sb, int c, const __nv_bfloat16* __restrict__ wc,
                                         const __nv_bfloat16* __restrict__ se1, const __nv_bfloat16* __restrict__ se2) {
    const int tid = threadIdx.x, lane = tid & 31, warp = tid >> 5;
    constexpr int NROW = 2 * NF * NF;
#pragma unroll
    for (int q = tid; q < NROW * 2; q += 384) cp16(sb + q * 16, wc + (q >> 1) * ND + c * 16 + (q & 1) * 8);
    if (tid == 0) sts128(sb + NROW * 32, 0, 0, 0, 0);
    if (tid < 256) {
        const int l2 = c >> 1, n = ((tid >> 2) & 1) * 8 + (tid >> 5) + (l2 ? (c & 1) * 16 : 0);
        const int k = ((tid >> 1) & 1) * 8 + ((tid >> 3) & 3) * 2 + (tid & 1), mm = k >> 1, u = k & 1;
        const int f = l2 ? fmap(n) : mm < 6 ? 4 * mm + 2 * c + u : (mm == 6 && u == 0) ? 24 + c : -1;
        float v = 0.f;
        if (f >= 0 && (l2 ? k : n) < NR) v = __bfloat162float(l2 ? se2[k * NF + f] : se1[f * NR + n]);
        reinterpret_cast<__nv_bfloat16*>(g_se)[c * 256 + tid] = __float2bfloat16(l2 ? 0.5f * v : v);
    }
    asm volatile("cp.async.wait_all;" ::: "memory");
    __syncthreads();
    const int k = 4 * (lane & 6) + 2 * (lane >> 3) + (lane & 1), i = fmap(k);
    const int g = lane >> 2, t = lane & 3;
#pragma unroll 4
    for (int task = warp; task < 128; task += 12) {
        const int eg = task & 1, n = (task >> 1) & 31, s = task >> 6;
        const int j = fmap(n ^ s);
        const uint32_t a = k < 28 ? sb + ((s * NF + i) * NF + j) * 32 + eg * 16 : sb + NROW * 32;
        uint4 v;
        asm volatile("ldmatrix.sync.aligned.m8n8.x4.trans.shared.b16 {%0,%1,%2,%3}, [%4];"
                     : "=r"(v.x), "=r"(v.y), "=r"(v.z), "=r"(v.w)
                     : "r"(a));
        const int e = eg * 8 + g;
        if (t == 3) {
            const uint32_t mask = eg ? 0xffff0000u : 0xffffu;
            v.x &= mask;
            v.y &= mask;
        }
        const int ch = (t < 2 ? t ^ ((e >> 1) & 1) : t) ^ ((n >> 1) & 3);
        g_wc[(c >> 1) * 8192 + ((g & 1) + 2 * eg + 2 * (g & 6)) * 512 + (c & 1) * 256 + s * 128 + n * 4 + ch] = v;
    }
    __threadfence();
    __syncthreads();
    if (tid == 0) atomicAdd(&g_ready, 1u);
}

#define TWARM 7
#define WPF_STEP 800
#define WDELAY 1600
#define WSTEP 500
#define START_MIN 3350
#define DB0 6
#define T_SHIFT 300
#define DBASE (mkdesc(sb + w * 4096, 16, 512, 2) + ((uint64_t)zero << 32))
#define POLL_AT 8000
#define PACE1 2100
#define PACE2 2700
#define PF_START 2600
#define PF_PACE 550
#define WPF_AT 2600

__global__ void __cluster_dims__(2, 1, 1) __launch_bounds__(384, 1)
fibinet_kernel(const int* __restrict__ idx, const uint4* __restrict__ table,
               const __nv_bfloat16* __restrict__ se1, const __nv_bfloat16* __restrict__ se2,
               const __nv_bfloat16* __restrict__ wc,
               const unsigned char* __restrict__ w1, const __nv_bfloat16* __restrict__ w2, __nv_bfloat16* __restrict__ out,
               const __grid_constant__ CUtensorMap tm_w1, const __grid_constant__ CUtensorMap tm_bi) {
    extern __shared__ __align__(1024) unsigned char smem[];
    const int tid = threadIdx.x;
    const int cta = blockIdx.x - NPREP, grp = cta >> 1, rank = cta & 1, lane = tid & 31;
    uint32_t ids[13][4], cid[3][2];
    const uint32_t idle = (tid >> 8) | (cta < 0);
    const uint32_t row = ((tid >> 5) & 3) * 16 + (lane >> 3);
    const unsigned char* ib = reinterpret_cast<const unsigned char*>(idx) + (int64_t)grp * (64 * NF * 4);
    {
        const unsigned char* ip = ib + (row * (NF * 4) + ((tid >> 4) & 8));
#pragma unroll
        for (int u = 0; u < 4; u++) {
            ids[0][u] = ids[1][u] = 0;
            asm volatile("{.reg .pred p; setp.eq.u32 p, %3, 0; @p ld.global.nc.L2::128B.v2.u32 {%0,%1}, [%2];}"
                         : "+r"(ids[0][u]), "+r"(ids[1][u])
                         : "l"(ip + 16 * NF * u), "r"(idle));
        }
    }
    const uint32_t t_0 = clock32();
    {
        const uint32_t co = ((tid & 127) >> 1) * (NF * 4) + ((tid >> 4) & 8) + 16 + 16 * (tid & 1);
#pragma unroll
        for (int k = 0; k < 3; k++) {
            cid[k][0] = cid[k][1] = 0;
            asm volatile("{.reg .pred p; setp.eq.u32 p, %3, 0; @p ld.global.nc.v2.u32 {%0,%1}, [%2];}"
                         : "+r"(cid[k][0]), "+r"(cid[k][1])
                         : "l"(ib + (co + 32 * k - (k == 2 ? 8 * ((tid >> 7) & tid & 1) : 0))), "r"(idle));
        }
    }
    const uint32_t t_start = (t_0 ^ (clock32() & blockIdx.y)) - T_SHIFT;
    const uint32_t sb = (uint32_t)__cvta_generic_to_shared(smem);
    uint32_t gd0 = sb + (tid >> 7) * XDELTA + row * 128 + (((lane & 7) ^ (lane >> 3) ^ ((tid >> 5) & 4)) << 4);
    const uint4* tp = table + (lane & 7);
    auto gather = [&](int i) {
#pragma unroll
        for (int u = 0; u < 4; u++)
            asm volatile(
                "{.reg .u64 a; .reg .pred p; setp.eq.u32 p, %3, 0; mad.wide.u32 a, %2, 128, %1; @p cp.async.cg.shared.global [%0], [a], 16;}" ::"r"(
                    (gd0 ^ ((u & 1) * 64)) + xpair(i) + u * 512),
                "l"(tp), "r"(ids[i][u]), "r"(i == 0 ? idle : 0u)
                : "memory");
        CP_COMMIT();
    };
    gather(0);
    if (cta < 0) {
        prep_cta(sb, blockIdx.x, wc, se1, se2);
        return;
    }
    if (tid == 288) asm volatile("prefetch.tensormap [%0];" ::"l"(&tm_w1));
    const int warp = __reduce_max_sync(0xffffffffu, tid >> 5);
    const int w = warp >> 2;

    if (w == 2) {
        asm volatile("setmaxnreg.dec.sync.aligned.u32 40;");
        auto load_wc = [&](int gi) {
            if (elect()) {
                const unsigned char* src = reinterpret_cast<const unsigned char*>(g_wc) + rank * 131072;
                mbar_expect(sb + BAR_WC + gi * 8, (wcfirst(gi + 1) - wcfirst(gi)) * 8192);
#pragma unroll
                for (int c = wcfirst(gi); c < wcfirst(gi + 1); c++) bulk(sb + wcslot(c), src + c * 8192, 8192, sb + BAR_WC + gi * 8);
            }
            __syncwarp();
        };
        if (warp == 8) {
            if (elect()) {
                mbar_init(sb + BAR_Z, 1);
                mbar_expect(sb + BAR_Z, 8192);
                tma2d(sb + ZOFF, &tm_bi, sb + BAR_Z, 32 * rank, 0);
            }
#pragma unroll
            for (int f = 0; f < 26; f++) {
                if (f == 2) {
                    if (elect()) {
#pragma unroll
                        for (int k = 2; k < 8; k++) mbar_init(sb + BAR_FULL + k * 8, 1);
                        asm volatile("fence.mbarrier_init.release.cluster;" ::: "memory");
                    }
                    __syncwarp();
                    asm volatile("barrier.cluster.arrive.relaxed.aligned;" ::: "memory");
                    mbar_wait(sb + BAR_Z);
#pragma unroll
                    for (int k = 0; k < 2; k++)
                        sts128(sb + ZOFF + (k * 32 + lane) * 128 + ((4 ^ (lane & 7)) << 4), 0x3c803c80u, 0x3c803c80u, 0x3c803c80u, 0x3c803c80u);
                    PROXY_FENCE();
                    asm volatile("bar.arrive 0, 384;" ::: "memory");
                    TS(31);
                }
                if (f == 5) asm volatile("bar.sync 7, 64;" ::: "memory");
                if (f >= 5) mbar_wait(sb + bdone(f - 5), bpar(f - 5));
                if (f >= 2 && f < 5)
                    while (clock32() - t_start < WDELAY + (f - 2) * WSTEP) {
                    }
                if (elect()) {
                    if (f < 2) mbar_init(sb + BAR_FULL + f * 8, 1);
                    mbar_expect(sb + bfull(f), 16384);
                    tma2d(sb + slot(2 * wl(f)), &tm_w1, sb + bfull(f), 128 * rank + 64 * (f & 1), fieldof(f) * 64);
                    tma2d(sb + slot(wl(f)), &tm_w1, sb + bfull(f), 128 * rank + 64 - 64 * (f & 1), fieldof(f) * 64);
                }
                TS(f);
            }
            if (elect()) mbar_arrive(sb + BAR_GO);
            TS_DUMP(2);
        } else if (warp == 9) {
            if (elect()) {
#pragma unroll
                for (int k = 0; k < 11; k++) mbar_init(sb + BAR_WC + k * 8, k < 10 ? 1 : 8);
                asm volatile("fence.mbarrier_init.release.cluster;" ::: "memory");
            }
            __syncwarp();
            asm volatile("barrier.cluster.arrive.relaxed.aligned;" ::: "memory");
            asm volatile("bar.sync 0, 384;" ::: "memory");
            while (clock32() - t_start < POLL_AT) __nanosleep(100);
            if (elect()) {
                unsigned v, it = 0;
                do {
                    asm volatile("ld.acquire.gpu.global.u32 %0, [%1];" : "=r"(v) : "l"(&g_ready) : "memory");
                } while (v < NPREP && ++it < 4000000u);
                asm volatile("fence.proxy.async.global;" ::: "memory");
                mbar_expect(sb + BAR_SE, 2048);
                bulk(sb + SEOFF, g_se, 2048, sb + BAR_SE);
                if (atomicAdd(&g_seen, 1u) == NMAIN - 1) {
                    g_seen = 0;
                    g_ready = 0;
                }
            }
            __syncwarp();
            TS(0);
            mbar_wait(sb + BAR_GO);
#pragma unroll
            for (int gi = 0; gi < 3; gi++) {
                mbar_wait(sb + bdone(21 + gi), bpar(21 + gi));
                load_wc(gi);
                TS(1 + gi);
            }
        } else if (warp == 10) {
            if (elect()) {
#pragma unroll
                for (int k = 0; k < 8; k++) mbar_init(sb + BAR_DONE + k * 8, 4);
                asm volatile("fence.mbarrier_init.release.cluster;" ::: "memory");
            }
            __syncwarp();
            asm volatile("barrier.cluster.arrive.relaxed.aligned;" ::: "memory");
            asm volatile("bar.arrive 7, 64;" ::: "memory");
            asm volatile("bar.sync 0, 384;" ::: "memory");
#pragma unroll 1
            for (int k = 0; k < 7; k++) {
                while (clock32() - t_start < (uint32_t)(WPF_AT + k * WPF_STEP)) __nanosleep(20);
                if (lane < 6)
                    asm volatile("prefetch.global.L2 [%0];" ::"l"(w1 + (5 + k * 3 + (lane >> 1)) * 32768 + cta * 256 + (lane & 1) * 128));
            }
        } else {
            asm volatile("bar.sync 0, 384;" ::: "memory");
            const uint2 v = __ldg(reinterpret_cast<const uint2*>(w2 + 128 * rank) + lane);
#pragma unroll
            for (int k = 0; k < 2; k++) {
                const uint32_t x = k ? v.y : v.x;
                sts64(sb + w2chunk((lane >> 2) * 4 + 2 * (lane & 1) + k) + (lane & 2) * 4,
                      __float_as_uint(0.5f * __uint_as_float(x << 16)), __float_as_uint(0.5f * __uint_as_float(x & 0xffff0000u)));
            }
            __syncwarp();
            if (lane == 0) mbar_arrive(sb + BAR_W2);
            mbar_wait(sb + BAR_GO);
            if (lane < 16) reinterpret_cast<uint32_t*>(out)[cta * 16 + lane] = 0;
            asm volatile("barrier.cluster.arrive.release.aligned;" ::: "memory");
        }
        {
            uint32_t bw[2][4], z0[4], z1[4];
            mbar_wait(sb + BAR_SE);
            lds128(bw[0], sb + SEOFF + lane * 16);
            lds128(bw[1], sb + SEOFF + 512 + lane * 16);
            asm volatile("bar.sync 2, 384;" ::: "memory");
            lds128(z0, sb + ZQOFF + (tid & 127) * 16);
            lds128(z1, sb + ZQOFF + 2048 + (tid & 127) * 16);
            TS(8);
            float s[2][4] = {};
#pragma unroll
            for (int n = 0; n < 2; n++) {
                mma16816(s[n], z0, bw[0][2 * n], bw[0][2 * n + 1]);
                mma16816(s[n], z1, bw[1][2 * n], bw[1][2 * n + 1]);
            }
            lds128(bw[0], sb + SEOFF + 1024 + lane * 16);
            lds128(bw[1], sb + SEOFF + 1536 + lane * 16);
            float th[8];
#pragma unroll
            for (int k = 0; k < 8; k++) th[k] = gelu_tanh(s[k >> 2][k & 3]);
            SCHED_FENCE();
            TS(9);
            uint32_t gq[4];
#pragma unroll
            for (int k = 0; k < 4; k++)
                gq[k] = pack(s[k >> 1][2 * (k & 1)] * ffma(th[2 * k], 0.5f, 0.5f), s[k >> 1][2 * (k & 1) + 1] * ffma(th[2 * k + 1], 0.5f, 0.5f));
            float a[4][4] = {};
#pragma unroll
            for (int n = 0; n < 4; n++) mma16816(a[n], gq, bw[n >> 1][2 * (n & 1)], bw[n >> 1][2 * (n & 1) + 1]);
#pragma unroll
            for (int k = 0; k < 16; k++)
                if (k < 13 || k == 14) a[k >> 2][k & 3] = tanh_fast(a[k >> 2][k & 3]);
            SCHED_FENCE();
            TS(10);
            uint32_t ap[8];
#pragma unroll
            for (int k = 0; k < 8; k++)
                ap[k] = pack(ffma(a[k >> 1][2 * (k & 1)], 0.5f, 0.5f), ffma(a[k >> 1][2 * (k & 1) + (k < 6)], 0.5f, 0.5f));
            sts128(sb + GOFF + (tid & 127) * 16, ap[0], ap[1], ap[2], ap[3]);
            sts128(sb + GOFF + 2048 + (tid & 127) * 16, ap[4], ap[5], ap[6], ap[7]);
            asm volatile("bar.arrive 3, 384;" ::: "memory");
            TS(11);
        }
        if (warp == 9) {
            load_wc(3);
            load_wc(4);
            mbar_wait(sb + BAR_TD);
            load_wc(5);
            if (lane < 16) TS_DUMP(3);
        } else if (warp == 10) {
            uint32_t* dst = reinterpret_cast<uint32_t*>(out) + grp * 32 + lane;
            asm volatile("barrier.cluster.wait.acquire.aligned;" : "+l"(dst)::"memory");
            SCHED_FENCE();
            asm volatile("bar.sync 4, 288;" ::: "memory");
            uint32_t p[4];
            lds64(p[0], p[1], sb + PARTOFF + lane * 8);
            lds64(p[2], p[3], sb + PARTOFF + 256 + lane * 8);
            asm volatile("red.relaxed.gpu.global.add.noftz.bf16x2 [%0], %1;" ::"l"(dst),
                         "r"(pack(__uint_as_float(p[0]) + __uint_as_float(p[2]), __uint_as_float(p[1]) + __uint_as_float(p[3])))
                         : "memory");
        }
    } else {
        asm volatile("setmaxnreg.inc.sync.aligned.u32 232;");
        asm volatile("barrier.cluster.arrive.relaxed.aligned;" ::: "memory");
        const int g = lane >> 2, t = lane & 3, wq = warp & 3, t128 = tid & 127;
        gd0 = opaque(gd0);
        TS(28);
        float acc[84];
#pragma unroll
        for (int k = 0; k < 84; k++) asm volatile("mov.b32 %0, 0;" : "=f"(acc[k]));
        uint32_t e0[9], e1[9], e2[9];
        uint32_t X[13][2][4];
        uint32_t zq[4] = {0, 0, 0, 0};
        const uint64_t dA = mkdesc(sb + w * XDELTA, 16, 1024, 1);
        uint32_t dBlo = (uint32_t)mkdesc(sb + ZOFF, 0, 0, 0);
        const uint32_t xl0 = opaque(sb + (t & 1) * XDELTA + (16 * wq + g) * 128 + (((4 * rank + 2 * w) ^ (4 * (t & 1)) ^ g) << 4));
        const uint32_t hi_half = t >> 1;
        const uint32_t sa0 = opaque(sb + AOFF + t * 4096 + (t >> 1) * 16 + (wq * 32 + g * 4 + w) * 16);
        const uint32_t sa1 = opaque(((g & 2) << 4) | ((t & 1) << 3));
        const uint32_t zero = blockIdx.y;
        auto expand = [&](int k0, int k1) {
#pragma unroll
            for (int k = k0; k < k1; k++)
#pragma unroll
                for (int u = 0; u < 4; u++)
                    asm volatile("shfl.sync.idx.b32 %0, %1, %2, 31, 0xffffffff;"
                                 : "=r"(ids[k][u])
                                 : "r"(k < 12 ? cid[(k - 2) >> 2][k & 1] : w ? cid[2][1] : cid[2][0]),
                                   "r"(2 * (lane >> 3) + 8 * u + (((k - 2) >> 1) & 1)));
        };
        auto twarm = [&]() {
            float s1[8];
            WG_FENCE();
            wgmma_rs_n16_set(s1, zq, mkdesc(sb + AOFF, 16, 512, 2));
            WG_COMMIT();
            WG_WAIT0();
            pin(s1);
            asm volatile("{.reg .pred p; setp.ne.u32 p, %1, 0; @p st.shared.f32 [%1], %0;}" ::"f"(s1[0]), "r"(zero));
        };
        expand(2, 8);
        if (TWARM & 1) twarm();
        TS(26);
        while (clock32() - t_start < PACE1) {
        }
        gather(1);
        expand(8, 13);
        if (TWARM & 2) twarm();
        TS(30);
        while (clock32() - t_start < PACE2) {
        }
        gather(2);
        if (TWARM & 4) twarm();
        asm volatile("bar.sync 0, 384;" ::: "memory");
        auto lift = [&](int i) {
            const int m = 2 * (i >> 2) + (i & 1);
#pragma unroll
            for (int r = 0; r < 2; r++)
#pragma unroll
                for (int cc = 0; cc < 2; cc++) {
                    const uint32_t a = (xl0 ^ (cc * 16)) + xpair(i) + r * 1024;
                    if (i == 12 ? r : (i & 2)) lds128_if(X[i == 12 ? 12 : 2 * m + r][cc], a, hi_half);
                    else lds128(X[2 * m + r][cc], a);
                }
        };
        auto store_pair = [&](int m, int half, const uint32_t (&ea)[9]) {
            uint32_t a;
            if (m < 4) a = sa0 + (sa1 ^ (((m & 1) << 5) | ((m >> 1) << 3)));
            else a = sb + BOFF + t * 2048 + (wq * 32 + g * 4 + ((2 * (m & 1) + w) ^ t)) * 8;
#pragma unroll
            for (int n = half; n < 4; n += 2)
#pragma unroll
                for (int u = 0; u < 2; u++)
                    sts64(a + (m < 4 ? (8 * n + u) * 2048 + n * 32 : (8 * n + u) * 1024),
                          __byte_perm(ea[2 * n], e1[2 * n], u ? 0x7632 : 0x5410),
                          __byte_perm(ea[2 * n + 1], e1[2 * n + 1], u ? 0x7632 : 0x5410));
        };
        auto z_pair = [&](int m, uint32_t a, uint32_t b) {
            asm volatile("{.reg .pred p; setp.eq.u32 p, %4, %5; @p prmt.b32 %0, %2, %3, 0x5410; @p prmt.b32 %1, %2, %3, 0x7632;}"
                         : "+r"(zq[2 * (m >> 2)]), "+r"(zq[2 * (m >> 2) + 1])
                         : "r"(a), "r"(b), "r"(t), "r"(m & 3));
        };

        TS(29);
        mbar_wait(sb + BAR_FULL + w * 8);
        CP_WAIT(2);
        while (clock32() - t_start < START_MIN) {
        }
        if (w == 1) {
            asm volatile("bar.arrive 6, 256;" ::: "memory");
            asm volatile("bar.sync 5, 256;" ::: "memory");
        }
#pragma unroll
        for (int i = 0; i < 13; i++) {
            const uint64_t da = dA + (xpair(i) >> 4) + ((uint64_t)i << 16);
            dBlo += (uint32_t)(w ? wl(2 * i + 1) - (i ? wl(2 * i - 1) : 0) : wl(2 * i) - (i ? wl(2 * i - 2) : 0)) *
                    (uint32_t)((SLOT << 12) - (SLOT >> 3));
            const uint64_t db = mkdesc(0, 0, 1024, 1) | dBlo;
            TS(i);
            WG_FENCE();
            wgmma_ss_n168_acc(acc, da, db + w * 256);
            wgmma_ss_n168_acc(acc, da + 2, db + w * 256 + 128);
            wgmma_ss_n168_acc(acc, da + 4, db + (w ^ 1) * 256);
            wgmma_ss_n168_acc(acc, da + 6, db + (w ^ 1) * 256 + 128);
            WG_COMMIT();
            if (i == 0) {
                if (w == 0) {
                    asm volatile("bar.arrive 5, 256;" ::: "memory");
                    asm volatile("bar.sync 6, 256;" ::: "memory");
                }
            } else {
                mbar_wait(sb + bdone(2 * i - 2) + (w ^ 1) * 8, bpar(2 * i - 2));
            }
            if (i < 10) gather(i + 3);
            if (i == 6) mbar_wait(sb + BAR_W2);
            lift(i);
            if (i == 10 || i == 11) mbar_wait(sb + bdone(2 * i - 2) + w * 8, bpar(2 * i - 2));
            if (i >= 2 && !(i & 1)) {
                z_pair((i - 2) >> 1, e0[8], e1[8]);
                store_pair((i - 2) >> 1, 0, e0);
#pragma unroll
                for (int k = 0; k < 8; k++) e2[k] = e0[k];
            } else if (i >= 3) {
                store_pair((i - 3) >> 1, 1, e2);
            }
            const uint32_t rdy = i < 12 ? mbar_test(sb + bfull(2 * i + 2) + w * 8, bpar(2 * i + 2)) : 0;
            WG_WAIT0();
            pin(acc);
            if (i == 12) TS(13);
            if (i == 0) TS(27);
            if (i < 10) CP_WAIT(2);
            else if (i == 10) CP_WAIT(1);
            else if (i == 11) CP_WAIT(0);
            if (i < 12 && lane == 0) mbar_arrive(sb + bdone(2 * i) + w * 8);
#pragma unroll
            for (int k = 0; k < 9; k++) {
                const int k0 = 64 + 2 * (k & 5) + ((k >> 1) & 1);
                const uint32_t v = k == 8 ? pack(acc[80], acc[82]) : i < 12 ? pack(acc[64 + 2 * k], acc[65 + 2 * k]) : pack(acc[k0], acc[k0 + 4]);
                if (i & 1) e1[k] = v;
                else e0[k] = v;
            }
            if (i < 12) {
#pragma unroll
                for (int k = 64; k < 83; k++)
                    if (k != 81) asm volatile("mov.b32 %0, %1;" : "+f"(acc[k]) : "r"(zero));
                mbar_wait_unless(rdy, sb + bfull(2 * i + 2) + w * 8, bpar(2 * i + 2));
            } else {
                z_pair(6, e0[8], 0);
                sts128(sb + ZQOFF + w * 2048 + t128 * 16, zq[0], zq[1], zq[2], zq[3]);
                asm volatile("bar.arrive 2, 384;" ::: "memory");
            }
        }
        TS(14);

        uint32_t ai[8];
        float sum0 = 0.f, sum1 = 0.f;
        float th[32];
        uint32_t hw[4][4];
        auto deep_issue = [&](int k2) {
            lds128(hw[k2], ((sb + w2chunk(w * 16 + t)) ^ ((k2 & 1) * 64)) + k2 * 512);
#pragma unroll
            for (int k = 8 * k2; k < 8 * k2 + 8; k++) th[k] = gelu_tanh(acc[k]);
        };
        auto deep_use = [&](int k2) {
#pragma unroll
            for (int k = 8 * k2; k < 8 * k2 + 8; k++) {
                const float h = __uint_as_float(hw[k2][((k >> 1) & 2) + (k & 1)]);
                const float y = ffma(th[k], h, h);
                if (k & 2) sum1 = ffma(acc[k], y, sum1);
                else sum0 = ffma(acc[k], y, sum0);
            }
        };
        auto deep_send = [&](int k0, int k1) {
#pragma unroll
            for (int k = k0; k < k1; k++)
                sts128(sb + EXOFF + w * SLOT + t128 * 16 + k * 2048, pack(acc[32 + 8 * k], acc[33 + 8 * k]),
                       pack(acc[34 + 8 * k], acc[35 + 8 * k]), pack(acc[36 + 8 * k], acc[37 + 8 * k]), pack(acc[38 + 8 * k], acc[39 + 8 * k]));
        };
        uint32_t o[4][4];
        auto deep_recv = [&](int k0, int k1) {
#pragma unroll
            for (int k = k0; k < k1; k++) lds128(o[k], sb + EXOFF + (w ^ 1) * SLOT + t128 * 16 + k * 2048);
        };
        auto deep_add = [&](int k0, int k1) {
            const uint32_t eye = (g >> 1) == t ? ((g & 1) ? 0x3f800000u : 0x3f80u) : 0u;
#pragma unroll
            for (int k = 2 * k0; k < 2 * k1; k++)
                asm volatile("mma.sync.aligned.m16n8k8.row.col.f32.bf16.bf16.f32 {%0,%1,%2,%3}, {%4,%5}, {%6}, {%0,%1,%2,%3};"
                             : "+f"(acc[4 * k]), "+f"(acc[4 * k + 1]), "+f"(acc[4 * k + 2]), "+f"(acc[4 * k + 3])
                             : "r"(o[k >> 1][2 * (k & 1)]), "r"(o[k >> 1][2 * (k & 1) + 1]), "r"(eye));
        };
        auto store_last = [&]() {
#pragma unroll
            for (int n = 0; n < 4; n++) sts64(sb + COFF + w * 4096 + n * 1024 + (t128 ^ w) * 8, e0[2 * n], e0[2 * n + 1]);
            store_pair(5, 1, e2);
        };
        const uint32_t la = sb + AOFF + w * (16 * 2048 + 64) + (wq * 32 + g * 4 + (t ^ (g & 2))) * 16;
        const uint32_t lb = sb + BOFF + w * (16 * 1024) + t128 * 8;
        const uint32_t lc0 = sb + COFF + (t & 1) * (4096 + 8) + w * 2048 + (wq * 8 + g) * 32, lc1 = lc0 ^ 8;
        uint32_t Ap[2][2][4];
        auto load_a = [&](int s) {
            const int e = estep(s);
            lds128(Ap[s & 1][0], la + e * 2048 + (e >> 2) * 16);
            lds64(Ap[s & 1][1][0], Ap[s & 1][1][1], (lb ^ ((e & 6) * 4)) + e * 1024);
            if (!(s & 2)) lds64(Ap[s & 1][1][2], Ap[s & 1][1][3], ((e & 2) ? lc1 : lc0) + (e & 1) * 1024 + (e & 4) * 4);
        };
        {
            uint32_t v[2][4];
            deep_send(0, 2);
            asm volatile("bar.sync 1, 256;" ::: "memory");
            deep_recv(0, 2);
            deep_send(2, 4);
            TS(15);
            deep_add(0, 2);
            deep_issue(0);
            asm volatile("bar.sync 1, 256;" ::: "memory");
            deep_recv(2, 4);
            SCHED_FENCE();
            deep_add(2, 4);
            TS(16);
            deep_issue(1);
            deep_use(0);
            store_last();
            SCHED_FENCE();
            TS(17);
            deep_issue(2);
            deep_use(1);
            mbar_wait(sb + BAR_WC);
            deep_use(2);
            TS(18);
            asm volatile("bar.sync 3, 384;" ::: "memory");
            lds128(v[0], sb + GOFF + t128 * 16);
            lds128(v[1], sb + GOFF + 2048 + t128 * 16);
            load_a(0);
            load_a(1);
            deep_issue(3);
#pragma unroll
            for (int k = 0; k < 8; k++) ai[k] = v[k >> 2][k & 3];
        }
        TS(19);

        uint32_t fin_a, dsum[2];
        {
            uint64_t dW[4];
#pragma unroll
            for (int k = 0; k < 4; k++) dW[k] = DBASE + (wcslot(0) >> 4) + (k >> 1) * 128 + (k & 1) * 2;
            uint32_t Aq[2][2][4], pq[13], gate[13];
            float S[2][2][16];
            auto scale_a = [&](int s) {
#pragma unroll
                for (int k = 0; k < ((s & 2) ? 6 : 8); k++)
                    Aq[s & 1][k >> 2][k & 3] = hmul2(Ap[s & 1][k >> 2][k & 3], ai[k < 4 ? k ^ (estep(s) & 2) : k]);
            };
            auto sbuf = [](int s) { return s <= DB0 ? 0 : (s - DB0) & 1; };
            auto issue = [&](int s) {
                const bool first = s == 0 || s == DB0 + 1;
                WG_FENCE();
                if (first) wgmma_rs_n32_set(S[sbuf(s)][0], Ap[s & 1][0], dW[0]);
                else wgmma_rs_n32_pred(S[sbuf(s)][0], Ap[s & 1][0], dW[0], zero);
                wgmma_rs_n32_acc(S[sbuf(s)][0], Ap[s & 1][1], dW[1]);
                if (first) wgmma_rs_n32_set(S[sbuf(s)][1], Aq[s & 1][0], dW[2]);
                else wgmma_rs_n32_pred(S[sbuf(s)][1], Aq[s & 1][0], dW[2], zero);
                wgmma_rs_n32_acc(S[sbuf(s)][1], Aq[s & 1][1], dW[3]);
                WG_COMMIT();
                if (s < 15) {
#pragma unroll
                    for (int k = 0; k < 4; k++)
                        asm volatile("add.s64 %0, %0, %1;" : "+l"(dW[k]) : "l"((int64_t)((wcslot(s + 1) - wcslot(s)) / 16)));
                }
            };
            scale_a(0);
            issue(0);
            SCHED_FENCE();
            deep_use(3);
            scale_a(1);
            mbar_wait(sb + BAR_WC + 8);
#pragma unroll
            for (int e = 0; e < 16; e++) {
                if (e >= DB0 && e < 15) {
                    issue(e + 1);
                    WG_WAIT1();
                } else {
                    WG_WAIT0();
                }
                pin(S[sbuf(e)][0]);
                pin(S[sbuf(e)][1]);
                if (e == 0 && lane == 0) mbar_arrive(sb + BAR_TD);
                if (e == 0) TS(20);
                if (e + 2 < 16) load_a(e + 2);
                uint32_t v[13];
                auto accum = [&](int q) {
                    const uint32_t x = X[q][(e >> 1) & 1][e >> 2];
                    pq[q] = (e & 1) ? hfma2_bcast<1>(v[q], x, pq[q]) : hfma2_bcast<0>(v[q], x, e ? pq[q] : 0u);
                };
#pragma unroll
                for (int q = 0; q < 13; q++) {
                    const int ix = 4 * (q >> 2) + 2 * (q & 1) + ((q >> 1) & 1);
                    v[q] = pack(S[sbuf(e)][0][ix], S[sbuf(e)][1][ix ^ 1]);
                    if (q == 12)
                        asm volatile("{.reg .pred p; setp.ne.u32 p, %3, 0; @p cvt.rn.bf16x2.f32 %0, %2, %1;}"
                                     : "+r"(v[q])
                                     : "f"(S[sbuf(e)][0][14]), "f"(S[sbuf(e)][1][15]), "r"(hi_half));
                    if (e >= DB0 || q < 7) accum(q);
                }
                if (e < DB0) {
                    issue(e + 1);
                    SCHED_FENCE();
#pragma unroll
                    for (int q = 7; q < 13; q++) accum(q);
                }
                if (e == 3) {
                    const float h0 = __uint_as_float(__float_as_uint(sum0) & 0xffff0000u);
                    const float h1 = __uint_as_float(__float_as_uint(sum1) & 0xffff0000u);
                    dsum[0] = pack(sum0 - h0, h0);
                    dsum[1] = pack(sum1 - h1, h1);
                }
                if (e == 13) {
                    fin_a = opaque(sb + PARTOFF + (warp * 16 + g) * 4);
                }
                if (e == 14) {
#pragma unroll
                    for (int q = 0; q < 13; q++)
                        asm volatile("prmt.b32 %0, %1, 0x3f80, %2;"
                                     : "=r"(gate[q])
                                     : "r"(q < 12 ? ai[2 * (q >> 2) + (q & 1)] : hi_half ? ai[7] : ai[6]), "r"((q & 2) ? 0x3254 : 0x1054));
                }
                if (e + 2 < 16) scale_a(e + 2);
                if (e == 0 || e == 3 || e == 6 || e == 9) mbar_wait(sb + BAR_WC + (e / 3 + 2) * 8);
                else if (e < 15) SCHED_FENCE();
                if (e == 7) TS(21);
            }
            float r0[4] = {0.f, 0.f, 0.f, 0.f}, r1[4] = {0.f, 0.f, 0.f, 0.f}, r2[4] = {0.f, 0.f, 0.f, 0.f};
#pragma unroll
            for (int c = 0; c < 3; c++) {
                const uint32_t a[4] = {pq[4 * c], pq[4 * c + 1], pq[4 * c + 2], pq[4 * c + 3]};
                mma16816(r0, a, gate[4 * c], gate[4 * c + 2]);
                mma16816(r1, a, gate[4 * c + 1], gate[4 * c + 3]);
            }
            const uint32_t rest[4] = {dsum[0], dsum[1], hi_half ? 0u : pq[12], hi_half ? pq[12] : 0u};
            mma16816(r2, rest, 0x3f803f80u, gate[12]);
            sum0 = (g & 1) ? r0[1] + r2[1] : r0[0] + r2[0];
            sum1 = (g & 1) ? r1[3] + r2[3] : r1[2] + r2[2];
        }
        TS(22);
        {
            asm volatile("{.reg .pred p; setp.eq.u32 p, %3, %4; @p st.shared.f32 [%0], %1; @p st.shared.f32 [%0 + 32], %2;}" ::"r"(fin_a),
                         "f"(sum0), "f"(sum1), "r"(t), "r"(g >> 1)
                         : "memory");
            asm volatile("bar.arrive 4, 288;" ::: "memory");
            if (wq == 0) TS_DUMP(w);
        }
    }
}

typedef CUresult (*EncodeFn)(CUtensorMap*, CUtensorMapDataType, cuuint32_t, void*, const cuuint64_t*, const cuuint64_t*,
                             const cuuint32_t*, const cuuint32_t*, CUtensorMapInterleave, CUtensorMapSwizzle,
                             CUtensorMapL2promotion, CUtensorMapFloatOOBfill);

}

extern "C" void kernel_launch(void* const* d_in, const int* in_sizes, int n_in, void* d_out, int out_size) {
    static EncodeFn encode = nullptr;
    if (!encode) {
        void* fn = nullptr;
        cudaDriverEntryPointQueryResult qr;
        cudaGetDriverEntryPoint("cuTensorMapEncodeTiled", &fn, cudaEnableDefault, &qr);
        encode = (EncodeFn)fn;
        cudaFuncSetAttribute(fibinet_kernel, cudaFuncAttributeMaxDynamicSharedMemorySize, SMEM_BYTES);
    }
    CUtensorMap tm;
    const cuuint64_t gd[2] = {NH, NF * ND};
    const cuuint64_t gs[1] = {NH * 2};
    const cuuint32_t bd[2] = {64, 64}, es[2] = {1, 1};
    encode(&tm, CU_TENSOR_MAP_DATA_TYPE_BFLOAT16, 2, d_in[6], gd, gs, bd, es, CU_TENSOR_MAP_INTERLEAVE_NONE,
           CU_TENSOR_MAP_SWIZZLE_128B, CU_TENSOR_MAP_L2_PROMOTION_L2_256B, CU_TENSOR_MAP_FLOAT_OOB_FILL_NONE);
    CUtensorMap tb;
    const cuuint64_t gd2[2] = {ND, ND};
    const cuuint64_t gs2[1] = {ND * 2};
    encode(&tb, CU_TENSOR_MAP_DATA_TYPE_BFLOAT16, 2, d_in[4], gd2, gs2, bd, es, CU_TENSOR_MAP_INTERLEAVE_NONE,
           CU_TENSOR_MAP_SWIZZLE_128B, CU_TENSOR_MAP_L2_PROMOTION_L2_256B, CU_TENSOR_MAP_FLOAT_OOB_FILL_NONE);
    fibinet_kernel<<<NPREP + NMAIN, 384, SMEM_BYTES>>>(
        (const int*)d_in[0], (const uint4*)d_in[1], (const __nv_bfloat16*)d_in[2], (const __nv_bfloat16*)d_in[3],
        (const __nv_bfloat16*)d_in[5], (const unsigned char*)d_in[6], (const __nv_bfloat16*)d_in[7], (__nv_bfloat16*)d_out, tm, tb);
}
```

```cpp
#include <cuda_runtime.h>
#include <cuda_bf16.h>
#include <cuda.h>
#include <stdint.h>

namespace {

constexpr int NB = 4096, NF = 26, ND = 64, NH = 256, NR = 13;
constexpr int NPREP = 4;
constexpr int NMAIN = 128;

constexpr int SLOT = 8192;
constexpr int ZOFF = 15 * SLOT;
__host__ __device__ constexpr int slot(int s) { return ZOFF - s * SLOT; }
constexpr int BOFF = ZOFF + SLOT;
constexpr int AOFF = BOFF + 32768;
constexpr int COFF = slot(12);
constexpr int MOFF = AOFF + 65536 + 128;
constexpr int BAR_FULL = MOFF, BAR_DONE = MOFF + 64, BAR_WC = MOFF + 128, BAR_FIN = MOFF + 176,
              BAR_GO = MOFF + 184, BAR_SE = MOFF + 192, BAR_W2 = MOFF + 200, BAR_TD = MOFF + 208, BAR_Z = MOFF + 216;
__host__ __device__ constexpr int bfull(int f) { return BAR_FULL + (f & 7) * 8; }
__host__ __device__ constexpr int bdone(int f) { return BAR_DONE + (f & 7) * 8; }
__host__ __device__ constexpr int bpar(int f) { return (f >> 3) & 1; }
constexpr int PARTOFF = MOFF + 256, SEOFF = MOFF + 768;
constexpr int SMEM_BYTES = MOFF + 2944;
constexpr int XDELTA = 2 * SLOT;
__host__ __device__ constexpr int xpair(int i) {
    return (i & 3) == 0 ? slot(11) : (i & 3) == 1 ? BOFF : (i & 3) == 2 ? BOFF + SLOT : slot(15);
}
__host__ __device__ constexpr int wl(int f) { return f % 5 == 0 ? 1 : f % 5 == 4 ? 7 : f % 5 + 2; }
__host__ __device__ constexpr int wcslot(int c) {
    return c == 0 ? slot(3) : c == 1 ? slot(8) : c == 2 ? slot(10) : c == 3 ? slot(15) : c == 4 ? slot(13)
         : c == 5 ? slot(11) : c == 6 ? slot(9) : c == 7 ? slot(14) : c == 8 ? slot(7) : c == 9 ? slot(2)
         : c == 10 ? slot(1) : c == 11 ? slot(4) : c == 12 ? slot(5) : c == 13 ? slot(6) : c == 14 ? ZOFF : slot(3);
}
__host__ __device__ constexpr int wcfirst(int gi) { return gi < 3 ? gi : gi == 3 ? 5 : gi == 4 ? 8 : gi == 5 ? 11 : 16; }
constexpr int EXOFF = slot(5);
constexpr int ZQOFF = slot(6);
constexpr int GOFF = ZQOFF + 4096;
__host__ __device__ constexpr int w2chunk(int c) { return ZOFF + c * 128 + ((5 ^ (c & 7)) << 4); }

__device__ uint4 g_wc[2 * 16 * 8192 / 16];
__device__ uint4 g_se[2048 / 16];
__device__ unsigned g_ready;
__device__ unsigned g_seen;

__host__ __device__ constexpr int fieldof(int f) { return f < 24 ? 4 * (f >> 2) + 2 * (f & 1) + ((f >> 1) & 1) : f; }
__device__ __forceinline__ int fmap(int n) { return n < 24 ? n : 24 + ((n >> 1) & 1); }
__host__ __device__ constexpr int estep(int s) { return (s & 1) + 2 * (s >> 2) + 4 * (s & 2); }

__device__ __forceinline__ uint64_t mkdesc(uint32_t addr, uint32_t lbo, uint32_t sbo, int sw) {
    return (uint64_t)((addr & 0x3ffff) >> 4) | ((uint64_t)(lbo >> 4) << 16) | ((uint64_t)(sbo >> 4) << 32) |
           ((uint64_t)sw << 62);
}
__device__ __forceinline__ void mbar_init(uint32_t b, uint32_t n) {
    asm volatile("mbarrier.init.shared.b64 [%0], %1;" ::"r"(b), "r"(n) : "memory");
}
__device__ __forceinline__ void mbar_wait(uint32_t b, uint32_t par = 0) {
    asm volatile(
        "{\n.reg .pred p, q;\n.reg .u32 n;\n"
        "mbarrier.try_wait.parity.shared.b64 p, [%0], %1;\n@p bra.uni WD%=;\nmov.u32 n, 0;\n"
        "WL%=:\nmbarrier.try_wait.parity.shared.b64 p, [%0], %1;\n@p bra.uni WD%=;\n"
        "add.u32 n, n, 1;\nsetp.lt.u32 q, n, 4000000;\n@q bra.uni WL%=;\nWD%=:\n}\n" ::"r"(b), "r"(par)
        : "memory");
}
__device__ __forceinline__ uint32_t mbar_test(uint32_t b, uint32_t par) {
    uint32_t ok;
    asm volatile("{.reg .pred p; mbarrier.test_wait.parity.shared.b64 p, [%1], %2; selp.u32 %0, 1, 0, p;}"
                 : "=r"(ok)
                 : "r"(b), "r"(par)
                 : "memory");
    return ok;
}
__device__ __forceinline__ void mbar_wait_unless(uint32_t ok, uint32_t b, uint32_t par) {
    asm volatile(
        "{\n.reg .pred p, q;\n.reg .u32 n;\n"
        "setp.ne.u32 p, %1, 0;\n@p bra.uni WD%=;\nmov.u32 n, 0;\n"
        "WL%=:\nmbarrier.try_wait.parity.shared.b64 p, [%0], %2;\n@p bra.uni WD%=;\n"
        "add.u32 n, n, 1;\nsetp.lt.u32 q, n, 4000000;\n@q bra.uni WL%=;\nWD%=:\n}\n" ::"r"(b), "r"(ok), "r"(par)
        : "memory");
}
__device__ __forceinline__ void mbar_arrive(uint32_t b) {
    asm volatile("mbarrier.arrive.shared.b64 _, [%0];" ::"r"(b) : "memory");
}
__device__ __forceinline__ void mbar_expect(uint32_t b, uint32_t bytes) {
    asm volatile("mbarrier.arrive.expect_tx.shared.b64 _, [%0], %1;" ::"r"(b), "r"(bytes) : "memory");
}
__device__ __forceinline__ uint32_t opaque(uint32_t v) { return __shfl_sync(0xffffffffu, v, threadIdx.x); }
__device__ __forceinline__ bool elect() {
    uint32_t p;
    asm volatile("{.reg .pred q; elect.sync _|q, 0xffffffff; selp.u32 %0, 1, 0, q;}" : "=r"(p));
    return p;
}
__device__ __forceinline__ void tma2d(uint32_t dst, const CUtensorMap* m, uint32_t bar, int x, int y) {
    asm volatile(
        "cp.async.bulk.tensor.2d.shared::cluster.global.mbarrier::complete_tx::bytes [%0], [%1, {%3, %4}], [%2];" ::"r"(dst),
        "l"(m), "r"(bar), "r"(x), "r"(y)
        : "memory");
}
__device__ __forceinline__ void bulk(uint32_t dst, const void* src, uint32_t bytes, uint32_t bar) {
    asm volatile("cp.async.bulk.shared::cluster.global.mbarrier::complete_tx::bytes [%0], [%1], %2, [%3];" ::"r"(dst),
                 "l"(src), "r"(bytes), "r"(bar)
                 : "memory");
}
__device__ __forceinline__ void cp16(uint32_t dst, const void* src) {
    asm volatile("cp.async.cg.shared.global [%0], [%1], 16;" ::"r"(dst), "l"(src) : "memory");
}
__device__ __forceinline__ void lds128(uint32_t (&v)[4], uint32_t a) {
    asm volatile("ld.shared.v4.u32 {%0,%1,%2,%3}, [%4];" : "=r"(v[0]), "=r"(v[1]), "=r"(v[2]), "=r"(v[3]) : "r"(a) : "memory");
}
__device__ __forceinline__ void lds128_if(uint32_t (&v)[4], uint32_t a, uint32_t p) {
    asm volatile("{.reg .pred q; setp.ne.u32 q, %5, 0; @q ld.shared.v4.u32 {%0,%1,%2,%3}, [%4];}"
                 : "+r"(v[0]), "+r"(v[1]), "+r"(v[2]), "+r"(v[3])
                 : "r"(a), "r"(p)
                 : "memory");
}
__device__ __forceinline__ void lds64(uint32_t& x, uint32_t& y, uint32_t a) {
    asm volatile("ld.shared.v2.u32 {%0,%1}, [%2];" : "=r"(x), "=r"(y) : "r"(a) : "memory");
}
__device__ __forceinline__ void sts128(uint32_t a, uint32_t x, uint32_t y, uint32_t z, uint32_t w) {
    asm volatile("st.shared.v4.u32 [%0], {%1,%2,%3,%4};" ::"r"(a), "r"(x), "r"(y), "r"(z), "r"(w) : "memory");
}
__device__ __forceinline__ void sts64(uint32_t a, uint32_t x, uint32_t y) {
    asm volatile("st.shared.v2.u32 [%0], {%1,%2};" ::"r"(a), "r"(x), "r"(y) : "memory");
}
__device__ __forceinline__ uint32_t pack(float lo, float hi) {
    uint32_t r;
    asm volatile("cvt.rn.bf16x2.f32 %0, %1, %2;" : "=r"(r) : "f"(hi), "f"(lo));
    return r;
}
__device__ __forceinline__ uint32_t hmul2(uint32_t a, uint32_t b) {
    uint32_t r;
    asm volatile("mul.rn.bf16x2 %0, %1, %2;" : "=r"(r) : "r"(a), "r"(b));
    return r;
}
__device__ __forceinline__ uint32_t hfma2(uint32_t a, uint32_t b, uint32_t c) {
    uint32_t r;
    asm volatile("fma.rn.bf16x2 %0, %1, %2, %3;" : "=r"(r) : "r"(a), "r"(b), "r"(c));
    return r;
}
template <int H>
__device__ __forceinline__ uint32_t hfma2_bcast(uint32_t a, uint32_t x, uint32_t c) {
    uint32_t r;
    if (H)
        asm volatile("{.reg .b16 l, h; .reg .b32 s; mov.b32 {l, h}, %2; mov.b32 s, {h, h}; fma.rn.bf16x2 %0, %1, s, %3;}"
                     : "=r"(r)
                     : "r"(a), "r"(x), "r"(c));
    else
        asm volatile("{.reg .b16 l, h; .reg .b32 s; mov.b32 {l, h}, %2; mov.b32 s, {l, l}; fma.rn.bf16x2 %0, %1, s, %3;}"
                     : "=r"(r)
                     : "r"(a), "r"(x), "r"(c));
    return r;
}
__device__ __forceinline__ float ffma(float a, float b, float c) {
    float r;
    asm volatile("fma.rn.f32 %0, %1, %2, %3;" : "=f"(r) : "f"(a), "f"(b), "f"(c));
    return r;
}
__device__ __forceinline__ float tanh_fast(float x) {
    float r;
    asm volatile("tanh.approx.f32 %0, %1;" : "=f"(r) : "f"(x));
    return r;
}
__device__ __forceinline__ float gelu_tanh(float x) {
    float r;
    asm volatile(
        "{.reg .f32 a; mul.f32 a, %1, %1; fma.rn.f32 a, a, 0f3D122279, 0f3F4C422A; mul.f32 a, a, %1; tanh.approx.f32 %0, a;}"
        : "=f"(r)
        : "f"(x));
    return r;
}
__device__ __forceinline__ void mma16816(float (&d)[4], const uint32_t (&a)[4], uint32_t b0, uint32_t b1) {
    asm volatile("mma.sync.aligned.m16n8k16.row.col.f32.bf16.bf16.f32 {%0,%1,%2,%3}, {%4,%5,%6,%7}, {%8,%9}, {%0,%1,%2,%3};"
                 : "+f"(d[0]), "+f"(d[1]), "+f"(d[2]), "+f"(d[3])
                 : "r"(a[0]), "r"(a[1]), "r"(a[2]), "r"(a[3]), "r"(b0), "r"(b1));
}
__device__ __forceinline__ uint32_t clock32() {
    uint32_t c;
    asm volatile("mov.u32 %0, %%clock;" : "=r"(c)::"memory");
    return c;
}
#define WG_FENCE() asm volatile("wgmma.fence.sync.aligned;" ::: "memory")
#define WG_COMMIT() asm volatile("wgmma.commit_group.sync.aligned;" ::: "memory")
#define WG_WAIT0() asm volatile("wgmma.wait_group.sync.aligned 0;" ::: "memory")
#define WG_WAIT1() asm volatile("wgmma.wait_group.sync.aligned 1;" ::: "memory")
#define CP_COMMIT() asm volatile("cp.async.commit_group;" ::: "memory")
#define CP_WAIT(n) asm volatile("cp.async.wait_group %0;" ::"n"(n) : "memory")
#define SCHED_FENCE() asm volatile("pmevent 0;" ::: "memory")
#define PROXY_FENCE() asm volatile("fence.proxy.async.shared::cta;" ::: "memory")
template <int N>
__device__ __forceinline__ void pin(float (&d)[N]) {
#pragma unroll
    for (int i = 0; i < N; i++) asm volatile("" : "+f"(d[i])::"memory");
}
#define TS(k)
#define TS_DUMP(role)

__device__ __forceinline__ void wgmma_ss_n168_acc(float (&d)[84], uint64_t da, uint64_t db) {
    asm volatile(
        "wgmma.mma_async.sync.aligned.m64n168k16.f32.bf16.bf16 "
        "{%0,%1,%2,%3,%4,%5,%6,%7,%8,%9,%10,%11,%12,%13,%14,%15,"
        "%16,%17,%18,%19,%20,%21,%22,%23,%24,%25,%26,%27,%28,%29,%30,%31,"
        "%32,%33,%34,%35,%36,%37,%38,%39,%40,%41,%42,%43,%44,%45,%46,%47,"
        "%48,%49,%50,%51,%52,%53,%54,%55,%56,%57,%58,%59,%60,%61,%62,%63,"
        "%64,%65,%66,%67,%68,%69,%70,%71,%72,%73,%74,%75,%76,%77,%78,%79,"
        "%80,%81,%82,%83}, "
        "%84, %85, 1, 1, 1, 0, 1;"
        : "+f"(d[0]), "+f"(d[1]), "+f"(d[2]), "+f"(d[3]), "+f"(d[4]), "+f"(d[5]), "+f"(d[6]), "+f"(d[7]),
          "+f"(d[8]), "+f"(d[9]), "+f"(d[10]), "+f"(d[11]), "+f"(d[12]), "+f"(d[13]), "+f"(d[14]), "+f"(d[15]),
          "+f"(d[16]), "+f"(d[17]), "+f"(d[18]), "+f"(d[19]), "+f"(d[20]), "+f"(d[21]), "+f"(d[22]), "+f"(d[23]),
          "+f"(d[24]), "+f"(d[25]), "+f"(d[26]), "+f"(d[27]), "+f"(d[28]), "+f"(d[29]), "+f"(d[30]), "+f"(d[31]),
          "+f"(d[32]), "+f"(d[33]), "+f"(d[34]), "+f"(d[35]), "+f"(d[36]), "+f"(d[37]), "+f"(d[38]), "+f"(d[39]),
          "+f"(d[40]), "+f"(d[41]), "+f"(d[42]), "+f"(d[43]), "+f"(d[44]), "+f"(d[45]), "+f"(d[46]), "+f"(d[47]),
          "+f"(d[48]), "+f"(d[49]), "+f"(d[50]), "+f"(d[51]), "+f"(d[52]), "+f"(d[53]), "+f"(d[54]), "+f"(d[55]),
          "+f"(d[56]), "+f"(d[57]), "+f"(d[58]), "+f"(d[59]), "+f"(d[60]), "+f"(d[61]), "+f"(d[62]), "+f"(d[63]),
          "+f"(d[64]), "+f"(d[65]), "+f"(d[66]), "+f"(d[67]), "+f"(d[68]), "+f"(d[69]), "+f"(d[70]), "+f"(d[71]),
          "+f"(d[72]), "+f"(d[73]), "+f"(d[74]), "+f"(d[75]), "+f"(d[76]), "+f"(d[77]), "+f"(d[78]), "+f"(d[79]),
          "+f"(d[80]), "+f"(d[81]), "+f"(d[82]), "+f"(d[83])
        : "l"(da), "l"(db));
}

__device__ __forceinline__ void wgmma_rs_n32_set(float (&d)[16], const uint32_t (&a)[4], uint64_t db) {
    asm volatile(
        "wgmma.mma_async.sync.aligned.m64n32k16.f32.bf16.bf16 "
        "{%0,%1,%2,%3,%4,%5,%6,%7,%8,%9,%10,%11,%12,%13,%14,%15}, "
        "{%16,%17,%18,%19}, %20, 0, 1, 1, 0;"
        : "=f"(d[0]), "=f"(d[1]), "=f"(d[2]), "=f"(d[3]), "=f"(d[4]), "=f"(d[5]), "=f"(d[6]), "=f"(d[7]),
          "=f"(d[8]), "=f"(d[9]), "=f"(d[10]), "=f"(d[11]), "=f"(d[12]), "=f"(d[13]), "=f"(d[14]), "=f"(d[15])
        : "r"(a[0]), "r"(a[1]), "r"(a[2]), "r"(a[3]), "l"(db));
}

__device__ __forceinline__ void wgmma_rs_n32_acc(float (&d)[16], const uint32_t (&a)[4], uint64_t db) {
    asm volatile(
        "wgmma.mma_async.sync.aligned.m64n32k16.f32.bf16.bf16 "
        "{%0,%1,%2,%3,%4,%5,%6,%7,%8,%9,%10,%11,%12,%13,%14,%15}, "
        "{%16,%17,%18,%19}, %20, 1, 1, 1, 0;"
        : "+f"(d[0]), "+f"(d[1]), "+f"(d[2]), "+f"(d[3]), "+f"(d[4]), "+f"(d[5]), "+f"(d[6]), "+f"(d[7]),
          "+f"(d[8]), "+f"(d[9]), "+f"(d[10]), "+f"(d[11]), "+f"(d[12]), "+f"(d[13]), "+f"(d[14]), "+f"(d[15])
        : "r"(a[0]), "r"(a[1]), "r"(a[2]), "r"(a[3]), "l"(db));
}

__device__ __forceinline__ void wgmma_rs_n16_set(float (&d)[8], const uint32_t (&a)[4], uint64_t db) {
    asm volatile(
        "wgmma.mma_async.sync.aligned.m64n16k16.f32.bf16.bf16 "
        "{%0,%1,%2,%3,%4,%5,%6,%7}, "
        "{%8,%9,%10,%11}, %12, 0, 1, 1, 0;"
        : "=f"(d[0]), "=f"(d[1]), "=f"(d[2]), "=f"(d[3]), "=f"(d[4]), "=f"(d[5]), "=f"(d[6]), "=f"(d[7])
        : "r"(a[0]), "r"(a[1]), "r"(a[2]), "r"(a[3]), "l"(db));
}

__device__ __forceinline__ void wgmma_rs_n16_acc(float (&d)[8], const uint32_t (&a)[4], uint64_t db) {
    asm volatile(
        "wgmma.mma_async.sync.aligned.m64n16k16.f32.bf16.bf16 "
        "{%0,%1,%2,%3,%4,%5,%6,%7}, "
        "{%8,%9,%10,%11}, %12, 1, 1, 1, 0;"
        : "+f"(d[0]), "+f"(d[1]), "+f"(d[2]), "+f"(d[3]), "+f"(d[4]), "+f"(d[5]), "+f"(d[6]), "+f"(d[7])
        : "r"(a[0]), "r"(a[1]), "r"(a[2]), "r"(a[3]), "l"(db));
}

__device__ __forceinline__ void wgmma_rs_n32_pred(float (&d)[16], const uint32_t (&a)[4], uint64_t db, uint32_t scale_d) {
    asm volatile(
        "{.reg .pred p; setp.ne.u32 p, %21, 0; wgmma.mma_async.sync.aligned.m64n32k16.f32.bf16.bf16 "
        "{%0,%1,%2,%3,%4,%5,%6,%7,%8,%9,%10,%11,%12,%13,%14,%15}, "
        "{%16,%17,%18,%19}, %20, p, 1, 1, 0;}"
        : "+f"(d[0]), "+f"(d[1]), "+f"(d[2]), "+f"(d[3]), "+f"(d[4]), "+f"(d[5]), "+f"(d[6]), "+f"(d[7]),
          "+f"(d[8]), "+f"(d[9]), "+f"(d[10]), "+f"(d[11]), "+f"(d[12]), "+f"(d[13]), "+f"(d[14]), "+f"(d[15])
        : "r"(a[0]), "r"(a[1]), "r"(a[2]), "r"(a[3]), "l"(db), "r"(scale_d));
}

__device__ __forceinline__ void prep_cta(uint32_t sb, int c, const __nv_bfloat16* __restrict__ wc,
                                         const __nv_bfloat16* __restrict__ se1, const __nv_bfloat16* __restrict__ se2) {
    const int tid = threadIdx.x, lane = tid & 31, warp = tid >> 5, s = c >> 1;
    constexpr int ZERO = 16 * NF * 128;
#pragma unroll
    for (int q = tid; q < 16 * NF * 8; q += 384) {
        const int i = q >> 7, nn = (q >> 3) & 15, j = fmap((16 * (c & 1) + nn) ^ s);
        cp16(sb + (q >> 3) * 128 + (((q & 7) ^ (i & 1) ^ ((i >> 3) << 1)) << 4), wc + ((s * NF + i) * NF + j) * ND + (q & 7) * 8);
    }
    if (tid < 8) sts128(sb + ZERO + tid * 16, 0, 0, 0, 0);
    if (tid < 256) {
        const int n = ((tid >> 2) & 1) * 8 + (tid >> 5) + (s ? (c & 1) * 16 : 0);
        const int k = ((tid >> 1) & 1) * 8 + ((tid >> 3) & 3) * 2 + (tid & 1), mm = k >> 1, u = k & 1;
        const int f = s ? fmap(n) : mm < 6 ? 4 * mm + 2 * c + u : (mm == 6 && u == 0) ? 24 + c : -1;
        float v = 0.f;
        if (f >= 0 && (s ? k : n) < NR) v = __bfloat162float(s ? se2[k * NF + f] : se1[f * NR + n]);
        reinterpret_cast<__nv_bfloat16*>(g_se)[c * 256 + tid] = __float2bfloat16(s ? 0.5f * v : v);
    }
    asm volatile("cp.async.wait_all;" ::: "memory");
    __syncthreads();
    const int k = 4 * (lane & 6) + 2 * (lane >> 3) + (lane & 1), i = fmap(k);
    const int g = lane >> 2, t = lane & 3;
#pragma unroll 4
    for (int task = warp; task < 128; task += 12) {
        const int nn = task & 15, eg = task >> 4, n = 16 * (c & 1) + nn;
        const uint32_t a = sb + (k < 28 ? (i * 16 + nn) * 128 : ZERO) + ((eg ^ (i & 1) ^ ((i >> 3) << 1)) << 4);
        uint4 v;
        asm volatile("ldmatrix.sync.aligned.m8n8.x4.trans.shared.b16 {%0,%1,%2,%3}, [%4];"
                     : "=r"(v.x), "=r"(v.y), "=r"(v.z), "=r"(v.w)
                     : "r"(a));
        if (t == 3) {
            const uint32_t mask = (eg & 1) ? 0xffff0000u : 0xffffu;
            v.x &= mask;
            v.y &= mask;
        }
        const int ch = (t < 2 ? t ^ ((g >> 1) & 1) : t) ^ ((n >> 1) & 3);
        const int step = (g & 1) + 2 * (eg & 1) + 2 * (g & 6);
        g_wc[(eg >> 2) * 8192 + step * 512 + ((eg >> 1) & 1) * 256 + s * 128 + n * 4 + ch] = v;
    }
    __threadfence();
    __syncthreads();
    if (tid == 0) atomicAdd(&g_ready, 1u);
}

#define TWARM 7
#define WPF_STEP 800
#define WDELAY 1600
#define WSTEP 500
#define START_MIN 3350
#define DB0 6
#define T_SHIFT 300
#define DBASE (mkdesc(sb + w * 4096, 16, 512, 2) + ((uint64_t)zero << 32))
#define POLL_AT 8000
#define PACE1 2100
#define PACE2 2700
#define PF_START 2600
#define PF_PACE 550
#define WPF_AT 2600

__global__ void __cluster_dims__(2, 1, 1) __launch_bounds__(384, 1)
fibinet_kernel(const int* __restrict__ idx, const uint4* __restrict__ table,
               const __nv_bfloat16* __restrict__ se1, const __nv_bfloat16* __restrict__ se2,
               const __nv_bfloat16* __restrict__ wc,
               const unsigned char* __restrict__ w1, const __nv_bfloat16* __restrict__ w2, __nv_bfloat16* __restrict__ out,
               const __grid_constant__ CUtensorMap tm_w1, const __grid_constant__ CUtensorMap tm_bi) {
    extern __shared__ __align__(1024) unsigned char smem[];
    const int tid = threadIdx.x;
    const int cta = blockIdx.x - NPREP, grp = cta >> 1, rank = cta & 1, lane = tid & 31;
    uint32_t ids[13][4], cid[3][2];
    const uint32_t idle = (tid >> 8) | (cta < 0);
    const uint32_t row = ((tid >> 5) & 3) * 16 + (lane >> 3);
    const unsigned char* ib = reinterpret_cast<const unsigned char*>(idx) + (int64_t)grp * (64 * NF * 4);
    {
        const unsigned char* ip = ib + (row * (NF * 4) + ((tid >> 4) & 8));
#pragma unroll
        for (int u = 0; u < 4; u++) {
            ids[0][u] = ids[1][u] = 0;
            asm volatile("{.reg .pred p; setp.eq.u32 p, %3, 0; @p ld.global.nc.L2::128B.v2.u32 {%0,%1}, [%2];}"
                         : "+r"(ids[0][u]), "+r"(ids[1][u])
                         : "l"(ip + 16 * NF * u), "r"(idle));
        }
    }
    const uint32_t t_0 = clock32();
    {
        const uint32_t co = ((tid & 127) >> 1) * (NF * 4) + ((tid >> 4) & 8) + 16 + 16 * (tid & 1);
#pragma unroll
        for (int k = 0; k < 3; k++) {
            cid[k][0] = cid[k][1] = 0;
            asm volatile("{.reg .pred p; setp.eq.u32 p, %3, 0; @p ld.global.nc.v2.u32 {%0,%1}, [%2];}"
                         : "+r"(cid[k][0]), "+r"(cid[k][1])
                         : "l"(ib + (co + 32 * k - (k == 2 ? 8 * ((tid >> 7) & tid & 1) : 0))), "r"(idle));
        }
    }
    const uint32_t t_start = (t_0 ^ (clock32() & blockIdx.y)) - T_SHIFT;
    const uint32_t sb = (uint32_t)__cvta_generic_to_shared(smem);
    uint32_t gd0 = sb + (tid >> 7) * XDELTA + row * 128 + (((lane & 7) ^ (lane >> 3) ^ ((tid >> 5) & 4)) << 4);
    const uint4* tp = table + (lane & 7);
    auto gather = [&](int i) {
#pragma unroll
        for (int u = 0; u < 4; u++)
            asm volatile(
                "{.reg .u64 a; .reg .pred p; setp.eq.u32 p, %3, 0; mad.wide.u32 a, %2, 128, %1; @p cp.async.cg.shared.global [%0], [a], 16;}" ::"r"(
                    (gd0 ^ ((u & 1) * 64)) + xpair(i) + u * 512),
                "l"(tp), "r"(ids[i][u]), "r"(i == 0 ? idle : 0u)
                : "memory");
        CP_COMMIT();
    };
    gather(0);
    if (cta < 0) {
        prep_cta(sb, blockIdx.x, wc, se1, se2);
        return;
    }
    if (tid == 288) asm volatile("prefetch.tensormap [%0];" ::"l"(&tm_w1));
    const int warp = __reduce_max_sync(0xffffffffu, tid >> 5);
    const int w = warp >> 2;

    if (w == 2) {
        asm volatile("setmaxnreg.dec.sync.aligned.u32 40;");
        auto load_wc = [&](int gi) {
            if (elect()) {
                const unsigned char* src = reinterpret_cast<const unsigned char*>(g_wc) + rank * 131072;
                mbar_expect(sb + BAR_WC + gi * 8, (wcfirst(gi + 1) - wcfirst(gi)) * 8192);
#pragma unroll
                for (int c = wcfirst(gi); c < wcfirst(gi + 1); c++) bulk(sb + wcslot(c), src + c * 8192, 8192, sb + BAR_WC + gi * 8);
            }
            __syncwarp();
        };
        if (warp == 8) {
            if (elect()) {
                mbar_init(sb + BAR_Z, 1);
                mbar_expect(sb + BAR_Z, 8192);
                tma2d(sb + ZOFF, &tm_bi, sb + BAR_Z, 32 * rank, 0);
            }
#pragma unroll
            for (int f = 0; f < 26; f++) {
                if (f == 2) {
                    if (elect()) {
#pragma unroll
                        for (int k = 2; k < 8; k++) mbar_init(sb + BAR_FULL + k * 8, 1);
                        asm volatile("fence.mbarrier_init.release.cluster;" ::: "memory");
                    }
                    __syncwarp();
                    asm volatile("barrier.cluster.arrive.relaxed.aligned;" ::: "memory");
                    mbar_wait(sb + BAR_Z);
#pragma unroll
                    for (int k = 0; k < 2; k++)
                        sts128(sb + ZOFF + (k * 32 + lane) * 128 + ((4 ^ (lane & 7)) << 4), 0x3c803c80u, 0x3c803c80u, 0x3c803c80u, 0x3c803c80u);
                    PROXY_FENCE();
                    asm volatile("bar.arrive 0, 384;" ::: "memory");
                    TS(31);
                }
                if (f == 5) asm volatile("bar.sync 7, 64;" ::: "memory");
                if (f >= 5) mbar_wait(sb + bdone(f - 5), bpar(f - 5));
                if (f >= 2 && f < 5)
                    while (clock32() - t_start < WDELAY + (f - 2) * WSTEP) {
                    }
                if (elect()) {
                    if (f < 2) mbar_init(sb + BAR_FULL + f * 8, 1);
                    mbar_expect(sb + bfull(f), 16384);
                    tma2d(sb + slot(2 * wl(f)), &tm_w1, sb + bfull(f), 128 * rank + 64 * (f & 1), fieldof(f) * 64);
                    tma2d(sb + slot(wl(f)), &tm_w1, sb + bfull(f), 128 * rank + 64 - 64 * (f & 1), fieldof(f) * 64);
                }
                TS(f);
            }
            if (elect()) mbar_arrive(sb + BAR_GO);
            TS_DUMP(2);
        } else if (warp == 9) {
            if (elect()) {
#pragma unroll
                for (int k = 0; k < 11; k++) mbar_init(sb + BAR_WC + k * 8, k < 10 ? 1 : 8);
                asm volatile("fence.mbarrier_init.release.cluster;" ::: "memory");
            }
            __syncwarp();
            asm volatile("barrier.cluster.arrive.relaxed.aligned;" ::: "memory");
            asm volatile("bar.sync 0, 384;" ::: "memory");
            while (clock32() - t_start < POLL_AT) __nanosleep(100);
            if (elect()) {
                unsigned v, it = 0;
                do {
                    asm volatile("ld.acquire.gpu.global.u32 %0, [%1];" : "=r"(v) : "l"(&g_ready) : "memory");
                } while (v < NPREP && ++it < 4000000u);
                asm volatile("fence.proxy.async.global;" ::: "memory");
                mbar_expect(sb + BAR_SE, 2048);
                bulk(sb + SEOFF, g_se, 2048, sb + BAR_SE);
            }
            __syncwarp();
            TS(0);
            mbar_wait(sb + BAR_GO);
#pragma unroll
            for (int gi = 0; gi < 3; gi++) {
                mbar_wait(sb + bdone(21 + gi), bpar(21 + gi));
                load_wc(gi);
                TS(1 + gi);
            }
        } else if (warp == 10) {
            if (elect()) {
#pragma unroll
                for (int k = 0; k < 8; k++) mbar_init(sb + BAR_DONE + k * 8, 4);
                asm volatile("fence.mbarrier_init.release.cluster;" ::: "memory");
            }
            __syncwarp();
            asm volatile("barrier.cluster.arrive.relaxed.aligned;" ::: "memory");
            asm volatile("bar.arrive 7, 64;" ::: "memory");
            asm volatile("bar.sync 0, 384;" ::: "memory");
#pragma unroll 1
            for (int k = 0; k < 7; k++) {
                while (clock32() - t_start < (uint32_t)(WPF_AT + k * WPF_STEP)) __nanosleep(20);
                if (lane < 6)
                    asm volatile("prefetch.global.L2 [%0];" ::"l"(w1 + (5 + k * 3 + (lane >> 1)) * 32768 + cta * 256 + (lane & 1) * 128));
            }
        } else {
            asm volatile("bar.sync 0, 384;" ::: "memory");
            const uint2 v = __ldg(reinterpret_cast<const uint2*>(w2 + 128 * rank) + lane);
#pragma unroll
            for (int k = 0; k < 2; k++) {
                const uint32_t x = k ? v.y : v.x;
                sts64(sb + w2chunk((lane >> 2) * 4 + 2 * (lane & 1) + k) + (lane & 2) * 4,
                      __float_as_uint(0.5f * __uint_as_float(x << 16)), __float_as_uint(0.5f * __uint_as_float(x & 0xffff0000u)));
            }
            __syncwarp();
            if (lane == 0) mbar_arrive(sb + BAR_W2);
            mbar_wait(sb + BAR_GO);
            if (lane < 16) reinterpret_cast<uint32_t*>(out)[cta * 16 + lane] = 0;
            asm volatile("barrier.cluster.arrive.release.aligned;" ::: "memory");
        }
        {
            uint32_t bw[2][4], z0[4], z1[4];
            mbar_wait(sb + BAR_SE);
            lds128(bw[0], sb + SEOFF + lane * 16);
            lds128(bw[1], sb + SEOFF + 512 + lane * 16);
            asm volatile("bar.sync 2, 384;" ::: "memory");
            lds128(z0, sb + ZQOFF + (tid & 127) * 16);
            lds128(z1, sb + ZQOFF + 2048 + (tid & 127) * 16);
            TS(8);
            float s[2][4] = {};
#pragma unroll
            for (int n = 0; n < 2; n++) {
                mma16816(s[n], z0, bw[0][2 * n], bw[0][2 * n + 1]);
                mma16816(s[n], z1, bw[1][2 * n], bw[1][2 * n + 1]);
            }
            lds128(bw[0], sb + SEOFF + 1024 + lane * 16);
            lds128(bw[1], sb + SEOFF + 1536 + lane * 16);
            float th[8];
#pragma unroll
            for (int k = 0; k < 8; k++) th[k] = gelu_tanh(s[k >> 2][k & 3]);
            SCHED_FENCE();
            TS(9);
            uint32_t gq[4];
#pragma unroll
            for (int k = 0; k < 4; k++)
                gq[k] = pack(s[k >> 1][2 * (k & 1)] * ffma(th[2 * k], 0.5f, 0.5f), s[k >> 1][2 * (k & 1) + 1] * ffma(th[2 * k + 1], 0.5f, 0.5f));
            float a[4][4] = {};
#pragma unroll
            for (int n = 0; n < 4; n++) mma16816(a[n], gq, bw[n >> 1][2 * (n & 1)], bw[n >> 1][2 * (n & 1) + 1]);
#pragma unroll
            for (int k = 0; k < 16; k++)
                if (k < 13 || k == 14) a[k >> 2][k & 3] = tanh_fast(a[k >> 2][k & 3]);
            SCHED_FENCE();
            TS(10);
            uint32_t ap[8];
#pragma unroll
            for (int k = 0; k < 8; k++)
                ap[k] = pack(ffma(a[k >> 1][2 * (k & 1)], 0.5f, 0.5f), ffma(a[k >> 1][2 * (k & 1) + (k < 6)], 0.5f, 0.5f));
            sts128(sb + GOFF + (tid & 127) * 16, ap[0], ap[1], ap[2], ap[3]);
            sts128(sb + GOFF + 2048 + (tid & 127) * 16, ap[4], ap[5], ap[6], ap[7]);
            asm volatile("bar.arrive 3, 384;" ::: "memory");
            TS(11);
        }
        if (warp == 9) {
            load_wc(3);
            load_wc(4);
            mbar_wait(sb + BAR_TD);
            load_wc(5);
            if (lane == 0 && atomicAdd(&g_seen, 1u) == NMAIN - 1) {
                g_seen = 0;
                g_ready = 0;
            }
            if (lane < 16) TS_DUMP(3);
        } else if (warp == 10) {
            uint32_t* dst = reinterpret_cast<uint32_t*>(out) + grp * 32 + lane;
            asm volatile("barrier.cluster.wait.acquire.aligned;" : "+l"(dst)::"memory");
            SCHED_FENCE();
            asm volatile("bar.sync 4, 288;" ::: "memory");
            uint32_t p[4];
            lds64(p[0], p[1], sb + PARTOFF + lane * 8);
            lds64(p[2], p[3], sb + PARTOFF + 256 + lane * 8);
            asm volatile("red.relaxed.gpu.global.add.noftz.bf16x2 [%0], %1;" ::"l"(dst),
                         "r"(pack(__uint_as_float(p[0]) + __uint_as_float(p[2]), __uint_as_float(p[1]) + __uint_as_float(p[3])))
                         : "memory");
        }
    } else {
        asm volatile("setmaxnreg.inc.sync.aligned.u32 232;");
        asm volatile("barrier.cluster.arrive.relaxed.aligned;" ::: "memory");
        const int g = lane >> 2, t = lane & 3, wq = warp & 3, t128 = tid & 127;
        gd0 = opaque(gd0);
        TS(28);
        float acc[84];
#pragma unroll
        for (int k = 0; k < 84; k++) asm volatile("mov.b32 %0, 0;" : "=f"(acc[k]));
        uint32_t e0[9], e1[9], e2[9];
        uint32_t X[13][2][4];
        uint32_t zq[4] = {0, 0, 0, 0};
        const uint64_t dA = mkdesc(sb + w * XDELTA, 16, 1024, 1);
        uint32_t dBlo = (uint32_t)mkdesc(sb + ZOFF, 0, 0, 0);
        const uint32_t xl0 = opaque(sb + (t & 1) * XDELTA + (16 * wq + g) * 128 + (((4 * rank + 2 * w) ^ (4 * (t & 1)) ^ g) << 4));
        const uint32_t hi_half = t >> 1;
        const uint32_t sa0 = opaque(sb + AOFF + t * 4096 + (t >> 1) * 16 + (wq * 32 + g * 4 + w) * 16);
        const uint32_t sa1 = opaque(((g & 2) << 4) | ((t & 1) << 3));
        const uint32_t zero = blockIdx.y;
        auto expand = [&](int k0, int k1) {
#pragma unroll
            for (int k = k0; k < k1; k++)
#pragma unroll
                for (int u = 0; u < 4; u++)
                    asm volatile("shfl.sync.idx.b32 %0, %1, %2, 31, 0xffffffff;"
                                 : "=r"(ids[k][u])
                                 : "r"(k < 12 ? cid[(k - 2) >> 2][k & 1] : w ? cid[2][1] : cid[2][0]),
                                   "r"(2 * (lane >> 3) + 8 * u + (((k - 2) >> 1) & 1)));
        };
        auto twarm = [&]() {
            float s1[8];
            WG_FENCE();
            wgmma_rs_n16_set(s1, zq, mkdesc(sb + AOFF, 16, 512, 2));
            WG_COMMIT();
            WG_WAIT0();
            pin(s1);
            asm volatile("{.reg .pred p; setp.ne.u32 p, %1, 0; @p st.shared.f32 [%1], %0;}" ::"f"(s1[0]), "r"(zero));
        };
        expand(2, 8);
        if (TWARM & 1) twarm();
        TS(26);
        while (clock32() - t_start < PACE1) {
        }
        gather(1);
        expand(8, 13);
        if (TWARM & 2) twarm();
        TS(30);
        while (clock32() - t_start < PACE2) {
        }
        gather(2);
        if (TWARM & 4) twarm();
        asm volatile("bar.sync 0, 384;" ::: "memory");
        auto lift = [&](int i) {
            const int m = 2 * (i >> 2) + (i & 1);
#pragma unroll
            for (int r = 0; r < 2; r++)
#pragma unroll
                for (int cc = 0; cc < 2; cc++) {
                    const uint32_t a = (xl0 ^ (cc * 16)) + xpair(i) + r * 1024;
                    if (i == 12 ? r : (i & 2)) lds128_if(X[i == 12 ? 12 : 2 * m + r][cc], a, hi_half);
                    else lds128(X[2 * m + r][cc], a);
                }
        };
        auto store_pair = [&](int m, int half, const uint32_t (&ea)[9]) {
            uint32_t a;
            if (m < 4) a = sa0 + (sa1 ^ (((m & 1) << 5) | ((m >> 1) << 3)));
            else a = sb + BOFF + t * 2048 + (wq * 32 + g * 4 + ((2 * (m & 1) + w) ^ t)) * 8;
#pragma unroll
            for (int n = half; n < 4; n += 2)
#pragma unroll
                for (int u = 0; u < 2; u++)
                    sts64(a + (m < 4 ? (8 * n + u) * 2048 + n * 32 : (8 * n + u) * 1024),
                          __byte_perm(ea[2 * n], e1[2 * n], u ? 0x7632 : 0x5410),
                          __byte_perm(ea[2 * n + 1], e1[2 * n + 1], u ? 0x7632 : 0x5410));
        };
        auto z_pair = [&](int m, uint32_t a, uint32_t b) {
            asm volatile("{.reg .pred p; setp.eq.u32 p, %4, %5; @p prmt.b32 %0, %2, %3, 0x5410; @p prmt.b32 %1, %2, %3, 0x7632;}"
                         : "+r"(zq[2 * (m >> 2)]), "+r"(zq[2 * (m >> 2) + 1])
                         : "r"(a), "r"(b), "r"(t), "r"(m & 3));
        };

        TS(29);
        mbar_wait(sb + BAR_FULL + w * 8);
        CP_WAIT(2);
        while (clock32() - t_start < START_MIN) {
        }
        if (w == 1) {
            asm volatile("bar.arrive 6, 256;" ::: "memory");
            asm volatile("bar.sync 5, 256;" ::: "memory");
        }
#pragma unroll
        for (int i = 0; i < 13; i++) {
            const uint64_t da = dA + (xpair(i) >> 4) + ((uint64_t)i << 16);
            dBlo += (uint32_t)(w ? wl(2 * i + 1) - (i ? wl(2 * i - 1) : 0) : wl(2 * i) - (i ? wl(2 * i - 2) : 0)) *
                    (uint32_t)((SLOT << 12) - (SLOT >> 3));
            const uint64_t db = mkdesc(0, 0, 1024, 1) | dBlo;
            TS(i);
            WG_FENCE();
            wgmma_ss_n168_acc(acc, da, db + w * 256);
            wgmma_ss_n168_acc(acc, da + 2, db + w * 256 + 128);
            wgmma_ss_n168_acc(acc, da + 4, db + (w ^ 1) * 256);
            wgmma_ss_n168_acc(acc, da + 6, db + (w ^ 1) * 256 + 128);
            WG_COMMIT();
            if (i == 0) {
                if (w == 0) {
                    asm volatile("bar.arrive 5, 256;" ::: "memory");
                    asm volatile("bar.sync 6, 256;" ::: "memory");
                }
            } else {
                mbar_wait(sb + bdone(2 * i - 2) + (w ^ 1) * 8, bpar(2 * i - 2));
            }
            if (i < 10) gather(i + 3);
            if (i == 6) mbar_wait(sb + BAR_W2);
            lift(i);
            if (i == 10 || i == 11) mbar_wait(sb + bdone(2 * i - 2) + w * 8, bpar(2 * i - 2));
            if (i >= 2 && !(i & 1)) {
                z_pair((i - 2) >> 1, e0[8], e1[8]);
                store_pair((i - 2) >> 1, 0, e0);
#pragma unroll
                for (int k = 0; k < 8; k++) e2[k] = e0[k];
            } else if (i >= 3) {
                store_pair((i - 3) >> 1, 1, e2);
            }
            const uint32_t rdy = i < 12 ? mbar_test(sb + bfull(2 * i + 2) + w * 8, bpar(2 * i + 2)) : 0;
            WG_WAIT0();
            pin(acc);
            if (i == 12) TS(13);
            if (i == 0) TS(27);
            if (i < 10) CP_WAIT(2);
            else if (i == 10) CP_WAIT(1);
            else if (i == 11) CP_WAIT(0);
            if (i < 12 && lane == 0) mbar_arrive(sb + bdone(2 * i) + w * 8);
#pragma unroll
            for (int k = 0; k < 9; k++) {
                const int k0 = 64 + 2 * (k & 5) + ((k >> 1) & 1);
                const uint32_t v = k == 8 ? pack(acc[80], acc[82]) : i < 12 ? pack(acc[64 + 2 * k], acc[65 + 2 * k]) : pack(acc[k0], acc[k0 + 4]);
                if (i & 1) e1[k] = v;
                else e0[k] = v;
            }
            if (i < 12) {
#pragma unroll
                for (int k = 64; k < 83; k++)
                    if (k != 81) asm volatile("mov.b32 %0, %1;" : "+f"(acc[k]) : "r"(zero));
                mbar_wait_unless(rdy, sb + bfull(2 * i + 2) + w * 8, bpar(2 * i + 2));
            } else {
                z_pair(6, e0[8], 0);
                sts128(sb + ZQOFF + w * 2048 + t128 * 16, zq[0], zq[1], zq[2], zq[3]);
                asm volatile("bar.arrive 2, 384;" ::: "memory");
            }
        }
        TS(14);

        uint32_t ai[8];
        float sum0 = 0.f, sum1 = 0.f;
        float th[32];
        uint32_t hw[4][4];
        auto deep_issue = [&](int k2) {
            lds128(hw[k2], ((sb + w2chunk(w * 16 + t)) ^ ((k2 & 1) * 64)) + k2 * 512);
#pragma unroll
            for (int k = 8 * k2; k < 8 * k2 + 8; k++) th[k] = gelu_tanh(acc[k]);
        };
        auto deep_use = [&](int k2) {
#pragma unroll
            for (int k = 8 * k2; k < 8 * k2 + 8; k++) {
                const float h = __uint_as_float(hw[k2][((k >> 1) & 2) + (k & 1)]);
                const float y = ffma(th[k], h, h);
                if (k & 2) sum1 = ffma(acc[k], y, sum1);
                else sum0 = ffma(acc[k], y, sum0);
            }
        };
        auto deep_send = [&](int k0, int k1) {
#pragma unroll
            for (int k = k0; k < k1; k++)
                sts128(sb + EXOFF + w * SLOT + t128 * 16 + k * 2048, pack(acc[32 + 8 * k], acc[33 + 8 * k]),
                       pack(acc[34 + 8 * k], acc[35 + 8 * k]), pack(acc[36 + 8 * k], acc[37 + 8 * k]), pack(acc[38 + 8 * k], acc[39 + 8 * k]));
        };
        uint32_t o[4][4];
        auto deep_recv = [&](int k0, int k1) {
#pragma unroll
            for (int k = k0; k < k1; k++) lds128(o[k], sb + EXOFF + (w ^ 1) * SLOT + t128 * 16 + k * 2048);
        };
        auto deep_add = [&](int k0, int k1) {
            const uint32_t eye = (g >> 1) == t ? ((g & 1) ? 0x3f800000u : 0x3f80u) : 0u;
#pragma unroll
            for (int k = 2 * k0; k < 2 * k1; k++)
                asm volatile("mma.sync.aligned.m16n8k8.row.col.f32.bf16.bf16.f32 {%0,%1,%2,%3}, {%4,%5}, {%6}, {%0,%1,%2,%3};"
                             : "+f"(acc[4 * k]), "+f"(acc[4 * k + 1]), "+f"(acc[4 * k + 2]), "+f"(acc[4 * k + 3])
                             : "r"(o[k >> 1][2 * (k & 1)]), "r"(o[k >> 1][2 * (k & 1) + 1]), "r"(eye));
        };
        auto store_last = [&]() {
#pragma unroll
            for (int n = 0; n < 4; n++) sts64(sb + COFF + w * 4096 + n * 1024 + (t128 ^ w) * 8, e0[2 * n], e0[2 * n + 1]);
            store_pair(5, 1, e2);
        };
        const uint32_t la = sb + AOFF + w * (16 * 2048 + 64) + (wq * 32 + g * 4 + (t ^ (g & 2))) * 16;
        const uint32_t lb = sb + BOFF + w * (16 * 1024) + t128 * 8;
        const uint32_t lc0 = sb + COFF + (t & 1) * (4096 + 8) + w * 2048 + (wq * 8 + g) * 32, lc1 = lc0 ^ 8;
        uint32_t Ap[2][2][4];
        auto load_a = [&](int s) {
            const int e = estep(s);
            lds128(Ap[s & 1][0], la + e * 2048 + (e >> 2) * 16);
            lds64(Ap[s & 1][1][0], Ap[s & 1][1][1], (lb ^ ((e & 6) * 4)) + e * 1024);
            if (!(s & 2)) lds64(Ap[s & 1][1][2], Ap[s & 1][1][3], ((e & 2) ? lc1 : lc0) + (e & 1) * 1024 + (e & 4) * 4);
        };
        {
            uint32_t v[2][4];
            deep_send(0, 2);
            asm volatile("bar.sync 1, 256;" ::: "memory");
            deep_recv(0, 2);
            deep_send(2, 4);
            TS(15);
            deep_add(0, 2);
            deep_issue(0);
            asm volatile("bar.sync 1, 256;" ::: "memory");
            deep_recv(2, 4);
            SCHED_FENCE();
            deep_add(2, 4);
            TS(16);
            deep_issue(1);
            deep_use(0);
            store_last();
            SCHED_FENCE();
            TS(17);
            deep_issue(2);
            deep_use(1);
            mbar_wait(sb + BAR_WC);
            deep_use(2);
            TS(18);
            asm volatile("bar.sync 3, 384;" ::: "memory");
            lds128(v[0], sb + GOFF + t128 * 16);
            lds128(v[1], sb + GOFF + 2048 + t128 * 16);
            load_a(0);
            load_a(1);
            deep_issue(3);
#pragma unroll
            for (int k = 0; k < 8; k++) ai[k] = v[k >> 2][k & 3];
        }
        TS(19);

        uint32_t fin_a, dsum[2];
        {
            uint64_t dW[4];
#pragma unroll
            for (int k = 0; k < 4; k++) dW[k] = DBASE + (wcslot(0) >> 4) + (k >> 1) * 128 + (k & 1) * 2;
            uint32_t Aq[2][2][4], pq[13], gate[13];
            float S[2][2][16];
            auto scale_a = [&](int s) {
#pragma unroll
                for (int k = 0; k < ((s & 2) ? 6 : 8); k++)
                    Aq[s & 1][k >> 2][k & 3] = hmul2(Ap[s & 1][k >> 2][k & 3], ai[k < 4 ? k ^ (estep(s) & 2) : k]);
            };
            auto sbuf = [](int s) { return s <= DB0 ? 0 : (s - DB0) & 1; };
            auto issue = [&](int s) {
                const bool first = s == 0 || s == DB0 + 1;
                WG_FENCE();
                if (first) wgmma_rs_n32_set(S[sbuf(s)][0], Ap[s & 1][0], dW[0]);
                else wgmma_rs_n32_pred(S[sbuf(s)][0], Ap[s & 1][0], dW[0], zero);
                wgmma_rs_n32_acc(S[sbuf(s)][0], Ap[s & 1][1], dW[1]);
                if (first) wgmma_rs_n32_set(S[sbuf(s)][1], Aq[s & 1][0], dW[2]);
                else wgmma_rs_n32_pred(S[sbuf(s)][1], Aq[s & 1][0], dW[2], zero);
                wgmma_rs_n32_acc(S[sbuf(s)][1], Aq[s & 1][1], dW[3]);
                WG_COMMIT();
                if (s < 15) {
#pragma unroll
                    for (int k = 0; k < 4; k++)
                        asm volatile("add.s64 %0, %0, %1;" : "+l"(dW[k]) : "l"((int64_t)((wcslot(s + 1) - wcslot(s)) / 16)));
                }
            };
            scale_a(0);
            issue(0);
            SCHED_FENCE();
            deep_use(3);
            scale_a(1);
            mbar_wait(sb + BAR_WC + 8);
#pragma unroll
            for (int e = 0; e < 16; e++) {
                if (e >= DB0 && e < 15) {
                    issue(e + 1);
                    WG_WAIT1();
                } else {
                    WG_WAIT0();
                }
                pin(S[sbuf(e)][0]);
                pin(S[sbuf(e)][1]);
                if (e == 0 && lane == 0) mbar_arrive(sb + BAR_TD);
                if (e == 0) TS(20);
                if (e + 2 < 16) load_a(e + 2);
                uint32_t v[13];
                auto accum = [&](int q) {
                    const uint32_t x = X[q][(e >> 1) & 1][e >> 2];
                    pq[q] = (e & 1) ? hfma2_bcast<1>(v[q], x, pq[q]) : hfma2_bcast<0>(v[q], x, e ? pq[q] : 0u);
                };
#pragma unroll
                for (int q = 0; q < 13; q++) {
                    const int ix = 4 * (q >> 2) + 2 * (q & 1) + ((q >> 1) & 1);
                    v[q] = pack(S[sbuf(e)][0][ix], S[sbuf(e)][1][ix ^ 1]);
                    if (q == 12)
                        asm volatile("{.reg .pred p; setp.ne.u32 p, %3, 0; @p cvt.rn.bf16x2.f32 %0, %2, %1;}"
                                     : "+r"(v[q])
                                     : "f"(S[sbuf(e)][0][14]), "f"(S[sbuf(e)][1][15]), "r"(hi_half));
                    if (e >= DB0 || q < 7) accum(q);
                }
                if (e < DB0) {
                    issue(e + 1);
                    SCHED_FENCE();
#pragma unroll
                    for (int q = 7; q < 13; q++) accum(q);
                }
                if (e == 3) {
                    const float h0 = __uint_as_float(__float_as_uint(sum0) & 0xffff0000u);
                    const float h1 = __uint_as_float(__float_as_uint(sum1) & 0xffff0000u);
                    dsum[0] = pack(sum0 - h0, h0);
                    dsum[1] = pack(sum1 - h1, h1);
                }
                if (e == 13) {
                    fin_a = opaque(sb + PARTOFF + (warp * 16 + g) * 4);
                }
                if (e == 14) {
#pragma unroll
                    for (int q = 0; q < 13; q++)
                        asm volatile("prmt.b32 %0, %1, 0x3f80, %2;"
                                     : "=r"(gate[q])
                                     : "r"(q < 12 ? ai[2 * (q >> 2) + (q & 1)] : hi_half ? ai[7] : ai[6]), "r"((q & 2) ? 0x3254 : 0x1054));
                }
                if (e + 2 < 16) scale_a(e + 2);
                if (e == 0 || e == 3 || e == 6 || e == 9) mbar_wait(sb + BAR_WC + (e / 3 + 2) * 8);
                else if (e < 15) SCHED_FENCE();
                if (e == 7) TS(21);
            }
            float r0[4] = {0.f, 0.f, 0.f, 0.f}, r1[4] = {0.f, 0.f, 0.f, 0.f}, r2[4] = {0.f, 0.f, 0.f, 0.f};
#pragma unroll
            for (int c = 0; c < 3; c++) {
                const uint32_t a[4] = {pq[4 * c], pq[4 * c + 1], pq[4 * c + 2], pq[4 * c + 3]};
                mma16816(r0, a, gate[4 * c], gate[4 * c + 2]);
                mma16816(r1, a, gate[4 * c + 1], gate[4 * c + 3]);
            }
            const uint32_t rest[4] = {dsum[0], dsum[1], hi_half ? 0u : pq[12], hi_half ? pq[12] : 0u};
            mma16816(r2, rest, 0x3f803f80u, gate[12]);
            sum0 = (g & 1) ? r0[1] + r2[1] : r0[0] + r2[0];
            sum1 = (g & 1) ? r1[3] + r2[3] : r1[2] + r2[2];
        }
        TS(22);
        {
            asm volatile("{.reg .pred p; setp.eq.u32 p, %3, %4; @p st.shared.f32 [%0], %1; @p st.shared.f32 [%0 + 32], %2;}" ::"r"(fin_a),
                         "f"(sum0), "f"(sum1), "r"(t), "r"(g >> 1)
                         : "memory");
            asm volatile("bar.arrive 4, 288;" ::: "memory");
            if (wq == 0) TS_DUMP(w);
        }
    }
}

typedef CUresult (*EncodeFn)(CUtensorMap*, CUtensorMapDataType, cuuint32_t, void*, const cuuint64_t*, const cuuint64_t*,
                             const cuuint32_t*, const cuuint32_t*, CUtensorMapInterleave, CUtensorMapSwizzle,
                             CUtensorMapL2promotion, CUtensorMapFloatOOBfill);

}

extern "C" void kernel_launch(void* const* d_in, const int* in_sizes, int n_in, void* d_out, int out_size) {
    static EncodeFn encode = nullptr;
    if (!encode) {
        void* fn = nullptr;
        cudaDriverEntryPointQueryResult qr;
        cudaGetDriverEntryPoint("cuTensorMapEncodeTiled", &fn, cudaEnableDefault, &qr);
        encode = (EncodeFn)fn;
        cudaFuncSetAttribute(fibinet_kernel, cudaFuncAttributeMaxDynamicSharedMemorySize, SMEM_BYTES);
    }
    CUtensorMap tm;
    const cuuint64_t gd[2] = {NH, NF * ND};
    const cuuint64_t gs[1] = {NH * 2};
    const cuuint32_t bd[2] = {64, 64}, es[2] = {1, 1};
    encode(&tm, CU_TENSOR_MAP_DATA_TYPE_BFLOAT16, 2, d_in[6], gd, gs, bd, es, CU_TENSOR_MAP_INTERLEAVE_NONE,
           CU_TENSOR_MAP_SWIZZLE_128B, CU_TENSOR_MAP_L2_PROMOTION_L2_256B, CU_TENSOR_MAP_FLOAT_OOB_FILL_NONE);
    CUtensorMap tb;
    const cuuint64_t gd2[2] = {ND, ND};
    const cuuint64_t gs2[1] = {ND * 2};
    encode(&tb, CU_TENSOR_MAP_DATA_TYPE_BFLOAT16, 2, d_in[4], gd2, gs2, bd, es, CU_TENSOR_MAP_INTERLEAVE_NONE,
           CU_TENSOR_MAP_SWIZZLE_128B, CU_TENSOR_MAP_L2_PROMOTION_L2_256B, CU_TENSOR_MAP_FLOAT_OOB_FILL_NONE);
    fibinet_kernel<<<NPREP + NMAIN, 384, SMEM_BYTES>>>(
        (const int*)d_in[0], (const uint4*)d_in[1], (const __nv_bfloat16*)d_in[2], (const __nv_bfloat16*)d_in[3],
        (const __nv_bfloat16*)d_in[5], (const unsigned char*)d_in[6], (const __nv_bfloat16*)d_in[7], (__nv_bfloat16*)d_out, tm, tb);
}
```

```cpp
#include <cuda_runtime.h>
#include <cuda_bf16.h>
#include <cuda.h>
#include <stdint.h>

namespace {

constexpr int NF = 26, ND = 64, NH = 256, NR = 13;
constexpr int NPREP = 4;
constexpr int NMAIN = 128;

constexpr int SLOT = 8192;
constexpr int ZOFF = 15 * SLOT;
__host__ __device__ constexpr int slot(int s) { return ZOFF - s * SLOT; }
constexpr int BOFF = ZOFF + SLOT;
constexpr int AOFF = BOFF + 32768;
constexpr int COFF = slot(12);
constexpr int MOFF = AOFF + 65536 + 128;
constexpr int BAR_FULL = MOFF, BAR_DONE = MOFF + 64, BAR_WC = MOFF + 128, BAR_GO = MOFF + 176, BAR_SE = MOFF + 184,
              BAR_W2 = MOFF + 192, BAR_TD = MOFF + 200, BAR_Z = MOFF + 208;
__host__ __device__ constexpr int bfull(int f) { return BAR_FULL + (f & 7) * 8; }
__host__ __device__ constexpr int bdone(int f) { return BAR_DONE + (f & 7) * 8; }
__host__ __device__ constexpr int bpar(int f) { return (f >> 3) & 1; }
constexpr int PARTOFF = MOFF + 256, SEOFF = MOFF + 768;
constexpr int SMEM_BYTES = MOFF + 2944;
constexpr int XDELTA = 2 * SLOT;
__host__ __device__ constexpr int xpair(int i) {
    return (i & 3) == 0 ? slot(11) : (i & 3) == 1 ? BOFF : (i & 3) == 2 ? BOFF + SLOT : slot(15);
}
__host__ __device__ constexpr int wl(int f) { return f % 5 == 0 ? 1 : f % 5 == 4 ? 7 : f % 5 + 2; }
__host__ __device__ constexpr int wcslot(int c) {
    return c == 0 ? slot(3) : c == 1 ? slot(8) : c == 2 ? slot(10) : c == 3 ? slot(15) : c == 4 ? slot(13)
         : c == 5 ? slot(11) : c == 6 ? slot(9) : c == 7 ? slot(14) : c == 8 ? slot(7) : c == 9 ? slot(2)
         : c == 10 ? slot(1) : c == 11 ? slot(4) : c == 12 ? slot(5) : c == 13 ? slot(6) : c == 14 ? ZOFF : slot(3);
}
__host__ __device__ constexpr int wcfirst(int gi) { return gi < 3 ? gi : gi == 3 ? 5 : gi == 4 ? 8 : gi == 5 ? 11 : 16; }
constexpr int EXOFF = slot(5);
constexpr int ZQOFF = slot(6);
constexpr int GOFF = ZQOFF + 4096;
__host__ __device__ constexpr int w2chunk(int c) { return ZOFF + c * 128 + ((5 ^ (c & 7)) << 4); }

__device__ uint4 g_wc[2 * 16 * 8192 / 16];
__device__ uint4 g_se[2048 / 16];
__device__ unsigned g_ready;
__device__ unsigned g_seen;

__host__ __device__ constexpr int fieldof(int f) { return f < 24 ? 4 * (f >> 2) + 2 * (f & 1) + ((f >> 1) & 1) : f; }
__device__ __forceinline__ int fmap(int n) { return n < 24 ? n : 24 + ((n >> 1) & 1); }
__host__ __device__ constexpr int estep(int s) { return (s & 1) + 2 * (s >> 2) + 4 * (s & 2); }

__device__ __forceinline__ uint64_t mkdesc(uint32_t addr, uint32_t lbo, uint32_t sbo, int sw) {
    return (uint64_t)((addr & 0x3ffff) >> 4) | ((uint64_t)(lbo >> 4) << 16) | ((uint64_t)(sbo >> 4) << 32) |
           ((uint64_t)sw << 62);
}
__device__ __forceinline__ void mbar_init(uint32_t b, uint32_t n) {
    asm volatile("mbarrier.init.shared.b64 [%0], %1;" ::"r"(b), "r"(n) : "memory");
}
__device__ __forceinline__ void mbar_wait(uint32_t b, uint32_t par = 0) {
    asm volatile(
        "{\n.reg .pred p, q;\n.reg .u32 n;\n"
        "mbarrier.try_wait.parity.shared.b64 p, [%0], %1;\n@p bra.uni WD%=;\nmov.u32 n, 0;\n"
        "WL%=:\nmbarrier.try_wait.parity.shared.b64 p, [%0], %1;\n@p bra.uni WD%=;\n"
        "add.u32 n, n, 1;\nsetp.lt.u32 q, n, 4000000;\n@q bra.uni WL%=;\nWD%=:\n}\n" ::"r"(b), "r"(par)
        : "memory");
}
__device__ __forceinline__ uint32_t mbar_test(uint32_t b, uint32_t par) {
    uint32_t ok;
    asm volatile("{.reg .pred p; mbarrier.test_wait.parity.shared.b64 p, [%1], %2; selp.u32 %0, 1, 0, p;}"
                 : "=r"(ok)
                 : "r"(b), "r"(par)
                 : "memory");
    return ok;
}
__device__ __forceinline__ void mbar_wait_unless(uint32_t ok, uint32_t b, uint32_t par) {
    asm volatile(
        "{\n.reg .pred p, q;\n.reg .u32 n;\n"
        "setp.ne.u32 p, %1, 0;\n@p bra.uni WD%=;\nmov.u32 n, 0;\n"
        "WL%=:\nmbarrier.try_wait.parity.shared.b64 p, [%0], %2;\n@p bra.uni WD%=;\n"
        "add.u32 n, n, 1;\nsetp.lt.u32 q, n, 4000000;\n@q bra.uni WL%=;\nWD%=:\n}\n" ::"r"(b), "r"(ok), "r"(par)
        : "memory");
}
__device__ __forceinline__ void mbar_arrive(uint32_t b) {
    asm volatile("mbarrier.arrive.shared.b64 _, [%0];" ::"r"(b) : "memory");
}
__device__ __forceinline__ void mbar_expect(uint32_t b, uint32_t bytes) {
    asm volatile("mbarrier.arrive.expect_tx.shared.b64 _, [%0], %1;" ::"r"(b), "r"(bytes) : "memory");
}
__device__ __forceinline__ uint32_t opaque(uint32_t v) { return __shfl_sync(0xffffffffu, v, threadIdx.x); }
__device__ __forceinline__ bool elect() {
    uint32_t p;
    asm volatile("{.reg .pred q; elect.sync _|q, 0xffffffff; selp.u32 %0, 1, 0, q;}" : "=r"(p));
    return p;
}
__device__ __forceinline__ void tma2d(uint32_t dst, const CUtensorMap* m, uint32_t bar, int x, int y) {
    asm volatile(
        "cp.async.bulk.tensor.2d.shared::cluster.global.mbarrier::complete_tx::bytes [%0], [%1, {%3, %4}], [%2];" ::"r"(dst),
        "l"(m), "r"(bar), "r"(x), "r"(y)
        : "memory");
}
__device__ __forceinline__ void bulk(uint32_t dst, const void* src, uint32_t bytes, uint32_t bar) {
    asm volatile("cp.async.bulk.shared::cluster.global.mbarrier::complete_tx::bytes [%0], [%1], %2, [%3];" ::"r"(dst),
                 "l"(src), "r"(bytes), "r"(bar)
                 : "memory");
}
__device__ __forceinline__ void cp16(uint32_t dst, const void* src) {
    asm volatile("cp.async.cg.shared.global [%0], [%1], 16;" ::"r"(dst), "l"(src) : "memory");
}
__device__ __forceinline__ void lds128(uint32_t (&v)[4], uint32_t a) {
    asm volatile("ld.shared.v4.u32 {%0,%1,%2,%3}, [%4];" : "=r"(v[0]), "=r"(v[1]), "=r"(v[2]), "=r"(v[3]) : "r"(a) : "memory");
}
__device__ __forceinline__ void lds128_if(uint32_t (&v)[4], uint32_t a, uint32_t p) {
    asm volatile("{.reg .pred q; setp.ne.u32 q, %5, 0; @q ld.shared.v4.u32 {%0,%1,%2,%3}, [%4];}"
                 : "+r"(v[0]), "+r"(v[1]), "+r"(v[2]), "+r"(v[3])
                 : "r"(a), "r"(p)
                 : "memory");
}
__device__ __forceinline__ void lds64(uint32_t& x, uint32_t& y, uint32_t a) {
    asm volatile("ld.shared.v2.u32 {%0,%1}, [%2];" : "=r"(x), "=r"(y) : "r"(a) : "memory");
}
__device__ __forceinline__ void sts128(uint32_t a, uint32_t x, uint32_t y, uint32_t z, uint32_t w) {
    asm volatile("st.shared.v4.u32 [%0], {%1,%2,%3,%4};" ::"r"(a), "r"(x), "r"(y), "r"(z), "r"(w) : "memory");
}
__device__ __forceinline__ void sts64(uint32_t a, uint32_t x, uint32_t y) {
    asm volatile("st.shared.v2.u32 [%0], {%1,%2};" ::"r"(a), "r"(x), "r"(y) : "memory");
}
__device__ __forceinline__ uint32_t pack(float lo, float hi) {
    uint32_t r;
    asm volatile("cvt.rn.bf16x2.f32 %0, %1, %2;" : "=r"(r) : "f"(hi), "f"(lo));
    return r;
}
__device__ __forceinline__ uint32_t hmul2(uint32_t a, uint32_t b) {
    uint32_t r;
    asm volatile("mul.rn.bf16x2 %0, %1, %2;" : "=r"(r) : "r"(a), "r"(b));
    return r;
}
template <int H>
__device__ __forceinline__ uint32_t hfma2_bcast(uint32_t a, uint32_t x, uint32_t c) {
    uint32_t r;
    if (H)
        asm volatile("{.reg .b16 l, h; .reg .b32 s; mov.b32 {l, h}, %2; mov.b32 s, {h, h}; fma.rn.bf16x2 %0, %1, s, %3;}"
                     : "=r"(r)
                     : "r"(a), "r"(x), "r"(c));
    else
        asm volatile("{.reg .b16 l, h; .reg .b32 s; mov.b32 {l, h}, %2; mov.b32 s, {l, l}; fma.rn.bf16x2 %0, %1, s, %3;}"
                     : "=r"(r)
                     : "r"(a), "r"(x), "r"(c));
    return r;
}
__device__ __forceinline__ float ffma(float a, float b, float c) {
    float r;
    asm volatile("fma.rn.f32 %0, %1, %2, %3;" : "=f"(r) : "f"(a), "f"(b), "f"(c));
    return r;
}
__device__ __forceinline__ float tanh_fast(float x) {
    float r;
    asm volatile("tanh.approx.f32 %0, %1;" : "=f"(r) : "f"(x));
    return r;
}
__device__ __forceinline__ float gelu_tanh(float x) {
    float r;
    asm volatile(
        "{.reg .f32 a; mul.f32 a, %1, %1; fma.rn.f32 a, a, 0f3D122279, 0f3F4C422A; mul.f32 a, a, %1; tanh.approx.f32 %0, a;}"
        : "=f"(r)
        : "f"(x));
    return r;
}
__device__ __forceinline__ void mma16816(float (&d)[4], const uint32_t (&a)[4], uint32_t b0, uint32_t b1) {
    asm volatile("mma.sync.aligned.m16n8k16.row.col.f32.bf16.bf16.f32 {%0,%1,%2,%3}, {%4,%5,%6,%7}, {%8,%9}, {%0,%1,%2,%3};"
                 : "+f"(d[0]), "+f"(d[1]), "+f"(d[2]), "+f"(d[3])
                 : "r"(a[0]), "r"(a[1]), "r"(a[2]), "r"(a[3]), "r"(b0), "r"(b1));
}
__device__ __forceinline__ uint32_t clock32() {
    uint32_t c;
    asm volatile("mov.u32 %0, %%clock;" : "=r"(c)::"memory");
    return c;
}
#define WG_FENCE() asm volatile("wgmma.fence.sync.aligned;" ::: "memory")
#define WG_COMMIT() asm volatile("wgmma.commit_group.sync.aligned;" ::: "memory")
#define WG_WAIT0() asm volatile("wgmma.wait_group.sync.aligned 0;" ::: "memory")
#define WG_WAIT1() asm volatile("wgmma.wait_group.sync.aligned 1;" ::: "memory")
#define CP_COMMIT() asm volatile("cp.async.commit_group;" ::: "memory")
#define CP_WAIT(n) asm volatile("cp.async.wait_group %0;" ::"n"(n) : "memory")
#define SCHED_FENCE() asm volatile("pmevent 0;" ::: "memory")
#define PROXY_FENCE() asm volatile("fence.proxy.async.shared::cta;" ::: "memory")
template <int N>
__device__ __forceinline__ void pin(float (&d)[N]) {
#pragma unroll
    for (int i = 0; i < N; i++) asm volatile("" : "+f"(d[i])::"memory");
}
#define TS(k)
#define TS_DUMP(role)

__device__ __forceinline__ void wgmma_ss_n168_acc(float (&d)[84], uint64_t da, uint64_t db) {
    asm volatile(
        "wgmma.mma_async.sync.aligned.m64n168k16.f32.bf16.bf16 "
        "{%0,%1,%2,%3,%4,%5,%6,%7,%8,%9,%10,%11,%12,%13,%14,%15,"
        "%16,%17,%18,%19,%20,%21,%22,%23,%24,%25,%26,%27,%28,%29,%30,%31,"
        "%32,%33,%34,%35,%36,%37,%38,%39,%40,%41,%42,%43,%44,%45,%46,%47,"
        "%48,%49,%50,%51,%52,%53,%54,%55,%56,%57,%58,%59,%60,%61,%62,%63,"
        "%64,%65,%66,%67,%68,%69,%70,%71,%72,%73,%74,%75,%76,%77,%78,%79,"
        "%80,%81,%82,%83}, "
        "%84, %85, 1, 1, 1, 0, 1;"
        : "+f"(d[0]), "+f"(d[1]), "+f"(d[2]), "+f"(d[3]), "+f"(d[4]), "+f"(d[5]), "+f"(d[6]), "+f"(d[7]),
          "+f"(d[8]), "+f"(d[9]), "+f"(d[10]), "+f"(d[11]), "+f"(d[12]), "+f"(d[13]), "+f"(d[14]), "+f"(d[15]),
          "+f"(d[16]), "+f"(d[17]), "+f"(d[18]), "+f"(d[19]), "+f"(d[20]), "+f"(d[21]), "+f"(d[22]), "+f"(d[23]),
          "+f"(d[24]), "+f"(d[25]), "+f"(d[26]), "+f"(d[27]), "+f"(d[28]), "+f"(d[29]), "+f"(d[30]), "+f"(d[31]),
          "+f"(d[32]), "+f"(d[33]), "+f"(d[34]), "+f"(d[35]), "+f"(d[36]), "+f"(d[37]), "+f"(d[38]), "+f"(d[39]),
          "+f"(d[40]), "+f"(d[41]), "+f"(d[42]), "+f"(d[43]), "+f"(d[44]), "+f"(d[45]), "+f"(d[46]), "+f"(d[47]),
          "+f"(d[48]), "+f"(d[49]), "+f"(d[50]), "+f"(d[51]), "+f"(d[52]), "+f"(d[53]), "+f"(d[54]), "+f"(d[55]),
          "+f"(d[56]), "+f"(d[57]), "+f"(d[58]), "+f"(d[59]), "+f"(d[60]), "+f"(d[61]), "+f"(d[62]), "+f"(d[63]),
          "+f"(d[64]), "+f"(d[65]), "+f"(d[66]), "+f"(d[67]), "+f"(d[68]), "+f"(d[69]), "+f"(d[70]), "+f"(d[71]),
          "+f"(d[72]), "+f"(d[73]), "+f"(d[74]), "+f"(d[75]), "+f"(d[76]), "+f"(d[77]), "+f"(d[78]), "+f"(d[79]),
          "+f"(d[80]), "+f"(d[81]), "+f"(d[82]), "+f"(d[83])
        : "l"(da), "l"(db));
}

__device__ __forceinline__ void wgmma_rs_n32_set(float (&d)[16], const uint32_t (&a)[4], uint64_t db) {
    asm volatile(
        "wgmma.mma_async.sync.aligned.m64n32k16.f32.bf16.bf16 "
        "{%0,%1,%2,%3,%4,%5,%6,%7,%8,%9,%10,%11,%12,%13,%14,%15}, "
        "{%16,%17,%18,%19}, %20, 0, 1, 1, 0;"
        : "=f"(d[0]), "=f"(d[1]), "=f"(d[2]), "=f"(d[3]), "=f"(d[4]), "=f"(d[5]), "=f"(d[6]), "=f"(d[7]),
          "=f"(d[8]), "=f"(d[9]), "=f"(d[10]), "=f"(d[11]), "=f"(d[12]), "=f"(d[13]), "=f"(d[14]), "=f"(d[15])
        : "r"(a[0]), "r"(a[1]), "r"(a[2]), "r"(a[3]), "l"(db));
}

__device__ __forceinline__ void wgmma_rs_n32_acc(float (&d)[16], const uint32_t (&a)[4], uint64_t db) {
    asm volatile(
        "wgmma.mma_async.sync.aligned.m64n32k16.f32.bf16.bf16 "
        "{%0,%1,%2,%3,%4,%5,%6,%7,%8,%9,%10,%11,%12,%13,%14,%15}, "
        "{%16,%17,%18,%19}, %20, 1, 1, 1, 0;"
        : "+f"(d[0]), "+f"(d[1]), "+f"(d[2]), "+f"(d[3]), "+f"(d[4]), "+f"(d[5]), "+f"(d[6]), "+f"(d[7]),
          "+f"(d[8]), "+f"(d[9]), "+f"(d[10]), "+f"(d[11]), "+f"(d[12]), "+f"(d[13]), "+f"(d[14]), "+f"(d[15])
        : "r"(a[0]), "r"(a[1]), "r"(a[2]), "r"(a[3]), "l"(db));
}

__device__ __forceinline__ void wgmma_rs_n16_set(float (&d)[8], const uint32_t (&a)[4], uint64_t db) {
    asm volatile(
        "wgmma.mma_async.sync.aligned.m64n16k16.f32.bf16.bf16 "
        "{%0,%1,%2,%3,%4,%5,%6,%7}, "
        "{%8,%9,%10,%11}, %12, 0, 1, 1, 0;"
        : "=f"(d[0]), "=f"(d[1]), "=f"(d[2]), "=f"(d[3]), "=f"(d[4]), "=f"(d[5]), "=f"(d[6]), "=f"(d[7])
        : "r"(a[0]), "r"(a[1]), "r"(a[2]), "r"(a[3]), "l"(db));
}

__device__ __forceinline__ void wgmma_rs_n32_pred(float (&d)[16], const uint32_t (&a)[4], uint64_t db, uint32_t scale_d) {
    asm volatile(
        "{.reg .pred p; setp.ne.u32 p, %21, 0; wgmma.mma_async.sync.aligned.m64n32k16.f32.bf16.bf16 "
        "{%0,%1,%2,%3,%4,%5,%6,%7,%8,%9,%10,%11,%12,%13,%14,%15}, "
        "{%16,%17,%18,%19}, %20, p, 1, 1, 0;}"
        : "+f"(d[0]), "+f"(d[1]), "+f"(d[2]), "+f"(d[3]), "+f"(d[4]), "+f"(d[5]), "+f"(d[6]), "+f"(d[7]),
          "+f"(d[8]), "+f"(d[9]), "+f"(d[10]), "+f"(d[11]), "+f"(d[12]), "+f"(d[13]), "+f"(d[14]), "+f"(d[15])
        : "r"(a[0]), "r"(a[1]), "r"(a[2]), "r"(a[3]), "l"(db), "r"(scale_d));
}

__device__ __forceinline__ void prep_cta(uint32_t sb, int c, const __nv_bfloat16* __restrict__ wc,
                                         const __nv_bfloat16* __restrict__ se1, const __nv_bfloat16* __restrict__ se2) {
    const int tid = threadIdx.x, lane = tid & 31, warp = tid >> 5, s = c >> 1;
    constexpr int ZERO = 16 * NF * 128;
#pragma unroll
    for (int q = tid; q < 16 * NF * 8; q += 384) {
        const int i = q >> 7, nn = (q >> 3) & 15, j = fmap((16 * (c & 1) + nn) ^ s);
        cp16(sb + (q >> 3) * 128 + (((q & 7) ^ (i & 1) ^ ((i >> 3) << 1)) << 4), wc + ((s * NF + i) * NF + j) * ND + (q & 7) * 8);
    }
    if (tid < 8) sts128(sb + ZERO + tid * 16, 0, 0, 0, 0);
    if (tid < 256) {
        const int n = ((tid >> 2) & 1) * 8 + (tid >> 5) + (s ? (c & 1) * 16 : 0);
        const int k = ((tid >> 1) & 1) * 8 + ((tid >> 3) & 3) * 2 + (tid & 1), mm = k >> 1, u = k & 1;
        const int f = s ? fmap(n) : mm < 6 ? 4 * mm + 2 * c + u : (mm == 6 && u == 0) ? 24 + c : -1;
        float v = 0.f;
        if (f >= 0 && (s ? k : n) < NR) v = __bfloat162float(s ? se2[k * NF + f] : se1[f * NR + n]);
        reinterpret_cast<__nv_bfloat16*>(g_se)[c * 256 + tid] = __float2bfloat16(s ? 0.5f * v : v);
    }
    asm volatile("cp.async.wait_all;" ::: "memory");
    __syncthreads();
    const int k = 4 * (lane & 6) + 2 * (lane >> 3) + (lane & 1), i = fmap(k);
    const int g = lane >> 2, t = lane & 3;
#pragma unroll 4
    for (int task = warp; task < 128; task += 12) {
        const int nn = task & 15, eg = task >> 4, n = 16 * (c & 1) + nn;
        const uint32_t a = sb + (k < 28 ? (i * 16 + nn) * 128 : ZERO) + ((eg ^ (i & 1) ^ ((i >> 3) << 1)) << 4);
        uint4 v;
        asm volatile("ldmatrix.sync.aligned.m8n8.x4.trans.shared.b16 {%0,%1,%2,%3}, [%4];"
                     : "=r"(v.x), "=r"(v.y), "=r"(v.z), "=r"(v.w)
                     : "r"(a));
        if (t == 3) {
            const uint32_t mask = (eg & 1) ? 0xffff0000u : 0xffffu;
            v.x &= mask;
            v.y &= mask;
        }
        const int ch = (t < 2 ? t ^ ((g >> 1) & 1) : t) ^ ((n >> 1) & 3);
        const int step = (g & 1) + 2 * (eg & 1) + 2 * (g & 6);
        g_wc[(eg >> 2) * 8192 + step * 512 + ((eg >> 1) & 1) * 256 + s * 128 + n * 4 + ch] = v;
    }
    __threadfence();
    __syncthreads();
    if (tid == 0) atomicAdd(&g_ready, 1u);
}

#define PACE1 2100
#define PACE2 2700
#define START_MIN 3350
#define WDELAY 1600
#define WSTEP 500
#define WPF_AT 2600
#define WPF_STEP 800
#define POLL_AT 6500
#define T_SHIFT 300
constexpr int DB0 = 6;

__global__ void __cluster_dims__(2, 1, 1) __launch_bounds__(384, 1)
fibinet_kernel(const int* __restrict__ idx, const uint4* __restrict__ table,
               const __nv_bfloat16* __restrict__ se1, const __nv_bfloat16* __restrict__ se2,
               const __nv_bfloat16* __restrict__ wc,
               const unsigned char* __restrict__ w1, const __nv_bfloat16* __restrict__ w2, __nv_bfloat16* __restrict__ out,
               const __grid_constant__ CUtensorMap tm_w1, const __grid_constant__ CUtensorMap tm_bi) {
    extern __shared__ __align__(1024) unsigned char smem[];
    const int tid = threadIdx.x;
    const int cta = blockIdx.x - NPREP, grp = cta >> 1, rank = cta & 1, lane = tid & 31;
    uint32_t ids[13][4], cid[3][2];
    const uint32_t idle = (tid >> 8) | (cta < 0);
    const uint32_t row = ((tid >> 5) & 3) * 16 + (lane >> 3);
    const unsigned char* ib = reinterpret_cast<const unsigned char*>(idx) + (int64_t)grp * (64 * NF * 4);
    {
        const unsigned char* ip = ib + (row * (NF * 4) + ((tid >> 4) & 8));
#pragma unroll
        for (int u = 0; u < 4; u++) {
            ids[0][u] = ids[1][u] = 0;
            asm volatile("{.reg .pred p; setp.eq.u32 p, %3, 0; @p ld.global.nc.L2::128B.v2.u32 {%0,%1}, [%2];}"
                         : "+r"(ids[0][u]), "+r"(ids[1][u])
                         : "l"(ip + 16 * NF * u), "r"(idle));
        }
    }
    const uint32_t t_0 = clock32();
    {
        const uint32_t co = ((tid & 127) >> 1) * (NF * 4) + ((tid >> 4) & 8) + 16 + 16 * (tid & 1);
#pragma unroll
        for (int k = 0; k < 3; k++) {
            cid[k][0] = cid[k][1] = 0;
            asm volatile("{.reg .pred p; setp.eq.u32 p, %3, 0; @p ld.global.nc.v2.u32 {%0,%1}, [%2];}"
                         : "+r"(cid[k][0]), "+r"(cid[k][1])
                         : "l"(ib + (co + 32 * k - (k == 2 ? 8 * ((tid >> 7) & tid & 1) : 0))), "r"(idle));
        }
    }
    const uint32_t t_start = (t_0 ^ (clock32() & blockIdx.y)) - T_SHIFT;
    const uint32_t sb = (uint32_t)__cvta_generic_to_shared(smem);
    uint32_t gd0 = sb + (tid >> 7) * XDELTA + row * 128 + (((lane & 7) ^ (lane >> 3) ^ ((tid >> 5) & 4)) << 4);
    const uint4* tp = table + (lane & 7);
    auto gather = [&](int i) {
#pragma unroll
        for (int u = 0; u < 4; u++)
            asm volatile(
                "{.reg .u64 a; .reg .pred p; setp.eq.u32 p, %3, 0; mad.wide.u32 a, %2, 128, %1; @p cp.async.cg.shared.global [%0], [a], 16;}" ::"r"(
                    (gd0 ^ ((u & 1) * 64)) + xpair(i) + u * 512),
                "l"(tp), "r"(ids[i][u]), "r"(i == 0 ? idle : 0u)
                : "memory");
        CP_COMMIT();
    };
    gather(0);
    if (cta < 0) {
        prep_cta(sb, blockIdx.x, wc, se1, se2);
        return;
    }
    if (tid == 288) asm volatile("prefetch.tensormap [%0];" ::"l"(&tm_w1));
    const int warp = __reduce_max_sync(0xffffffffu, tid >> 5);
    const int w = warp >> 2;

    if (w == 2) {
        asm volatile("setmaxnreg.dec.sync.aligned.u32 40;");
        auto load_wc = [&](int gi) {
            if (elect()) {
                const unsigned char* src = reinterpret_cast<const unsigned char*>(g_wc) + rank * 131072;
                mbar_expect(sb + BAR_WC + gi * 8, (wcfirst(gi + 1) - wcfirst(gi)) * 8192);
#pragma unroll
                for (int c = wcfirst(gi); c < wcfirst(gi + 1); c++) bulk(sb + wcslot(c), src + c * 8192, 8192, sb + BAR_WC + gi * 8);
            }
            __syncwarp();
        };
        if (warp == 8) {
            if (elect()) {
                mbar_init(sb + BAR_Z, 1);
                mbar_expect(sb + BAR_Z, 8192);
                tma2d(sb + ZOFF, &tm_bi, sb + BAR_Z, 32 * rank, 0);
            }
#pragma unroll
            for (int f = 0; f < 26; f++) {
                if (f == 2) {
                    if (elect()) {
#pragma unroll
                        for (int k = 2; k < 8; k++) mbar_init(sb + BAR_FULL + k * 8, 1);
                        asm volatile("fence.mbarrier_init.release.cluster;" ::: "memory");
                    }
                    __syncwarp();
                    asm volatile("barrier.cluster.arrive.relaxed.aligned;" ::: "memory");
                    mbar_wait(sb + BAR_Z);
#pragma unroll
                    for (int k = 0; k < 2; k++)
                        sts128(sb + ZOFF + (k * 32 + lane) * 128 + ((4 ^ (lane & 7)) << 4), 0x3c803c80u, 0x3c803c80u, 0x3c803c80u, 0x3c803c80u);
                    PROXY_FENCE();
                    asm volatile("bar.arrive 0, 384;" ::: "memory");
                    TS(31);
                }
                if (f == 5) asm volatile("bar.sync 7, 64;" ::: "memory");
                if (f >= 5) mbar_wait(sb + bdone(f - 5), bpar(f - 5));
                if (f >= 2 && f < 5)
                    while (clock32() - t_start < WDELAY + (f - 2) * WSTEP) {
                    }
                if (elect()) {
                    if (f < 2) mbar_init(sb + BAR_FULL + f * 8, 1);
                    mbar_expect(sb + bfull(f), 16384);
                    tma2d(sb + slot(2 * wl(f)), &tm_w1, sb + bfull(f), 128 * rank + 64 * (f & 1), fieldof(f) * 64);
                    tma2d(sb + slot(wl(f)), &tm_w1, sb + bfull(f), 128 * rank + 64 - 64 * (f & 1), fieldof(f) * 64);
                }
                TS(f);
            }
            if (elect()) mbar_arrive(sb + BAR_GO);
            TS_DUMP(2);
        } else if (warp == 9) {
            if (elect()) {
#pragma unroll
                for (int k = 0; k < 10; k++) mbar_init(sb + BAR_WC + k * 8, k < 9 ? 1 : 8);
                asm volatile("fence.mbarrier_init.release.cluster;" ::: "memory");
            }
            __syncwarp();
            asm volatile("barrier.cluster.arrive.relaxed.aligned;" ::: "memory");
            asm volatile("bar.sync 0, 384;" ::: "memory");
            while (clock32() - t_start < POLL_AT) __nanosleep(100);
            if (elect()) {
                unsigned v, it = 0;
                do {
                    asm volatile("ld.acquire.gpu.global.u32 %0, [%1];" : "=r"(v) : "l"(&g_ready) : "memory");
                } while (v < NPREP && ++it < 4000000u);
                asm volatile("fence.proxy.async.global;" ::: "memory");
                mbar_expect(sb + BAR_SE, 2048);
                bulk(sb + SEOFF, g_se, 2048, sb + BAR_SE);
            }
            __syncwarp();
            TS(0);
            mbar_wait(sb + BAR_GO);
#pragma unroll
            for (int gi = 0; gi < 3; gi++) {
                mbar_wait(sb + bdone(21 + gi), bpar(21 + gi));
                load_wc(gi);
                TS(1 + gi);
            }
        } else if (warp == 10) {
            if (elect()) {
#pragma unroll
                for (int k = 0; k < 8; k++) mbar_init(sb + BAR_DONE + k * 8, 4);
                asm volatile("fence.mbarrier_init.release.cluster;" ::: "memory");
            }
            __syncwarp();
            asm volatile("barrier.cluster.arrive.relaxed.aligned;" ::: "memory");
            asm volatile("bar.arrive 7, 64;" ::: "memory");
            asm volatile("bar.sync 0, 384;" ::: "memory");
#pragma unroll 1
            for (int k = 0; k < 7; k++) {
                while (clock32() - t_start < (uint32_t)(WPF_AT + k * WPF_STEP)) __nanosleep(20);
                if (lane < 6)
                    asm volatile("prefetch.global.L2 [%0];" ::"l"(w1 + (5 + k * 3 + (lane >> 1)) * 32768 + cta * 256 + (lane & 1) * 128));
            }
        } else {
            asm volatile("bar.sync 0, 384;" ::: "memory");
            const uint2 v = __ldg(reinterpret_cast<const uint2*>(w2 + 128 * rank) + lane);
#pragma unroll
            for (int k = 0; k < 2; k++) {
                const uint32_t x = k ? v.y : v.x;
                sts64(sb + w2chunk((lane >> 2) * 4 + 2 * (lane & 1) + k) + (lane & 2) * 4,
                      __float_as_uint(0.5f * __uint_as_float(x << 16)), __float_as_uint(0.5f * __uint_as_float(x & 0xffff0000u)));
            }
            __syncwarp();
            if (lane == 0) mbar_arrive(sb + BAR_W2);
            mbar_wait(sb + BAR_GO);
            if (lane < 16) reinterpret_cast<uint32_t*>(out)[cta * 16 + lane] = 0;
            asm volatile("barrier.cluster.arrive.release.aligned;" ::: "memory");
        }
        {
            uint32_t bw[2][4], z0[4], z1[4];
            mbar_wait(sb + BAR_SE);
            lds128(bw[0], sb + SEOFF + lane * 16);
            lds128(bw[1], sb + SEOFF + 512 + lane * 16);
            asm volatile("bar.sync 2, 384;" ::: "memory");
            lds128(z0, sb + ZQOFF + (tid & 127) * 16);
            lds128(z1, sb + ZQOFF + 2048 + (tid & 127) * 16);
            TS(8);
            float s[2][4] = {};
#pragma unroll
            for (int n = 0; n < 2; n++) {
                mma16816(s[n], z0, bw[0][2 * n], bw[0][2 * n + 1]);
                mma16816(s[n], z1, bw[1][2 * n], bw[1][2 * n + 1]);
            }
            lds128(bw[0], sb + SEOFF + 1024 + lane * 16);
            lds128(bw[1], sb + SEOFF + 1536 + lane * 16);
            float th[8];
#pragma unroll
            for (int k = 0; k < 8; k++) th[k] = gelu_tanh(s[k >> 2][k & 3]);
            SCHED_FENCE();
            TS(9);
            uint32_t gq[4];
#pragma unroll
            for (int k = 0; k < 4; k++)
                gq[k] = pack(s[k >> 1][2 * (k & 1)] * ffma(th[2 * k], 0.5f, 0.5f), s[k >> 1][2 * (k & 1) + 1] * ffma(th[2 * k + 1], 0.5f, 0.5f));
            float a[4][4] = {};
#pragma unroll
            for (int n = 0; n < 4; n++) mma16816(a[n], gq, bw[n >> 1][2 * (n & 1)], bw[n >> 1][2 * (n & 1) + 1]);
#pragma unroll
            for (int k = 0; k < 16; k++)
                if (k < 13 || k == 14) a[k >> 2][k & 3] = tanh_fast(a[k >> 2][k & 3]);
            SCHED_FENCE();
            TS(10);
            uint32_t ap[8];
#pragma unroll
            for (int k = 0; k < 8; k++)
                ap[k] = pack(ffma(a[k >> 1][2 * (k & 1)], 0.5f, 0.5f), ffma(a[k >> 1][2 * (k & 1) + (k < 6)], 0.5f, 0.5f));
            sts128(sb + GOFF + (tid & 127) * 16, ap[0], ap[1], ap[2], ap[3]);
            sts128(sb + GOFF + 2048 + (tid & 127) * 16, ap[4], ap[5], ap[6], ap[7]);
            asm volatile("bar.arrive 3, 384;" ::: "memory");
            TS(11);
        }
        if (warp == 9) {
            load_wc(3);
            load_wc(4);
            mbar_wait(sb + BAR_TD);
            load_wc(5);
            if (lane == 0 && atomicAdd(&g_seen, 1u) == NMAIN - 1) {
                g_seen = 0;
                g_ready = 0;
            }
            if (lane < 16) TS_DUMP(3);
        } else if (warp == 10) {
            uint32_t* dst = reinterpret_cast<uint32_t*>(out) + grp * 32 + lane;
            asm volatile("barrier.cluster.wait.acquire.aligned;" : "+l"(dst)::"memory");
            SCHED_FENCE();
            asm volatile("bar.sync 4, 288;" ::: "memory");
            uint32_t p[4];
            lds64(p[0], p[1], sb + PARTOFF + lane * 8);
            lds64(p[2], p[3], sb + PARTOFF + 256 + lane * 8);
            asm volatile("red.relaxed.gpu.global.add.noftz.bf16x2 [%0], %1;" ::"l"(dst),
                         "r"(pack(__uint_as_float(p[0]) + __uint_as_float(p[2]), __uint_as_float(p[1]) + __uint_as_float(p[3])))
                         : "memory");
        }
    } else {
        asm volatile("setmaxnreg.inc.sync.aligned.u32 232;");
        asm volatile("barrier.cluster.arrive.relaxed.aligned;" ::: "memory");
        const uint32_t sb = __reduce_max_sync(0xffffffffu, (uint32_t)__cvta_generic_to_shared(smem) | (tid >> 10));
        const int t128 = opaque(tid & 127), lane = t128 & 31;
        const int g = lane >> 2, t = lane & 3, wq = warp & 3;
        gd0 = opaque(gd0);
        TS(28);
        float acc[84];
#pragma unroll
        for (int k = 0; k < 84; k++) asm volatile("mov.b32 %0, 0;" : "=f"(acc[k]));
        uint32_t e0[9], e1[9], e2[9];
        uint32_t X[13][2][4];
        uint32_t zq[4] = {0, 0, 0, 0};
        const uint64_t dA = mkdesc(sb + w * XDELTA, 16, 1024, 1);
        uint32_t dBlo = (uint32_t)mkdesc(sb + ZOFF, 0, 0, 0);
        const uint32_t xl0 = opaque(sb + (t & 1) * XDELTA + (16 * wq + g) * 128 + (((4 * rank + 2 * w) ^ (4 * (t & 1)) ^ g) << 4));
        const uint32_t hi_half = t >> 1;
        const uint32_t sa0 = opaque(sb + AOFF + t * 4096 + (t >> 1) * 16 + (wq * 32 + g * 4 + w) * 16);
        const uint32_t sa1 = opaque(((g & 2) << 4) | ((t & 1) << 3));
        const uint32_t zero = __reduce_max_sync(0xffffffffu, blockIdx.y | (tid >> 10));
        auto expand = [&](int k0, int k1) {
#pragma unroll
            for (int k = k0; k < k1; k++)
#pragma unroll
                for (int u = 0; u < 4; u++)
                    asm volatile("shfl.sync.idx.b32 %0, %1, %2, 31, 0xffffffff;"
                                 : "=r"(ids[k][u])
                                 : "r"(k < 12 ? cid[(k - 2) >> 2][k & 1] : w ? cid[2][1] : cid[2][0]),
                                   "r"(2 * (lane >> 3) + 8 * u + (((k - 2) >> 1) & 1)));
        };
        auto twarm = [&]() {
            float s1[8];
            WG_FENCE();
            wgmma_rs_n16_set(s1, zq, mkdesc(sb + AOFF, 16, 512, 2));
            WG_COMMIT();
            WG_WAIT0();
            pin(s1);
            asm volatile("{.reg .pred p; setp.ne.u32 p, %1, 0; @p st.shared.f32 [%1], %0;}" ::"f"(s1[0]), "r"(zero));
        };
        expand(2, 8);
        twarm();
        TS(26);
        while (clock32() - t_start < PACE1) {
        }
        gather(1);
        expand(8, 13);
        twarm();
        TS(30);
        while (clock32() - t_start < PACE2) {
        }
        gather(2);
        twarm();
        asm volatile("bar.sync 0, 384;" ::: "memory");
        auto lift = [&](int i) {
            const int m = 2 * (i >> 2) + (i & 1);
#pragma unroll
            for (int r = 0; r < 2; r++)
#pragma unroll
                for (int cc = 0; cc < 2; cc++) {
                    const uint32_t a = (xl0 ^ (cc * 16)) + xpair(i) + r * 1024;
                    if (i == 12 ? r : (i & 2)) lds128_if(X[i == 12 ? 12 : 2 * m + r][cc], a, hi_half);
                    else lds128(X[2 * m + r][cc], a);
                }
        };
        auto store_pair = [&](int m, int half, const uint32_t (&ea)[9]) {
            uint32_t a;
            if (m < 4) a = sa0 + (sa1 ^ (((m & 1) << 5) | ((m >> 1) << 3)));
            else a = sb + BOFF + t * 2048 + (wq * 32 + g * 4 + ((2 * (m & 1) + w) ^ t)) * 8;
#pragma unroll
            for (int n = half; n < 4; n += 2)
#pragma unroll
                for (int u = 0; u < 2; u++)
                    sts64(a + (m < 4 ? (8 * n + u) * 2048 + n * 32 : (8 * n + u) * 1024),
                          __byte_perm(ea[2 * n], e1[2 * n], u ? 0x7632 : 0x5410),
                          __byte_perm(ea[2 * n + 1], e1[2 * n + 1], u ? 0x7632 : 0x5410));
        };
        auto z_pair = [&](int m, uint32_t a, uint32_t b) {
            asm volatile("{.reg .pred p; setp.eq.u32 p, %4, %5; @p prmt.b32 %0, %2, %3, 0x5410; @p prmt.b32 %1, %2, %3, 0x7632;}"
                         : "+r"(zq[2 * (m >> 2)]), "+r"(zq[2 * (m >> 2) + 1])
                         : "r"(a), "r"(b), "r"(t), "r"(m & 3));
        };

        TS(29);
        mbar_wait(sb + BAR_FULL + w * 8);
        CP_WAIT(2);
        while (clock32() - t_start < START_MIN) {
        }
        if (w == 1) {
            asm volatile("bar.arrive 6, 256;" ::: "memory");
            asm volatile("bar.sync 5, 256;" ::: "memory");
        }
#pragma unroll
        for (int i = 0; i < 13; i++) {
            const uint64_t da = dA + (xpair(i) >> 4) + ((uint64_t)i << 16);
            dBlo += (uint32_t)(w ? wl(2 * i + 1) - (i ? wl(2 * i - 1) : 0) : wl(2 * i) - (i ? wl(2 * i - 2) : 0)) *
                    (uint32_t)((SLOT << 12) - (SLOT >> 3));
            const uint64_t db = mkdesc(0, 0, 1024, 1) | dBlo;
            TS(i);
            WG_FENCE();
            wgmma_ss_n168_acc(acc, da, db + w * 256);
            wgmma_ss_n168_acc(acc, da + 2, db + w * 256 + 128);
            wgmma_ss_n168_acc(acc, da + 4, db + (w ^ 1) * 256);
            wgmma_ss_n168_acc(acc, da + 6, db + (w ^ 1) * 256 + 128);
            WG_COMMIT();
            if (i == 0) {
                if (w == 0) {
                    asm volatile("bar.arrive 5, 256;" ::: "memory");
                    asm volatile("bar.sync 6, 256;" ::: "memory");
                }
            } else {
                mbar_wait(sb + bdone(2 * i - 2) + (w ^ 1) * 8, bpar(2 * i - 2));
            }
            if (i < 10) gather(i + 3);
            if (i == 6) mbar_wait(sb + BAR_W2);
            lift(i);
            if (i == 10 || i == 11) mbar_wait(sb + bdone(2 * i - 2) + w * 8, bpar(2 * i - 2));
            if (i >= 2 && !(i & 1)) {
                z_pair((i - 2) >> 1, e0[8], e1[8]);
                store_pair((i - 2) >> 1, 0, e0);
#pragma unroll
                for (int k = 0; k < 8; k++) e2[k] = e0[k];
            } else if (i >= 3) {
                store_pair((i - 3) >> 1, 1, e2);
            }
            const uint32_t rdy = i < 12 ? mbar_test(sb + bfull(2 * i + 2) + w * 8, bpar(2 * i + 2)) : 0;
            WG_WAIT0();
            pin(acc);
            if (i == 12) TS(13);
            if (i == 0) TS(27);
            if (i < 10) CP_WAIT(2);
            else if (i == 10) CP_WAIT(1);
            else if (i == 11) CP_WAIT(0);
            if (i < 12 && lane == 0) mbar_arrive(sb + bdone(2 * i) + w * 8);
#pragma unroll
            for (int k = 0; k < 9; k++) {
                const int k0 = 64 + 2 * (k & 5) + ((k >> 1) & 1);
                const uint32_t v = k == 8 ? pack(acc[80], acc[82]) : i < 12 ? pack(acc[64 + 2 * k], acc[65 + 2 * k]) : pack(acc[k0], acc[k0 + 4]);
                if (i & 1) e1[k] = v;
                else e0[k] = v;
            }
            if (i < 12) {
#pragma unroll
                for (int k = 64; k < 83; k++)
                    if (k != 81) asm volatile("mov.b32 %0, %1;" : "+f"(acc[k]) : "r"(zero));
                mbar_wait_unless(rdy, sb + bfull(2 * i + 2) + w * 8, bpar(2 * i + 2));
            } else {
                z_pair(6, e0[8], 0);
                sts128(sb + ZQOFF + w * 2048 + t128 * 16, zq[0], zq[1], zq[2], zq[3]);
                asm volatile("bar.arrive 2, 384;" ::: "memory");
            }
        }
        TS(14);

        uint32_t ai[8];
        float sum0 = 0.f, sum1 = 0.f;
        float th[32];
        uint32_t hw[4][4];
        auto deep_issue = [&](int k2) {
            lds128(hw[k2], ((sb + w2chunk(w * 16 + t)) ^ ((k2 & 1) * 64)) + k2 * 512);
#pragma unroll
            for (int k = 8 * k2; k < 8 * k2 + 8; k++) th[k] = gelu_tanh(acc[k]);
        };
        auto deep_use = [&](int k2) {
#pragma unroll
            for (int k = 8 * k2; k < 8 * k2 + 8; k++) {
                const float h = __uint_as_float(hw[k2][((k >> 1) & 2) + (k & 1)]);
                const float y = ffma(th[k], h, h);
                if (k & 2) sum1 = ffma(acc[k], y, sum1);
                else sum0 = ffma(acc[k], y, sum0);
            }
        };
        auto deep_send = [&](int k0, int k1) {
#pragma unroll
            for (int k = k0; k < k1; k++)
                sts128(sb + EXOFF + w * SLOT + t128 * 16 + k * 2048, pack(acc[32 + 8 * k], acc[33 + 8 * k]),
                       pack(acc[34 + 8 * k], acc[35 + 8 * k]), pack(acc[36 + 8 * k], acc[37 + 8 * k]), pack(acc[38 + 8 * k], acc[39 + 8 * k]));
        };
        uint32_t o[4][4];
        auto deep_recv = [&](int k0, int k1) {
#pragma unroll
            for (int k = k0; k < k1; k++) lds128(o[k], sb + EXOFF + (w ^ 1) * SLOT + t128 * 16 + k * 2048);
        };
        auto deep_add = [&](int k0, int k1) {
            const uint32_t eye = (g >> 1) == t ? ((g & 1) ? 0x3f800000u : 0x3f80u) : 0u;
#pragma unroll
            for (int k = 2 * k0; k < 2 * k1; k++)
                asm volatile("mma.sync.aligned.m16n8k8.row.col.f32.bf16.bf16.f32 {%0,%1,%2,%3}, {%4,%5}, {%6}, {%0,%1,%2,%3};"
                             : "+f"(acc[4 * k]), "+f"(acc[4 * k + 1]), "+f"(acc[4 * k + 2]), "+f"(acc[4 * k + 3])
                             : "r"(o[k >> 1][2 * (k & 1)]), "r"(o[k >> 1][2 * (k & 1) + 1]), "r"(eye));
        };
        auto store_last = [&]() {
#pragma unroll
            for (int n = 0; n < 4; n++) sts64(sb + COFF + w * 4096 + n * 1024 + (t128 ^ w) * 8, e0[2 * n], e0[2 * n + 1]);
            store_pair(5, 1, e2);
        };
        const uint32_t la = (sb + AOFF + w * (16 * 2048 + 64) + (wq * 32 + g * 4 + (t ^ (g & 2))) * 16);
        const uint32_t lb = (sb + BOFF + w * (16 * 1024) + t128 * 8);
        const uint32_t lc0 = (sb + COFF + (t & 1) * (4096 + 8) + w * 2048 + (wq * 8 + g) * 32), lc1 = lc0 ^ 8;
        uint32_t Ap[2][2][4];
        auto load_a = [&](int s) {
            const int e = estep(s);
            lds128(Ap[s & 1][0], la + e * 2048 + (e >> 2) * 16);
            lds64(Ap[s & 1][1][0], Ap[s & 1][1][1], (lb ^ ((e & 6) * 4)) + e * 1024);
            if (!(s & 2)) lds64(Ap[s & 1][1][2], Ap[s & 1][1][3], ((e & 2) ? lc1 : lc0) + (e & 1) * 1024 + (e & 4) * 4);
        };
        {
            uint32_t v[2][4];
            deep_send(0, 2);
            asm volatile("bar.sync 1, 256;" ::: "memory");
            deep_recv(0, 2);
            deep_send(2, 4);
            TS(15);
            deep_add(0, 2);
            deep_issue(0);
            asm volatile("bar.sync 1, 256;" ::: "memory");
            deep_recv(2, 4);
            SCHED_FENCE();
            deep_add(2, 4);
            TS(16);
            deep_issue(1);
            deep_use(0);
            store_last();
            SCHED_FENCE();
            TS(17);
            deep_issue(2);
            deep_use(1);
            mbar_wait(sb + BAR_WC);
            deep_use(2);
            TS(18);
            asm volatile("bar.sync 3, 384;" ::: "memory");
            lds128(v[0], sb + GOFF + t128 * 16);
            lds128(v[1], sb + GOFF + 2048 + t128 * 16);
            load_a(0);
            load_a(1);
            deep_issue(3);
#pragma unroll
            for (int k = 0; k < 8; k++) ai[k] = v[k >> 2][k & 3];
        }
        TS(19);

        uint32_t fin_a, dsum[2], tid2;
        const uint32_t hi2 = lb & 16;
        {
            uint64_t dW[4];
#pragma unroll
            for (int k = 0; k < 4; k++) dW[k] = mkdesc(sb + w * 4096, 16, 512, 2) + ((uint64_t)zero << 32) + (wcslot(0) >> 4) + (k >> 1) * 128 + (k & 1) * 2;
            uint32_t Aq[2][2][4], pq[13], gate[13];
            float S[2][2][16];
            auto scale_a = [&](int s) {
#pragma unroll
                for (int k = 0; k < ((s & 2) ? 6 : 8); k++)
                    Aq[s & 1][k >> 2][k & 3] = hmul2(Ap[s & 1][k >> 2][k & 3], ai[k < 4 ? k ^ (estep(s) & 2) : k]);
            };
            auto sbuf = [](int s) { return s <= DB0 ? 0 : (s - DB0) & 1; };
            auto issue = [&](int s) {
                const bool first = s == 0 || s == DB0 + 1;
                WG_FENCE();
                if (first) wgmma_rs_n32_set(S[sbuf(s)][0], Ap[s & 1][0], dW[0]);
                else wgmma_rs_n32_pred(S[sbuf(s)][0], Ap[s & 1][0], dW[0], zero);
                wgmma_rs_n32_acc(S[sbuf(s)][0], Ap[s & 1][1], dW[1]);
                if (first) wgmma_rs_n32_set(S[sbuf(s)][1], Aq[s & 1][0], dW[2]);
                else wgmma_rs_n32_pred(S[sbuf(s)][1], Aq[s & 1][0], dW[2], zero);
                wgmma_rs_n32_acc(S[sbuf(s)][1], Aq[s & 1][1], dW[3]);
                WG_COMMIT();
                if (s < 15) {
#pragma unroll
                    for (int k = 0; k < 4; k++)
                        asm volatile("add.s64 %0, %0, %1;" : "+l"(dW[k]) : "l"((int64_t)((wcslot(s + 1) - wcslot(s)) / 16)));
                }
            };
            scale_a(0);
            issue(0);
            SCHED_FENCE();
            deep_use(3);
            scale_a(1);
            mbar_wait(sb + BAR_WC + 8);
#pragma unroll
            for (int e = 0; e < 16; e++) {
                if (e >= DB0 && e < 15) {
                    issue(e + 1);
                    WG_WAIT1();
                } else {
                    WG_WAIT0();
                }
                pin(S[sbuf(e)][0]);
                pin(S[sbuf(e)][1]);
                if (e == 0 && (lb & 0xf8) == 0) mbar_arrive(sb + BAR_TD);
                if (e == 0) TS(20);
                if (e + 2 < 16) load_a(e + 2);
#pragma unroll
                for (int q = 0; q < 13; q++) {
                    const int ix = 4 * (q >> 2) + 2 * (q & 1) + ((q >> 1) & 1);
                    uint32_t v = pack(S[sbuf(e)][0][ix], S[sbuf(e)][1][ix ^ 1]);
                    if (q == 12)
                        asm volatile("{.reg .pred p; setp.ne.u32 p, %3, 0; @p cvt.rn.bf16x2.f32 %0, %2, %1;}"
                                     : "+r"(v)
                                     : "f"(S[sbuf(e)][0][14]), "f"(S[sbuf(e)][1][15]), "r"(hi2));
                    const uint32_t x = X[q][(e >> 1) & 1][e >> 2];
                    pq[q] = (e & 1) ? hfma2_bcast<1>(v, x, pq[q]) : hfma2_bcast<0>(v, x, e ? pq[q] : 0u);
                }
                if (e < DB0) {
                    issue(e + 1);
                    SCHED_FENCE();
                }
                if (e == 3) {
                    const float h0 = __uint_as_float(__float_as_uint(sum0) & 0xffff0000u);
                    const float h1 = __uint_as_float(__float_as_uint(sum1) & 0xffff0000u);
                    dsum[0] = pack(sum0 - h0, h0);
                    dsum[1] = pack(sum1 - h1, h1);
                }
                if (e == 13) {
                    asm volatile("mov.u32 %0, %%tid.x;" : "=r"(tid2));
                    fin_a = sb + PARTOFF + (tid2 >> 5) * 64 + (tid2 & 28);
                }
                if (e == 14) {
#pragma unroll
                    for (int q = 0; q < 13; q++)
                        asm volatile("prmt.b32 %0, %1, 0x3f80, %2;"
                                     : "=r"(gate[q])
                                     : "r"(q < 12 ? ai[2 * (q >> 2) + (q & 1)] : hi2 ? ai[7] : ai[6]), "r"((q & 2) ? 0x3254 : 0x1054));
                }
                if (e + 2 < 16) scale_a(e + 2);
                if (e == 0 || e == 3 || e == 6 || e == 9) mbar_wait(sb + BAR_WC + (e / 3 + 2) * 8);
                else if (e < 15) SCHED_FENCE();
                if (e == 7) TS(21);
            }
            float r0[4] = {0.f, 0.f, 0.f, 0.f}, r1[4] = {0.f, 0.f, 0.f, 0.f}, r2[4] = {0.f, 0.f, 0.f, 0.f};
#pragma unroll
            for (int c = 0; c < 3; c++) {
                const uint32_t a[4] = {pq[4 * c], pq[4 * c + 1], pq[4 * c + 2], pq[4 * c + 3]};
                mma16816(r0, a, gate[4 * c], gate[4 * c + 2]);
                mma16816(r1, a, gate[4 * c + 1], gate[4 * c + 3]);
            }
            const uint32_t rest[4] = {dsum[0], dsum[1], hi2 ? 0u : pq[12], hi2 ? pq[12] : 0u};
            mma16816(r2, rest, 0x3f803f80u, gate[12]);
            sum0 = (tid2 & 4) ? r0[1] + r2[1] : r0[0] + r2[0];
            sum1 = (tid2 & 4) ? r1[3] + r2[3] : r1[2] + r2[2];
        }
        TS(22);
        {
            asm volatile("{.reg .pred p; setp.eq.u32 p, %3, %4; @p st.shared.f32 [%0], %1; @p st.shared.f32 [%0 + 32], %2;}" ::"r"(fin_a),
                         "f"(sum0), "f"(sum1), "r"(tid2 & 3), "r"((tid2 >> 3) & 3)
                         : "memory");
            asm volatile("bar.arrive 4, 288;" ::: "memory");
            if (wq == 0) TS_DUMP(w);
        }
    }
}

typedef CUresult (*EncodeFn)(CUtensorMap*, CUtensorMapDataType, cuuint32_t, void*, const cuuint64_t*, const cuuint64_t*,
                             const cuuint32_t*, const cuuint32_t*, CUtensorMapInterleave, CUtensorMapSwizzle,
                             CUtensorMapL2promotion, CUtensorMapFloatOOBfill);

}

extern "C" void kernel_launch(void* const* d_in, const int* in_sizes, int n_in, void* d_out, int out_size) {
    static EncodeFn encode = nullptr;
    if (!encode) {
        void* fn = nullptr;
        cudaDriverEntryPointQueryResult qr;
        cudaGetDriverEntryPoint("cuTensorMapEncodeTiled", &fn, cudaEnableDefault, &qr);
        encode = (EncodeFn)fn;
        cudaFuncSetAttribute(fibinet_kernel, cudaFuncAttributeMaxDynamicSharedMemorySize, SMEM_BYTES);
    }
    CUtensorMap tm;
    const cuuint64_t gd[2] = {NH, NF * ND};
    const cuuint64_t gs[1] = {NH * 2};
    const cuuint32_t bd[2] = {64, 64}, es[2] = {1, 1};
    encode(&tm, CU_TENSOR_MAP_DATA_TYPE_BFLOAT16, 2, d_in[6], gd, gs, bd, es, CU_TENSOR_MAP_INTERLEAVE_NONE,
           CU_TENSOR_MAP_SWIZZLE_128B, CU_TENSOR_MAP_L2_PROMOTION_L2_256B, CU_TENSOR_MAP_FLOAT_OOB_FILL_NONE);
    CUtensorMap tb;
    const cuuint64_t gd2[2] = {ND, ND};
    const cuuint64_t gs2[1] = {ND * 2};
    encode(&tb, CU_TENSOR_MAP_DATA_TYPE_BFLOAT16, 2, d_in[4], gd2, gs2, bd, es, CU_TENSOR_MAP_INTERLEAVE_NONE,
           CU_TENSOR_MAP_SWIZZLE_128B, CU_TENSOR_MAP_L2_PROMOTION_L2_256B, CU_TENSOR_MAP_FLOAT_OOB_FILL_NONE);
    fibinet_kernel<<<NPREP + NMAIN, 384, SMEM_BYTES>>>(
        (const int*)d_in[0], (const uint4*)d_in[1], (const __nv_bfloat16*)d_in[2], (const __nv_bfloat16*)d_in[3],
        (const __nv_bfloat16*)d_in[5], (const unsigned char*)d_in[6], (const __nv_bfloat16*)d_in[7], (__nv_bfloat16*)d_out, tm, tb);
}
```

```cpp
#include <cuda_runtime.h>
#include <cuda_bf16.h>
#include <cuda.h>
#include <stdint.h>

namespace {

constexpr int NF = 26, ND = 64, NH = 256, NR = 13;
constexpr int NPREP = 4;
constexpr int NMAIN = 128;

constexpr int SLOT = 8192;
constexpr int ZOFF = 15 * SLOT;
__host__ __device__ constexpr int slot(int s) { return ZOFF - s * SLOT; }
constexpr int BOFF = ZOFF + SLOT;
constexpr int AOFF = BOFF + 32768;
constexpr int COFF = slot(12);
constexpr int MOFF = AOFF + 65536 + 128;
constexpr int BAR_FULL = MOFF, BAR_DONE = MOFF + 64, BAR_WC = MOFF + 128, BAR_SE = MOFF + 176, BAR_TD = MOFF + 184,
              BAR_Z = MOFF + 192;
__host__ __device__ constexpr int bfull(int f) { return BAR_FULL + (f & 7) * 8; }
__host__ __device__ constexpr int bdone(int f) { return BAR_DONE + (f & 7) * 8; }
__host__ __device__ constexpr int bpar(int f) { return (f >> 3) & 1; }
constexpr int W2OFF = MOFF + 256, SEOFF = MOFF + 768;
constexpr int PARTOFF = SEOFF;
constexpr int SMEM_BYTES = MOFF + 2944;
constexpr int XDELTA = 2 * SLOT;
__host__ __device__ constexpr int xpair(int i) {
    return (i & 3) == 0 ? slot(11) : (i & 3) == 1 ? BOFF : (i & 3) == 2 ? BOFF + SLOT : slot(15);
}
__host__ __device__ constexpr int wl(int f) { return f % 5 == 0 ? 1 : f % 5 == 4 ? 7 : f % 5 + 2; }
__host__ __device__ constexpr int wcslot(int c) {
    return c == 0 ? slot(3) : c == 1 ? slot(8) : c == 2 ? slot(10) : c == 3 ? slot(15) : c == 4 ? slot(13)
         : c == 5 ? slot(11) : c == 6 ? slot(9) : c == 7 ? slot(14) : c == 8 ? slot(7) : c == 9 ? slot(2)
         : c == 10 ? slot(1) : c == 11 ? slot(4) : c == 12 ? slot(5) : c == 13 ? slot(6) : c == 14 ? ZOFF : slot(3);
}
__host__ __device__ constexpr int wcfirst(int gi) { return gi < 3 ? gi : gi == 3 ? 5 : gi == 4 ? 8 : gi == 5 ? 11 : 16; }
constexpr int EXOFF = slot(5);
constexpr int ZQOFF = slot(6);
constexpr int GOFF = ZQOFF + 4096;

__device__ uint4 g_wc[2 * 16 * 8192 / 16];
__device__ uint4 g_se[2048 / 16];
__device__ float4 g_w2[NH / 4];
__device__ unsigned g_ready;
__device__ unsigned g_seen;

__host__ __device__ constexpr int fieldof(int f) { return f < 24 ? 4 * (f >> 2) + 2 * (f & 1) + ((f >> 1) & 1) : f; }
__device__ __forceinline__ int fmap(int n) { return n < 24 ? n : 24 + ((n >> 1) & 1); }
__host__ __device__ constexpr int estep(int s) { return (s & 1) + 2 * (s >> 2) + 4 * (s & 2); }

__device__ __forceinline__ uint64_t mkdesc(uint32_t addr, uint32_t lbo, uint32_t sbo, int sw) {
    return (uint64_t)((addr & 0x3ffff) >> 4) | ((uint64_t)(lbo >> 4) << 16) | ((uint64_t)(sbo >> 4) << 32) |
           ((uint64_t)sw << 62);
}
__device__ __forceinline__ void mbar_init(uint32_t b, uint32_t n) {
    asm volatile("mbarrier.init.shared.b64 [%0], %1;" ::"r"(b), "r"(n) : "memory");
}
__device__ __forceinline__ void mbar_wait(uint32_t b, uint32_t par = 0) {
    asm volatile(
        "{\n.reg .pred p, q;\n.reg .u32 n;\n"
        "mbarrier.try_wait.parity.shared.b64 p, [%0], %1;\n@p bra.uni WD%=;\nmov.u32 n, 0;\n"
        "WL%=:\nmbarrier.try_wait.parity.shared.b64 p, [%0], %1;\n@p bra.uni WD%=;\n"
        "add.u32 n, n, 1;\nsetp.lt.u32 q, n, 4000000;\n@q bra.uni WL%=;\nWD%=:\n}\n" ::"r"(b), "r"(par)
        : "memory");
}
__device__ __forceinline__ uint32_t mbar_test(uint32_t b, uint32_t par) {
    uint32_t ok;
    asm volatile("{.reg .pred p; mbarrier.test_wait.parity.shared.b64 p, [%1], %2; selp.u32 %0, 1, 0, p;}"
                 : "=r"(ok)
                 : "r"(b), "r"(par)
                 : "memory");
    return ok;
}
__device__ __forceinline__ void mbar_wait_unless(uint32_t ok, uint32_t b, uint32_t par) {
    asm volatile(
        "{\n.reg .pred p, q;\n.reg .u32 n;\n"
        "setp.ne.u32 p, %1, 0;\n@p bra.uni WD%=;\nmov.u32 n, 0;\n"
        "WL%=:\nmbarrier.try_wait.parity.shared.b64 p, [%0], %2;\n@p bra.uni WD%=;\n"
        "add.u32 n, n, 1;\nsetp.lt.u32 q, n, 4000000;\n@q bra.uni WL%=;\nWD%=:\n}\n" ::"r"(b), "r"(ok), "r"(par)
        : "memory");
}
__device__ __forceinline__ void mbar_arrive(uint32_t b) {
    asm volatile("mbarrier.arrive.shared.b64 _, [%0];" ::"r"(b) : "memory");
}
__device__ __forceinline__ void mbar_expect(uint32_t b, uint32_t bytes) {
    asm volatile("mbarrier.arrive.expect_tx.shared.b64 _, [%0], %1;" ::"r"(b), "r"(bytes) : "memory");
}
__device__ __forceinline__ uint32_t opaque(uint32_t v) { return __shfl_sync(0xffffffffu, v, threadIdx.x); }
__device__ __forceinline__ bool elect() {
    uint32_t p;
    asm volatile("{.reg .pred q; elect.sync _|q, 0xffffffff; selp.u32 %0, 1, 0, q;}" : "=r"(p));
    return p;
}
__device__ __forceinline__ void tma2d(uint32_t dst, const CUtensorMap* m, uint32_t bar, int x, int y) {
    asm volatile(
        "cp.async.bulk.tensor.2d.shared::cluster.global.mbarrier::complete_tx::bytes [%0], [%1, {%3, %4}], [%2];" ::"r"(dst),
        "l"(m), "r"(bar), "r"(x), "r"(y)
        : "memory");
}
__device__ __forceinline__ void bulk(uint32_t dst, const void* src, uint32_t bytes, uint32_t bar) {
    asm volatile("cp.async.bulk.shared::cluster.global.mbarrier::complete_tx::bytes [%0], [%1], %2, [%3];" ::"r"(dst),
                 "l"(src), "r"(bytes), "r"(bar)
                 : "memory");
}
__device__ __forceinline__ void cp16(uint32_t dst, const void* src) {
    asm volatile("cp.async.cg.shared.global [%0], [%1], 16;" ::"r"(dst), "l"(src) : "memory");
}
__device__ __forceinline__ void lds128(uint32_t (&v)[4], uint32_t a) {
    asm volatile("ld.shared.v4.u32 {%0,%1,%2,%3}, [%4];" : "=r"(v[0]), "=r"(v[1]), "=r"(v[2]), "=r"(v[3]) : "r"(a) : "memory");
}
__device__ __forceinline__ void lds128_if(uint32_t (&v)[4], uint32_t a, uint32_t p) {
    asm volatile("{.reg .pred q; setp.ne.u32 q, %5, 0; @q ld.shared.v4.u32 {%0,%1,%2,%3}, [%4];}"
                 : "+r"(v[0]), "+r"(v[1]), "+r"(v[2]), "+r"(v[3])
                 : "r"(a), "r"(p)
                 : "memory");
}
__device__ __forceinline__ void lds64(uint32_t& x, uint32_t& y, uint32_t a) {
    asm volatile("ld.shared.v2.u32 {%0,%1}, [%2];" : "=r"(x), "=r"(y) : "r"(a) : "memory");
}
__device__ __forceinline__ void sts128(uint32_t a, uint32_t x, uint32_t y, uint32_t z, uint32_t w) {
    asm volatile("st.shared.v4.u32 [%0], {%1,%2,%3,%4};" ::"r"(a), "r"(x), "r"(y), "r"(z), "r"(w) : "memory");
}
__device__ __forceinline__ void sts64(uint32_t a, uint32_t x, uint32_t y) {
    asm volatile("st.shared.v2.u32 [%0], {%1,%2};" ::"r"(a), "r"(x), "r"(y) : "memory");
}
__device__ __forceinline__ uint32_t pack(float lo, float hi) {
    uint32_t r;
    asm volatile("cvt.rn.bf16x2.f32 %0, %1, %2;" : "=r"(r) : "f"(hi), "f"(lo));
    return r;
}
__device__ __forceinline__ uint32_t hmul2(uint32_t a, uint32_t b) {
    uint32_t r;
    asm volatile("mul.rn.bf16x2 %0, %1, %2;" : "=r"(r) : "r"(a), "r"(b));
    return r;
}
template <int H>
__device__ __forceinline__ uint32_t hfma2_bcast(uint32_t a, uint32_t x, uint32_t c) {
    uint32_t r;
    if (H)
        asm volatile("{.reg .b16 l, h; .reg .b32 s; mov.b32 {l, h}, %2; mov.b32 s, {h, h}; fma.rn.bf16x2 %0, %1, s, %3;}"
                     : "=r"(r)
                     : "r"(a), "r"(x), "r"(c));
    else
        asm volatile("{.reg .b16 l, h; .reg .b32 s; mov.b32 {l, h}, %2; mov.b32 s, {l, l}; fma.rn.bf16x2 %0, %1, s, %3;}"
                     : "=r"(r)
                     : "r"(a), "r"(x), "r"(c));
    return r;
}
__device__ __forceinline__ float ffma(float a, float b, float c) {
    float r;
    asm volatile("fma.rn.f32 %0, %1, %2, %3;" : "=f"(r) : "f"(a), "f"(b), "f"(c));
    return r;
}
__device__ __forceinline__ float tanh_fast(float x) {
    float r;
    asm volatile("tanh.approx.f32 %0, %1;" : "=f"(r) : "f"(x));
    return r;
}
__device__ __forceinline__ float gelu_tanh(float x) {
    float r;
    asm volatile(
        "{.reg .f32 a; mul.f32 a, %1, %1; fma.rn.f32 a, a, 0f3D122279, 0f3F4C422A; mul.f32 a, a, %1; tanh.approx.f32 %0, a;}"
        : "=f"(r)
        : "f"(x));
    return r;
}
__device__ __forceinline__ void mma16816(float (&d)[4], const uint32_t (&a)[4], uint32_t b0, uint32_t b1) {
    asm volatile("mma.sync.aligned.m16n8k16.row.col.f32.bf16.bf16.f32 {%0,%1,%2,%3}, {%4,%5,%6,%7}, {%8,%9}, {%0,%1,%2,%3};"
                 : "+f"(d[0]), "+f"(d[1]), "+f"(d[2]), "+f"(d[3])
                 : "r"(a[0]), "r"(a[1]), "r"(a[2]), "r"(a[3]), "r"(b0), "r"(b1));
}
__device__ __forceinline__ uint32_t clock32() {
    uint32_t c;
    asm volatile("mov.u32 %0, %%clock;" : "=r"(c)::"memory");
    return c;
}
#define WG_FENCE() asm volatile("wgmma.fence.sync.aligned;" ::: "memory")
#define WG_COMMIT() asm volatile("wgmma.commit_group.sync.aligned;" ::: "memory")
#define WG_WAIT0() asm volatile("wgmma.wait_group.sync.aligned 0;" ::: "memory")
#define WG_WAIT1() asm volatile("wgmma.wait_group.sync.aligned 1;" ::: "memory")
#define CP_COMMIT() asm volatile("cp.async.commit_group;" ::: "memory")
#define CP_WAIT(n) asm volatile("cp.async.wait_group %0;" ::"n"(n) : "memory")
#define SCHED_FENCE() asm volatile("pmevent 0;" ::: "memory")
#define PROXY_FENCE() asm volatile("fence.proxy.async.shared::cta;" ::: "memory")
template <int N>
__device__ __forceinline__ void pin(float (&d)[N]) {
#pragma unroll
    for (int i = 0; i < N; i++) asm volatile("" : "+f"(d[i])::"memory");
}
#define TS(k)
#define TS_DUMP(role)

__device__ __forceinline__ void wgmma_ss_n168_acc(float (&d)[84], uint64_t da, uint64_t db) {
    asm volatile(
        "wgmma.mma_async.sync.aligned.m64n168k16.f32.bf16.bf16 "
        "{%0,%1,%2,%3,%4,%5,%6,%7,%8,%9,%10,%11,%12,%13,%14,%15,"
        "%16,%17,%18,%19,%20,%21,%22,%23,%24,%25,%26,%27,%28,%29,%30,%31,"
        "%32,%33,%34,%35,%36,%37,%38,%39,%40,%41,%42,%43,%44,%45,%46,%47,"
        "%48,%49,%50,%51,%52,%53,%54,%55,%56,%57,%58,%59,%60,%61,%62,%63,"
        "%64,%65,%66,%67,%68,%69,%70,%71,%72,%73,%74,%75,%76,%77,%78,%79,"
        "%80,%81,%82,%83}, "
        "%84, %85, 1, 1, 1, 0, 1;"
        : "+f"(d[0]), "+f"(d[1]), "+f"(d[2]), "+f"(d[3]), "+f"(d[4]), "+f"(d[5]), "+f"(d[6]), "+f"(d[7]),
          "+f"(d[8]), "+f"(d[9]), "+f"(d[10]), "+f"(d[11]), "+f"(d[12]), "+f"(d[13]), "+f"(d[14]), "+f"(d[15]),
          "+f"(d[16]), "+f"(d[17]), "+f"(d[18]), "+f"(d[19]), "+f"(d[20]), "+f"(d[21]), "+f"(d[22]), "+f"(d[23]),
          "+f"(d[24]), "+f"(d[25]), "+f"(d[26]), "+f"(d[27]), "+f"(d[28]), "+f"(d[29]), "+f"(d[30]), "+f"(d[31]),
          "+f"(d[32]), "+f"(d[33]), "+f"(d[34]), "+f"(d[35]), "+f"(d[36]), "+f"(d[37]), "+f"(d[38]), "+f"(d[39]),
          "+f"(d[40]), "+f"(d[41]), "+f"(d[42]), "+f"(d[43]), "+f"(d[44]), "+f"(d[45]), "+f"(d[46]), "+f"(d[47]),
          "+f"(d[48]), "+f"(d[49]), "+f"(d[50]), "+f"(d[51]), "+f"(d[52]), "+f"(d[53]), "+f"(d[54]), "+f"(d[55]),
          "+f"(d[56]), "+f"(d[57]), "+f"(d[58]), "+f"(d[59]), "+f"(d[60]), "+f"(d[61]), "+f"(d[62]), "+f"(d[63]),
          "+f"(d[64]), "+f"(d[65]), "+f"(d[66]), "+f"(d[67]), "+f"(d[68]), "+f"(d[69]), "+f"(d[70]), "+f"(d[71]),
          "+f"(d[72]), "+f"(d[73]), "+f"(d[74]), "+f"(d[75]), "+f"(d[76]), "+f"(d[77]), "+f"(d[78]), "+f"(d[79]),
          "+f"(d[80]), "+f"(d[81]), "+f"(d[82]), "+f"(d[83])
        : "l"(da), "l"(db));
}

__device__ __forceinline__ void wgmma_rs_n32_set(float (&d)[16], const uint32_t (&a)[4], uint64_t db) {
    asm volatile(
        "wgmma.mma_async.sync.aligned.m64n32k16.f32.bf16.bf16 "
        "{%0,%1,%2,%3,%4,%5,%6,%7,%8,%9,%10,%11,%12,%13,%14,%15}, "
        "{%16,%17,%18,%19}, %20, 0, 1, 1, 0;"
        : "=f"(d[0]), "=f"(d[1]), "=f"(d[2]), "=f"(d[3]), "=f"(d[4]), "=f"(d[5]), "=f"(d[6]), "=f"(d[7]),
          "=f"(d[8]), "=f"(d[9]), "=f"(d[10]), "=f"(d[11]), "=f"(d[12]), "=f"(d[13]), "=f"(d[14]), "=f"(d[15])
        : "r"(a[0]), "r"(a[1]), "r"(a[2]), "r"(a[3]), "l"(db));
}

__device__ __forceinline__ void wgmma_rs_n32_acc(float (&d)[16], const uint32_t (&a)[4], uint64_t db) {
    asm volatile(
        "wgmma.mma_async.sync.aligned.m64n32k16.f32.bf16.bf16 "
        "{%0,%1,%2,%3,%4,%5,%6,%7,%8,%9,%10,%11,%12,%13,%14,%15}, "
        "{%16,%17,%18,%19}, %20, 1, 1, 1, 0;"
        : "+f"(d[0]), "+f"(d[1]), "+f"(d[2]), "+f"(d[3]), "+f"(d[4]), "+f"(d[5]), "+f"(d[6]), "+f"(d[7]),
          "+f"(d[8]), "+f"(d[9]), "+f"(d[10]), "+f"(d[11]), "+f"(d[12]), "+f"(d[13]), "+f"(d[14]), "+f"(d[15])
        : "r"(a[0]), "r"(a[1]), "r"(a[2]), "r"(a[3]), "l"(db));
}

__device__ __forceinline__ void wgmma_rs_n16_set(float (&d)[8], const uint32_t (&a)[4], uint64_t db) {
    asm volatile(
        "wgmma.mma_async.sync.aligned.m64n16k16.f32.bf16.bf16 "
        "{%0,%1,%2,%3,%4,%5,%6,%7}, "
        "{%8,%9,%10,%11}, %12, 0, 1, 1, 0;"
        : "=f"(d[0]), "=f"(d[1]), "=f"(d[2]), "=f"(d[3]), "=f"(d[4]), "=f"(d[5]), "=f"(d[6]), "=f"(d[7])
        : "r"(a[0]), "r"(a[1]), "r"(a[2]), "r"(a[3]), "l"(db));
}

__device__ __forceinline__ void wgmma_rs_n32_pred(float (&d)[16], const uint32_t (&a)[4], uint64_t db, uint32_t scale_d) {
    asm volatile(
        "{.reg .pred p; setp.ne.u32 p, %21, 0; wgmma.mma_async.sync.aligned.m64n32k16.f32.bf16.bf16 "
        "{%0,%1,%2,%3,%4,%5,%6,%7,%8,%9,%10,%11,%12,%13,%14,%15}, "
        "{%16,%17,%18,%19}, %20, p, 1, 1, 0;}"
        : "+f"(d[0]), "+f"(d[1]), "+f"(d[2]), "+f"(d[3]), "+f"(d[4]), "+f"(d[5]), "+f"(d[6]), "+f"(d[7]),
          "+f"(d[8]), "+f"(d[9]), "+f"(d[10]), "+f"(d[11]), "+f"(d[12]), "+f"(d[13]), "+f"(d[14]), "+f"(d[15])
        : "r"(a[0]), "r"(a[1]), "r"(a[2]), "r"(a[3]), "l"(db), "r"(scale_d));
}

__device__ __forceinline__ void prep_cta(uint32_t sb, int c, const __nv_bfloat16* __restrict__ wc,
                                         const __nv_bfloat16* __restrict__ se1, const __nv_bfloat16* __restrict__ se2,
                                         const __nv_bfloat16* __restrict__ w2) {
    const int tid = threadIdx.x, lane = tid & 31, warp = tid >> 5, s = c >> 1;
    constexpr int ZERO = 16 * NF * 128;
#pragma unroll
    for (int q = tid; q < 16 * NF * 8; q += 384) {
        const int i = q >> 7, nn = (q >> 3) & 15, j = fmap((16 * (c & 1) + nn) ^ s);
        cp16(sb + (q >> 3) * 128 + (((q & 7) ^ (i & 1) ^ ((i >> 3) << 1)) << 4), wc + ((s * NF + i) * NF + j) * ND + (q & 7) * 8);
    }
    if (tid < 8) sts128(sb + ZERO + tid * 16, 0, 0, 0, 0);
    if (tid < 256) {
        const int n = ((tid >> 2) & 1) * 8 + (tid >> 5) + (s ? (c & 1) * 16 : 0);
        const int k = ((tid >> 1) & 1) * 8 + ((tid >> 3) & 3) * 2 + (tid & 1), mm = k >> 1, u = k & 1;
        const int f = s ? fmap(n) : mm < 6 ? 4 * mm + 2 * c + u : (mm == 6 && u == 0) ? 24 + c : -1;
        float v = 0.f;
        if (f >= 0 && (s ? k : n) < NR) v = __bfloat162float(s ? se2[k * NF + f] : se1[f * NR + n]);
        reinterpret_cast<__nv_bfloat16*>(g_se)[c * 256 + tid] = __float2bfloat16(s ? 0.5f * v : v);
    } else if (tid < 320) {
        const int q = tid - 256;
        reinterpret_cast<float*>(g_w2)[c * 64 + q] = 0.5f * __bfloat162float(w2[c * 64 + (q & 48) + 4 * (q & 2) + ((q >> 1) & 6) + (q & 1)]);
    }
    asm volatile("cp.async.wait_all;" ::: "memory");
    __syncthreads();
    const int k = 4 * (lane & 6) + 2 * (lane >> 3) + (lane & 1), i = fmap(k);
    const int g = lane >> 2, t = lane & 3;
#pragma unroll 4
    for (int task = warp; task < 128; task += 12) {
        const int nn = task & 15, eg = task >> 4, n = 16 * (c & 1) + nn;
        const uint32_t a = sb + (k < 28 ? (i * 16 + nn) * 128 : ZERO) + ((eg ^ (i & 1) ^ ((i >> 3) << 1)) << 4);
        uint4 v;
        asm volatile("ldmatrix.sync.aligned.m8n8.x4.trans.shared.b16 {%0,%1,%2,%3}, [%4];"
                     : "=r"(v.x), "=r"(v.y), "=r"(v.z), "=r"(v.w)
                     : "r"(a));
        if (t == 3) {
            const uint32_t mask = (eg & 1) ? 0xffff0000u : 0xffffu;
            v.x &= mask;
            v.y &= mask;
        }
        const int ch = (t < 2 ? t ^ ((g >> 1) & 1) : t) ^ ((n >> 1) & 3);
        const int step = (g & 1) + 2 * (eg & 1) + 2 * (g & 6);
        g_wc[(eg >> 2) * 8192 + step * 512 + ((eg >> 1) & 1) * 256 + s * 128 + n * 4 + ch] = v;
    }
    __threadfence();
    __syncthreads();
    if (tid == 0) atomicAdd(&g_ready, 1u);
}

#define PACE1 2250
#define PACE2 2850
#define START_MIN 3400
#define WDELAY 1600
#define WSTEP 500
#define WPF_AT 2600
#define WPF_STEP 800
#define POLL_AT 6500
#define T_SHIFT 300
constexpr int DB0 = 6;

__global__ void __cluster_dims__(2, 1, 1) __launch_bounds__(384, 1)
fibinet_kernel(const int* __restrict__ idx, const uint4* __restrict__ table,
               const __nv_bfloat16* __restrict__ se1, const __nv_bfloat16* __restrict__ se2,
               const __nv_bfloat16* __restrict__ wc,
               const unsigned char* __restrict__ w1, const __nv_bfloat16* __restrict__ w2, __nv_bfloat16* __restrict__ out,
               const __grid_constant__ CUtensorMap tm_w1, const __grid_constant__ CUtensorMap tm_bi) {
    extern __shared__ __align__(1024) unsigned char smem[];
    const int tid = threadIdx.x;
    const int cta = blockIdx.x - NPREP, grp = cta >> 1, rank = cta & 1, lane = tid & 31;
    uint32_t ids[13][4], cid[3][2];
    const uint32_t idle = (tid >> 8) | (cta < 0);
    const uint32_t row = ((tid >> 5) & 3) * 16 + (lane >> 3);
    const unsigned char* ib = reinterpret_cast<const unsigned char*>(idx) + (int64_t)grp * (64 * NF * 4);
    {
        const unsigned char* ip = ib + (row * (NF * 4) + ((tid >> 4) & 8));
#pragma unroll
        for (int u = 0; u < 4; u++) {
            ids[0][u] = ids[1][u] = 0;
            asm volatile("{.reg .pred p; setp.eq.u32 p, %3, 0; @p ld.global.nc.L2::128B.v2.u32 {%0,%1}, [%2];}"
                         : "+r"(ids[0][u]), "+r"(ids[1][u])
                         : "l"(ip + 16 * NF * u), "r"(idle));
        }
    }
    const uint32_t t_0 = clock32();
    {
        const uint32_t co = ((tid & 127) >> 1) * (NF * 4) + ((tid >> 4) & 8) + 16 + 16 * (tid & 1);
#pragma unroll
        for (int k = 0; k < 3; k++) {
            cid[k][0] = cid[k][1] = 0;
            asm volatile("{.reg .pred p; setp.eq.u32 p, %3, 0; @p ld.global.nc.v2.u32 {%0,%1}, [%2];}"
                         : "+r"(cid[k][0]), "+r"(cid[k][1])
                         : "l"(ib + (co + 32 * k - (k == 2 ? 8 * ((tid >> 7) & tid & 1) : 0))), "r"(idle));
        }
    }
    const uint32_t t_start = (t_0 ^ (clock32() & blockIdx.y)) - T_SHIFT;
    const uint32_t sb = (uint32_t)__cvta_generic_to_shared(smem);
    uint32_t gd0 = sb + (tid >> 7) * XDELTA + row * 128 + (((lane & 7) ^ (lane >> 3) ^ ((tid >> 5) & 4)) << 4);
    const uint4* tp = table + (lane & 7);
    auto gather = [&](int i) {
#pragma unroll
        for (int u = 0; u < 4; u++)
            asm volatile(
                "{.reg .u64 a; .reg .pred p; setp.eq.u32 p, %3, 0; mad.wide.u32 a, %2, 128, %1; @p cp.async.cg.shared.global [%0], [a], 16;}" ::"r"(
                    (gd0 ^ ((u & 1) * 64)) + xpair(i) + u * 512),
                "l"(tp), "r"(ids[i][u]), "r"(i == 0 ? idle : 0u)
                : "memory");
        CP_COMMIT();
    };
    gather(0);
    if (cta < 0) {
        prep_cta(sb, blockIdx.x, wc, se1, se2, w2);
        return;
    }
    if (tid == 288) asm volatile("prefetch.tensormap [%0];" ::"l"(&tm_w1));
    const int warp = __reduce_max_sync(0xffffffffu, tid >> 5);
    const int w = warp >> 2;

    if (w == 2) {
        asm volatile("setmaxnreg.dec.sync.aligned.u32 40;");
        auto load_wc = [&](int gi) {
            if (elect()) {
                const unsigned char* src = reinterpret_cast<const unsigned char*>(g_wc) + rank * 131072;
                mbar_expect(sb + BAR_WC + gi * 8, (wcfirst(gi + 1) - wcfirst(gi)) * 8192);
#pragma unroll
                for (int c = wcfirst(gi); c < wcfirst(gi + 1); c++) bulk(sb + wcslot(c), src + c * 8192, 8192, sb + BAR_WC + gi * 8);
            }
            __syncwarp();
        };
        if (warp == 8) {
            if (elect()) {
                mbar_init(sb + BAR_Z, 1);
                mbar_expect(sb + BAR_Z, 8192);
                tma2d(sb + ZOFF, &tm_bi, sb + BAR_Z, 32 * rank, 0);
            }
#pragma unroll
            for (int f = 0; f < 26; f++) {
                if (f == 2) {
                    if (elect()) {
#pragma unroll
                        for (int k = 2; k < 8; k++) mbar_init(sb + BAR_FULL + k * 8, 1);
                        asm volatile("fence.mbarrier_init.release.cluster;" ::: "memory");
                    }
                    __syncwarp();
                    asm volatile("barrier.cluster.arrive.relaxed.aligned;" ::: "memory");
                    mbar_wait(sb + BAR_Z);
#pragma unroll
                    for (int k = 0; k < 2; k++)
                        sts128(sb + ZOFF + (k * 32 + lane) * 128 + ((4 ^ (lane & 7)) << 4), 0x3c803c80u, 0x3c803c80u, 0x3c803c80u, 0x3c803c80u);
                    PROXY_FENCE();
                    asm volatile("bar.arrive 0, 384;" ::: "memory");
                    TS(31);
                }
                if (f == 5) asm volatile("bar.sync 7, 64;" ::: "memory");
                if (f >= 5) mbar_wait(sb + bdone(f - 5), bpar(f - 5));
                if (f >= 2 && f < 5)
                    while (clock32() - t_start < WDELAY + (f - 2) * WSTEP) {
                    }
                if (elect()) {
                    if (f < 2) mbar_init(sb + BAR_FULL + f * 8, 1);
                    mbar_expect(sb + bfull(f), 16384);
                    tma2d(sb + slot(2 * wl(f)), &tm_w1, sb + bfull(f), 128 * rank + 64 * (f & 1), fieldof(f) * 64);
                    tma2d(sb + slot(wl(f)), &tm_w1, sb + bfull(f), 128 * rank + 64 - 64 * (f & 1), fieldof(f) * 64);
                }
                TS(f);
            }
            asm volatile("bar.arrive 8, 128;" ::: "memory");
            TS_DUMP(2);
        } else if (warp == 9) {
            if (elect()) {
#pragma unroll
                for (int k = 0; k < 8; k++) mbar_init(sb + BAR_WC + k * 8, k < 7 ? 1 : 8);
                asm volatile("fence.mbarrier_init.release.cluster;" ::: "memory");
            }
            __syncwarp();
            asm volatile("barrier.cluster.arrive.relaxed.aligned;" ::: "memory");
            asm volatile("bar.sync 0, 384;" ::: "memory");
            while (clock32() - t_start < POLL_AT) __nanosleep(100);
            if (elect()) {
                unsigned v, it = 0;
                do {
                    asm volatile("ld.acquire.gpu.global.u32 %0, [%1];" : "=r"(v) : "l"(&g_ready) : "memory");
                } while (v < NPREP && ++it < 4000000u);
                asm volatile("fence.proxy.async.global;" ::: "memory");
                mbar_expect(sb + BAR_SE, 2048 + 512);
                bulk(sb + SEOFF, g_se, 2048, sb + BAR_SE);
                bulk(sb + W2OFF, g_w2 + rank * 32, 512, sb + BAR_SE);
            }
            __syncwarp();
            TS(0);
            asm volatile("bar.sync 8, 128;" ::: "memory");
#pragma unroll
            for (int gi = 0; gi < 3; gi++) {
                mbar_wait(sb + bdone(21 + gi), bpar(21 + gi));
                load_wc(gi);
                TS(1 + gi);
            }
        } else if (warp == 10) {
            if (elect()) {
#pragma unroll
                for (int k = 0; k < 8; k++) mbar_init(sb + BAR_DONE + k * 8, 4);
                asm volatile("fence.mbarrier_init.release.cluster;" ::: "memory");
            }
            __syncwarp();
            asm volatile("barrier.cluster.arrive.relaxed.aligned;" ::: "memory");
            asm volatile("bar.arrive 7, 64;" ::: "memory");
            asm volatile("bar.sync 0, 384;" ::: "memory");
#pragma unroll 1
            for (int k = 0; k < 7; k++) {
                while (clock32() - t_start < (uint32_t)(WPF_AT + k * WPF_STEP)) __nanosleep(150);
                if (lane < 6)
                    asm volatile("prefetch.global.L2 [%0];" ::"l"(w1 + (5 + k * 3 + (lane >> 1)) * 32768 + cta * 256 + (lane & 1) * 128));
            }
            asm volatile("bar.sync 8, 128;" ::: "memory");
        } else {
            asm volatile("bar.sync 0, 384;" ::: "memory");
            asm volatile("bar.sync 8, 128;" ::: "memory");
        }
        {
            uint32_t bw[2][4], z0[4], z1[4];
            mbar_wait(sb + BAR_SE);
            lds128(bw[0], sb + SEOFF + lane * 16);
            lds128(bw[1], sb + SEOFF + 512 + lane * 16);
            asm volatile("bar.sync 2, 384;" ::: "memory");
            lds128(z0, sb + ZQOFF + (tid & 127) * 16);
            lds128(z1, sb + ZQOFF + 2048 + (tid & 127) * 16);
            TS(8);
            float s[2][4] = {};
#pragma unroll
            for (int n = 0; n < 2; n++) {
                mma16816(s[n], z0, bw[0][2 * n], bw[0][2 * n + 1]);
                mma16816(s[n], z1, bw[1][2 * n], bw[1][2 * n + 1]);
            }
            lds128(bw[0], sb + SEOFF + 1024 + lane * 16);
            lds128(bw[1], sb + SEOFF + 1536 + lane * 16);
            float th[8];
#pragma unroll
            for (int k = 0; k < 8; k++) th[k] = gelu_tanh(s[k >> 2][k & 3]);
            SCHED_FENCE();
            TS(9);
            uint32_t gq[4];
#pragma unroll
            for (int k = 0; k < 4; k++)
                gq[k] = pack(s[k >> 1][2 * (k & 1)] * ffma(th[2 * k], 0.5f, 0.5f), s[k >> 1][2 * (k & 1) + 1] * ffma(th[2 * k + 1], 0.5f, 0.5f));
            float a[4][4] = {};
#pragma unroll
            for (int n = 0; n < 4; n++) mma16816(a[n], gq, bw[n >> 1][2 * (n & 1)], bw[n >> 1][2 * (n & 1) + 1]);
#pragma unroll
            for (int k = 0; k < 16; k++)
                if (k < 13 || k == 14) a[k >> 2][k & 3] = tanh_fast(a[k >> 2][k & 3]);
            SCHED_FENCE();
            TS(10);
            uint32_t ap[8];
#pragma unroll
            for (int k = 0; k < 8; k++)
                ap[k] = pack(ffma(a[k >> 1][2 * (k & 1)], 0.5f, 0.5f), ffma(a[k >> 1][2 * (k & 1) + (k < 6)], 0.5f, 0.5f));
            sts128(sb + GOFF + (tid & 127) * 16, ap[0], ap[1], ap[2], ap[3]);
            sts128(sb + GOFF + 2048 + (tid & 127) * 16, ap[4], ap[5], ap[6], ap[7]);
            asm volatile("bar.arrive 3, 384;" ::: "memory");
            TS(11);
        }
        if (warp == 9) {
            load_wc(3);
            load_wc(4);
            mbar_wait(sb + BAR_TD);
            load_wc(5);
            if (lane == 0 && atomicAdd(&g_seen, 1u) == NMAIN - 1) {
                g_seen = 0;
                g_ready = 0;
            }
            if (lane < 16) TS_DUMP(3);
        } else if (warp == 11) {
            if (lane < 16) reinterpret_cast<uint32_t*>(out)[cta * 16 + lane] = 0;
            asm volatile("barrier.cluster.arrive.release.aligned;" ::: "memory");
        } else if (warp == 10) {
            uint32_t* dst = reinterpret_cast<uint32_t*>(out) + grp * 32 + lane;
            asm volatile("barrier.cluster.wait.acquire.aligned;" : "+l"(dst)::"memory");
            SCHED_FENCE();
            asm volatile("bar.sync 4, 288;" ::: "memory");
            uint32_t p[4];
            lds64(p[0], p[1], sb + PARTOFF + lane * 8);
            lds64(p[2], p[3], sb + PARTOFF + 256 + lane * 8);
            asm volatile("red.relaxed.gpu.global.add.noftz.bf16x2 [%0], %1;" ::"l"(dst),
                         "r"(pack(__uint_as_float(p[0]) + __uint_as_float(p[2]), __uint_as_float(p[1]) + __uint_as_float(p[3])))
                         : "memory");
        }
    } else {
        asm volatile("setmaxnreg.inc.sync.aligned.u32 232;");
        asm volatile("barrier.cluster.arrive.relaxed.aligned;" ::: "memory");
        const uint32_t sb = __reduce_max_sync(0xffffffffu, (uint32_t)__cvta_generic_to_shared(smem) | (tid >> 10));
        const int t128 = opaque(tid & 127), lane = t128 & 31;
        const int g = lane >> 2, t = lane & 3, wq = warp & 3;
        gd0 = opaque(gd0);
        TS(28);
        float acc[84];
#pragma unroll
        for (int k = 0; k < 84; k++) asm volatile("mov.b32 %0, 0;" : "=f"(acc[k]));
        uint32_t e0[9], e1[9], e2[9];
        uint32_t X[13][2][4];
        uint32_t zq[4] = {0, 0, 0, 0};
        const uint64_t dA = mkdesc(sb + w * XDELTA, 16, 1024, 1);
        uint32_t dBlo = (uint32_t)mkdesc(sb + ZOFF, 0, 0, 0);
        const uint32_t xl0 = opaque(sb + (t & 1) * XDELTA + (16 * wq + g) * 128 + (((4 * rank + 2 * w) ^ (4 * (t & 1)) ^ g) << 4));
        const uint32_t hi_half = t >> 1;
        const uint32_t sa0 = opaque(sb + AOFF + t * 4096 + (t >> 1) * 16 + (wq * 32 + g * 4 + w) * 16);
        const uint32_t sa1 = opaque(((g & 2) << 4) | ((t & 1) << 3));
        const uint32_t zero = __reduce_max_sync(0xffffffffu, blockIdx.y | (tid >> 10));
        auto expand = [&](int k0, int k1) {
#pragma unroll
            for (int k = k0; k < k1; k++)
#pragma unroll
                for (int u = 0; u < 4; u++)
                    asm volatile("shfl.sync.idx.b32 %0, %1, %2, 31, 0xffffffff;"
                                 : "=r"(ids[k][u])
                                 : "r"(k < 12 ? cid[(k - 2) >> 2][k & 1] : w ? cid[2][1] : cid[2][0]),
                                   "r"(2 * (lane >> 3) + 8 * u + (((k - 2) >> 1) & 1)));
        };
        auto twarm = [&]() {
            float s1[8];
            WG_FENCE();
            wgmma_rs_n16_set(s1, zq, mkdesc(sb + AOFF, 16, 512, 2));
            WG_COMMIT();
            WG_WAIT0();
            pin(s1);
            asm volatile("{.reg .pred p; setp.ne.u32 p, %1, 0; @p st.shared.f32 [%1], %0;}" ::"f"(s1[0]), "r"(zero));
        };
        expand(2, 8);
        twarm();
        TS(26);
        while (clock32() - t_start < PACE1) {
        }
        gather(1);
        expand(8, 13);
        twarm();
        TS(30);
        while (clock32() - t_start < PACE2) {
        }
        gather(2);
        twarm();
        asm volatile("bar.sync 0, 384;" ::: "memory");
        auto lift = [&](int i) {
            const int m = 2 * (i >> 2) + (i & 1);
#pragma unroll
            for (int r = 0; r < 2; r++)
#pragma unroll
                for (int cc = 0; cc < 2; cc++) {
                    const uint32_t a = (xl0 ^ (cc * 16)) + xpair(i) + r * 1024;
                    if (i == 12 ? r : (i & 2)) lds128_if(X[i == 12 ? 12 : 2 * m + r][cc], a, hi_half);
                    else lds128(X[2 * m + r][cc], a);
                }
        };
        auto store_pair = [&](int m, int half, const uint32_t (&ea)[9]) {
            uint32_t a;
            if (m < 4) a = sa0 + (sa1 ^ (((m & 1) << 5) | ((m >> 1) << 3)));
            else a = sb + BOFF + t * 2048 + (wq * 32 + g * 4 + ((2 * (m & 1) + w) ^ t)) * 8;
#pragma unroll
            for (int n = half; n < 4; n += 2)
#pragma unroll
                for (int u = 0; u < 2; u++)
                    sts64(a + (m < 4 ? (8 * n + u) * 2048 + n * 32 : (8 * n + u) * 1024),
                          __byte_perm(ea[2 * n], e1[2 * n], u ? 0x7632 : 0x5410),
                          __byte_perm(ea[2 * n + 1], e1[2 * n + 1], u ? 0x7632 : 0x5410));
        };
        auto z_pair = [&](int m, uint32_t a, uint32_t b) {
            asm volatile("{.reg .pred p; setp.eq.u32 p, %4, %5; @p prmt.b32 %0, %2, %3, 0x5410; @p prmt.b32 %1, %2, %3, 0x7632;}"
                         : "+r"(zq[2 * (m >> 2)]), "+r"(zq[2 * (m >> 2) + 1])
                         : "r"(a), "r"(b), "r"(t), "r"(m & 3));
        };

        TS(29);
        mbar_wait(sb + BAR_FULL + w * 8);
        CP_WAIT(2);
        while (clock32() - t_start < START_MIN) {
        }
        if (w == 1) {
            asm volatile("bar.arrive 6, 256;" ::: "memory");
            asm volatile("bar.sync 5, 256;" ::: "memory");
        }
#pragma unroll
        for (int i = 0; i < 13; i++) {
            const uint64_t da = dA + (xpair(i) >> 4) + ((uint64_t)i << 16);
            dBlo += (uint32_t)(w ? wl(2 * i + 1) - (i ? wl(2 * i - 1) : 0) : wl(2 * i) - (i ? wl(2 * i - 2) : 0)) *
                    (uint32_t)((SLOT << 12) - (SLOT >> 3));
            const uint64_t db = mkdesc(0, 0, 1024, 1) | dBlo;
            TS(i);
            WG_FENCE();
            wgmma_ss_n168_acc(acc, da, db + w * 256);
            wgmma_ss_n168_acc(acc, da + 2, db + w * 256 + 128);
            wgmma_ss_n168_acc(acc, da + 4, db + (w ^ 1) * 256);
            wgmma_ss_n168_acc(acc, da + 6, db + (w ^ 1) * 256 + 128);
            WG_COMMIT();
            if (i == 0) {
                if (w == 0) {
                    asm volatile("bar.arrive 5, 256;" ::: "memory");
                    asm volatile("bar.sync 6, 256;" ::: "memory");
                }
            } else {
                mbar_wait(sb + bdone(2 * i - 2) + (w ^ 1) * 8, bpar(2 * i - 2));
            }
            if (i < 10) gather(i + 3);
            if (i == 12) mbar_wait(sb + BAR_SE);
            lift(i);
            if (i == 10 || i == 11) mbar_wait(sb + bdone(2 * i - 2) + w * 8, bpar(2 * i - 2));
            if (i >= 2 && !(i & 1)) {
                z_pair((i - 2) >> 1, e0[8], e1[8]);
                store_pair((i - 2) >> 1, 0, e0);
#pragma unroll
                for (int k = 0; k < 8; k++) e2[k] = e0[k];
            } else if (i >= 3) {
                store_pair((i - 3) >> 1, 1, e2);
            }
            const uint32_t rdy = i < 12 ? mbar_test(sb + bfull(2 * i + 2) + w * 8, bpar(2 * i + 2)) : 0;
            WG_WAIT0();
            pin(acc);
            if (i == 12) TS(13);
            if (i == 0) TS(27);
            if (i < 10) CP_WAIT(2);
            else if (i == 10) CP_WAIT(1);
            else if (i == 11) CP_WAIT(0);
            if (i < 12 && lane == 0) mbar_arrive(sb + bdone(2 * i) + w * 8);
#pragma unroll
            for (int k = 0; k < 9; k++) {
                const int k0 = 64 + 2 * (k & 5) + ((k >> 1) & 1);
                const uint32_t v = k == 8 ? pack(acc[80], acc[82]) : i < 12 ? pack(acc[64 + 2 * k], acc[65 + 2 * k]) : pack(acc[k0], acc[k0 + 4]);
                if (i & 1) e1[k] = v;
                else e0[k] = v;
            }
            if (i < 12) {
#pragma unroll
                for (int k = 64; k < 83; k++)
                    if (k != 81) asm volatile("mov.b32 %0, %1;" : "+f"(acc[k]) : "r"(zero));
                mbar_wait_unless(rdy, sb + bfull(2 * i + 2) + w * 8, bpar(2 * i + 2));
            } else {
                z_pair(6, e0[8], 0);
                sts128(sb + ZQOFF + w * 2048 + t128 * 16, zq[0], zq[1], zq[2], zq[3]);
                asm volatile("bar.arrive 2, 384;" ::: "memory");
            }
        }
        TS(14);

        uint32_t ai[8];
        float sum0 = 0.f, sum1 = 0.f;
        float th[32];
        uint32_t hw[4][4];
        auto deep_issue = [&](int k2) {
            lds128(hw[k2], sb + W2OFF + w * 256 + t * 16 + k2 * 64);
#pragma unroll
            for (int k = 8 * k2; k < 8 * k2 + 8; k++) th[k] = gelu_tanh(acc[k]);
        };
        auto deep_use = [&](int k2) {
#pragma unroll
            for (int k = 8 * k2; k < 8 * k2 + 8; k++) {
                const float h = __uint_as_float(hw[k2][((k >> 1) & 2) + (k & 1)]);
                const float y = ffma(th[k], h, h);
                if (k & 2) sum1 = ffma(acc[k], y, sum1);
                else sum0 = ffma(acc[k], y, sum0);
            }
        };
        auto deep_send = [&](int k0, int k1) {
#pragma unroll
            for (int k = k0; k < k1; k++)
                sts128(sb + EXOFF + w * SLOT + t128 * 16 + k * 2048, pack(acc[32 + 8 * k], acc[33 + 8 * k]),
                       pack(acc[34 + 8 * k], acc[35 + 8 * k]), pack(acc[36 + 8 * k], acc[37 + 8 * k]), pack(acc[38 + 8 * k], acc[39 + 8 * k]));
        };
        uint32_t o[4][4];
        auto deep_recv = [&](int k0, int k1) {
#pragma unroll
            for (int k = k0; k < k1; k++) lds128(o[k], sb + EXOFF + (w ^ 1) * SLOT + t128 * 16 + k * 2048);
        };
        auto deep_add = [&](int k0, int k1) {
            const uint32_t eye = (g >> 1) == t ? ((g & 1) ? 0x3f800000u : 0x3f80u) : 0u;
#pragma unroll
            for (int k = 2 * k0; k < 2 * k1; k++)
                asm volatile("mma.sync.aligned.m16n8k8.row.col.f32.bf16.bf16.f32 {%0,%1,%2,%3}, {%4,%5}, {%6}, {%0,%1,%2,%3};"
                             : "+f"(acc[4 * k]), "+f"(acc[4 * k + 1]), "+f"(acc[4 * k + 2]), "+f"(acc[4 * k + 3])
                             : "r"(o[k >> 1][2 * (k & 1)]), "r"(o[k >> 1][2 * (k & 1) + 1]), "r"(eye));
        };
        auto store_last = [&]() {
#pragma unroll
            for (int n = 0; n < 4; n++) sts64(sb + COFF + w * 4096 + n * 1024 + (t128 ^ w) * 8, e0[2 * n], e0[2 * n + 1]);
            store_pair(5, 1, e2);
        };
        const uint32_t la = (sb + AOFF + w * (16 * 2048 + 64) + (wq * 32 + g * 4 + (t ^ (g & 2))) * 16);
        const uint32_t lb = (sb + BOFF + w * (16 * 1024) + t128 * 8);
        const uint32_t lc0 = (sb + COFF + (t & 1) * (4096 + 8) + w * 2048 + (wq * 8 + g) * 32), lc1 = lc0 ^ 8;
        uint32_t Ap[2][2][4];
        auto load_a = [&](int s) {
            const int e = estep(s);
            lds128(Ap[s & 1][0], la + e * 2048 + (e >> 2) * 16);
            lds64(Ap[s & 1][1][0], Ap[s & 1][1][1], (lb ^ ((e & 6) * 4)) + e * 1024);
            if (!(s & 2)) lds64(Ap[s & 1][1][2], Ap[s & 1][1][3], ((e & 2) ? lc1 : lc0) + (e & 1) * 1024 + (e & 4) * 4);
        };
        {
            uint32_t v[2][4];
            deep_send(0, 2);
            asm volatile("bar.sync 1, 256;" ::: "memory");
            deep_recv(0, 2);
            deep_send(2, 4);
            TS(15);
            deep_add(0, 2);
            deep_issue(0);
            asm volatile("bar.sync 1, 256;" ::: "memory");
            deep_recv(2, 4);
            SCHED_FENCE();
            deep_add(2, 4);
            TS(16);
            deep_issue(1);
            deep_use(0);
            store_last();
            SCHED_FENCE();
            TS(17);
            deep_issue(2);
            deep_use(1);
            mbar_wait(sb + BAR_WC);
            deep_use(2);
            TS(18);
            asm volatile("bar.sync 3, 384;" ::: "memory");
            lds128(v[0], sb + GOFF + t128 * 16);
            lds128(v[1], sb + GOFF + 2048 + t128 * 16);
            load_a(0);
            load_a(1);
            deep_issue(3);
#pragma unroll
            for (int k = 0; k < 8; k++) ai[k] = v[k >> 2][k & 3];
        }
        TS(19);

        uint32_t fin_a, dsum[2], tid2;
        const uint32_t hi2 = lb & 16;
        {
            uint64_t dW[4];
#pragma unroll
            for (int k = 0; k < 4; k++) dW[k] = mkdesc(sb + w * 4096, 16, 512, 2) + ((uint64_t)zero << 32) + (wcslot(0) >> 4) + (k >> 1) * 128 + (k & 1) * 2;
            uint32_t Aq[2][2][4], pq[13], gate[13];
            float S[2][2][16];
            auto scale_a = [&](int s) {
#pragma unroll
                for (int k = 0; k < ((s & 2) ? 6 : 8); k++)
                    Aq[s & 1][k >> 2][k & 3] = hmul2(Ap[s & 1][k >> 2][k & 3], ai[k < 4 ? k ^ (estep(s) & 2) : k]);
            };
            auto sbuf = [](int s) { return s <= DB0 ? 0 : (s - DB0) & 1; };
            auto issue = [&](int s) {
                const bool first = s == 0 || s == DB0 + 1;
                WG_FENCE();
                if (first) wgmma_rs_n32_set(S[sbuf(s)][0], Ap[s & 1][0], dW[0]);
                else wgmma_rs_n32_pred(S[sbuf(s)][0], Ap[s & 1][0], dW[0], zero);
                wgmma_rs_n32_acc(S[sbuf(s)][0], Ap[s & 1][1], dW[1]);
                if (first) wgmma_rs_n32_set(S[sbuf(s)][1], Aq[s & 1][0], dW[2]);
                else wgmma_rs_n32_pred(S[sbuf(s)][1], Aq[s & 1][0], dW[2], zero);
                wgmma_rs_n32_acc(S[sbuf(s)][1], Aq[s & 1][1], dW[3]);
                WG_COMMIT();
                if (s < 15) {
#pragma unroll
                    for (int k = 0; k < 4; k++)
                        asm volatile("add.s64 %0, %0, %1;" : "+l"(dW[k]) : "l"((int64_t)((wcslot(s + 1) - wcslot(s)) / 16)));
                }
            };
            scale_a(0);
            issue(0);
            SCHED_FENCE();
            deep_use(3);
            scale_a(1);
            mbar_wait(sb + BAR_WC + 8);
#pragma unroll
            for (int e = 0; e < 16; e++) {
                if (e >= DB0 && e < 15) {
                    issue(e + 1);
                    WG_WAIT1();
                } else {
                    WG_WAIT0();
                }
                pin(S[sbuf(e)][0]);
                pin(S[sbuf(e)][1]);
                if (e == 0 && (lb & 0xf8) == 0) mbar_arrive(sb + BAR_TD);
                if (e == 0) TS(20);
                if (e + 2 < 16) load_a(e + 2);
#pragma unroll
                for (int q = 0; q < 13; q++) {
                    const int ix = 4 * (q >> 2) + 2 * (q & 1) + ((q >> 1) & 1);
                    uint32_t v = pack(S[sbuf(e)][0][ix], S[sbuf(e)][1][ix ^ 1]);
                    if (q == 12)
                        asm volatile("{.reg .pred p; setp.ne.u32 p, %3, 0; @p cvt.rn.bf16x2.f32 %0, %2, %1;}"
                                     : "+r"(v)
                                     : "f"(S[sbuf(e)][0][14]), "f"(S[sbuf(e)][1][15]), "r"(hi2));
                    const uint32_t x = X[q][(e >> 1) & 1][e >> 2];
                    pq[q] = (e & 1) ? hfma2_bcast<1>(v, x, pq[q]) : hfma2_bcast<0>(v, x, e ? pq[q] : 0u);
                }
                if (e < DB0) {
                    issue(e + 1);
                    SCHED_FENCE();
                }
                if (e == 3) {
                    const float h0 = __uint_as_float(__float_as_uint(sum0) & 0xffff0000u);
                    const float h1 = __uint_as_float(__float_as_uint(sum1) & 0xffff0000u);
                    dsum[0] = pack(sum0 - h0, h0);
                    dsum[1] = pack(sum1 - h1, h1);
                }
                if (e == 13) {
                    asm volatile("mov.u32 %0, %%tid.x;" : "=r"(tid2));
                    fin_a = sb + PARTOFF + (tid2 >> 5) * 64 + (tid2 & 28);
                }
                if (e == 14) {
#pragma unroll
                    for (int q = 0; q < 13; q++)
                        asm volatile("prmt.b32 %0, %1, 0x3f80, %2;"
                                     : "=r"(gate[q])
                                     : "r"(q < 12 ? ai[2 * (q >> 2) + (q & 1)] : hi2 ? ai[7] : ai[6]), "r"((q & 2) ? 0x3254 : 0x1054));
                }
                if (e + 2 < 16) scale_a(e + 2);
                if (e == 0 || e == 3 || e == 6 || e == 9) mbar_wait(sb + BAR_WC + (e / 3 + 2) * 8);
                else if (e < 15) SCHED_FENCE();
                if (e == 7) TS(21);
            }
            float r0[4] = {0.f, 0.f, 0.f, 0.f}, r1[4] = {0.f, 0.f, 0.f, 0.f}, r2[4] = {0.f, 0.f, 0.f, 0.f};
#pragma unroll
            for (int c = 0; c < 3; c++) {
                const uint32_t a[4] = {pq[4 * c], pq[4 * c + 1], pq[4 * c + 2], pq[4 * c + 3]};
                mma16816(r0, a, gate[4 * c], gate[4 * c + 2]);
                mma16816(r1, a, gate[4 * c + 1], gate[4 * c + 3]);
            }
            const uint32_t rest[4] = {dsum[0], dsum[1], hi2 ? 0u : pq[12], hi2 ? pq[12] : 0u};
            mma16816(r2, rest, 0x3f803f80u, gate[12]);
            sum0 = (tid2 & 4) ? r0[1] + r2[1] : r0[0] + r2[0];
            sum1 = (tid2 & 4) ? r1[3] + r2[3] : r1[2] + r2[2];
        }
        TS(22);
        {
            asm volatile("{.reg .pred p; setp.eq.u32 p, %3, %4; @p st.shared.f32 [%0], %1; @p st.shared.f32 [%0 + 32], %2;}" ::"r"(fin_a),
                         "f"(sum0), "f"(sum1), "r"(tid2 & 3), "r"((tid2 >> 3) & 3)
                         : "memory");
            asm volatile("bar.arrive 4, 288;" ::: "memory");
            if (wq == 0) TS_DUMP(w);
        }
    }
}

typedef CUresult (*EncodeFn)(CUtensorMap*, CUtensorMapDataType, cuuint32_t, void*, const cuuint64_t*, const cuuint64_t*,
                             const cuuint32_t*, const cuuint32_t*, CUtensorMapInterleave, CUtensorMapSwizzle,
                             CUtensorMapL2promotion, CUtensorMapFloatOOBfill);

}

extern "C" void kernel_launch(void* const* d_in, const int* in_sizes, int n_in, void* d_out, int out_size) {
    static EncodeFn encode = nullptr;
    if (!encode) {
        void* fn = nullptr;
        cudaDriverEntryPointQueryResult qr;
        cudaGetDriverEntryPoint("cuTensorMapEncodeTiled", &fn, cudaEnableDefault, &qr);
        encode = (EncodeFn)fn;
        cudaFuncSetAttribute(fibinet_kernel, cudaFuncAttributeMaxDynamicSharedMemorySize, SMEM_BYTES);
    }
    CUtensorMap tm;
    const cuuint64_t gd[2] = {NH, NF * ND};
    const cuuint64_t gs[1] = {NH * 2};
    const cuuint32_t bd[2] = {64, 64}, es[2] = {1, 1};
    encode(&tm, CU_TENSOR_MAP_DATA_TYPE_BFLOAT16, 2, d_in[6], gd, gs, bd, es, CU_TENSOR_MAP_INTERLEAVE_NONE,
           CU_TENSOR_MAP_SWIZZLE_128B, CU_TENSOR_MAP_L2_PROMOTION_L2_256B, CU_TENSOR_MAP_FLOAT_OOB_FILL_NONE);
    CUtensorMap tb;
    const cuuint64_t gd2[2] = {ND, ND};
    const cuuint64_t gs2[1] = {ND * 2};
    encode(&tb, CU_TENSOR_MAP_DATA_TYPE_BFLOAT16, 2, d_in[4], gd2, gs2, bd, es, CU_TENSOR_MAP_INTERLEAVE_NONE,
           CU_TENSOR_MAP_SWIZZLE_128B, CU_TENSOR_MAP_L2_PROMOTION_L2_256B, CU_TENSOR_MAP_FLOAT_OOB_FILL_NONE);
    fibinet_kernel<<<NPREP + NMAIN, 384, SMEM_BYTES>>>(
        (const int*)d_in[0], (const uint4*)d_in[1], (const __nv_bfloat16*)d_in[2], (const __nv_bfloat16*)d_in[3],
        (const __nv_bfloat16*)d_in[5], (const unsigned char*)d_in[6], (const __nv_bfloat16*)d_in[7], (__nv_bfloat16*)d_out, tm, tb);
}
```

```cpp
#include <cuda_runtime.h>
#include <cuda_bf16.h>
#include <cuda.h>
#include <stdint.h>

namespace {

constexpr int NF = 26, ND = 64, NH = 256, NR = 13;
constexpr int NPREP = 4;
constexpr int NMAIN = 128;

constexpr int SLOT = 8192;
constexpr int ZOFF = 15 * SLOT;
__host__ __device__ constexpr int slot(int s) { return ZOFF - s * SLOT; }
constexpr int BOFF = ZOFF + SLOT;
constexpr int AOFF = BOFF + 32768;
constexpr int COFF = slot(12);
constexpr int MOFF = AOFF + 65536 + 128;
constexpr int BAR_FULL = MOFF, BAR_DONE = MOFF + 64, BAR_WC = MOFF + 128, BAR_SE = MOFF + 176, BAR_TD = MOFF + 184,
              BAR_Z = MOFF + 192;
__host__ __device__ constexpr int bfull(int f) { return BAR_FULL + (f & 7) * 8; }
__host__ __device__ constexpr int bdone(int f) { return BAR_DONE + (f & 7) * 8; }
__host__ __device__ constexpr int bpar(int f) { return (f >> 3) & 1; }
constexpr int W2OFF = MOFF + 256, SEOFF = MOFF + 768;
constexpr int PARTOFF = SEOFF;
constexpr int SMEM_BYTES = MOFF + 2944;
constexpr int XDELTA = 2 * SLOT;
__host__ __device__ constexpr int xpair(int i) {
    return (i & 3) == 0 ? slot(11) : (i & 3) == 1 ? BOFF : (i & 3) == 2 ? BOFF + SLOT : slot(15);
}
__host__ __device__ constexpr int wl(int f) { return f % 5 == 0 ? 1 : f % 5 == 4 ? 7 : f % 5 + 2; }
__host__ __device__ constexpr int wcslot(int c) {
    return c == 0 ? slot(3) : c == 1 ? slot(8) : c == 2 ? slot(10) : c == 3 ? slot(15) : c == 4 ? slot(13)
         : c == 5 ? slot(11) : c == 6 ? slot(9) : c == 7 ? slot(14) : c == 8 ? slot(7) : c == 9 ? slot(2)
         : c == 10 ? slot(1) : c == 11 ? slot(4) : c == 12 ? slot(5) : c == 13 ? slot(6) : c == 14 ? ZOFF : slot(3);
}
__host__ __device__ constexpr int wcfirst(int gi) { return gi < 3 ? gi : gi == 3 ? 5 : gi == 4 ? 8 : gi == 5 ? 11 : 16; }
constexpr int EXOFF = slot(5);
constexpr int ZQOFF = slot(6);
constexpr int GOFF = ZQOFF + 4096;

__device__ uint4 g_wc[2 * 16 * 8192 / 16];
__device__ uint4 g_se[2048 / 16];
__device__ uint4 g_w2[NH / 8];
__device__ unsigned g_ready;
__device__ unsigned g_seen;

__host__ __device__ constexpr int fieldof(int f) { return f < 24 ? 4 * (f >> 2) + 2 * (f & 1) + ((f >> 1) & 1) : f; }
__device__ __forceinline__ int fmap(int n) { return n < 24 ? n : 24 + ((n >> 1) & 1); }
__host__ __device__ constexpr int estep(int s) { return (s & 1) + 2 * (s >> 2) + 4 * (s & 2); }

__device__ __forceinline__ uint64_t mkdesc(uint32_t addr, uint32_t lbo, uint32_t sbo, int sw) {
    return (uint64_t)((addr & 0x3ffff) >> 4) | ((uint64_t)(lbo >> 4) << 16) | ((uint64_t)(sbo >> 4) << 32) |
           ((uint64_t)sw << 62);
}
__device__ __forceinline__ void mbar_init(uint32_t b, uint32_t n) {
    asm volatile("mbarrier.init.shared.b64 [%0], %1;" ::"r"(b), "r"(n) : "memory");
}
__device__ __forceinline__ void mbar_wait(uint32_t b, uint32_t par = 0) {
    asm volatile(
        "{\n.reg .pred p, q;\n.reg .u32 n;\n"
        "mbarrier.try_wait.parity.shared.b64 p, [%0], %1;\n@p bra.uni WD%=;\nmov.u32 n, 0;\n"
        "WL%=:\nmbarrier.try_wait.parity.shared.b64 p, [%0], %1;\n@p bra.uni WD%=;\n"
        "add.u32 n, n, 1;\nsetp.lt.u32 q, n, 4000000;\n@q bra.uni WL%=;\nWD%=:\n}\n" ::"r"(b), "r"(par)
        : "memory");
}
__device__ __forceinline__ uint32_t mbar_test(uint32_t b, uint32_t par) {
    uint32_t ok;
    asm volatile("{.reg .pred p; mbarrier.test_wait.parity.shared.b64 p, [%1], %2; selp.u32 %0, 1, 0, p;}"
                 : "=r"(ok)
                 : "r"(b), "r"(par)
                 : "memory");
    return ok;
}
__device__ __forceinline__ void mbar_wait_unless(uint32_t ok, uint32_t b, uint32_t par) {
    asm volatile(
        "{\n.reg .pred p, q;\n.reg .u32 n;\n"
        "setp.ne.u32 p, %1, 0;\n@p bra.uni WD%=;\nmov.u32 n, 0;\n"
        "WL%=:\nmbarrier.try_wait.parity.shared.b64 p, [%0], %2;\n@p bra.uni WD%=;\n"
        "add.u32 n, n, 1;\nsetp.lt.u32 q, n, 4000000;\n@q bra.uni WL%=;\nWD%=:\n}\n" ::"r"(b), "r"(ok), "r"(par)
        : "memory");
}
__device__ __forceinline__ void mbar_arrive(uint32_t b) {
    asm volatile("mbarrier.arrive.shared.b64 _, [%0];" ::"r"(b) : "memory");
}
__device__ __forceinline__ void mbar_expect(uint32_t b, uint32_t bytes) {
    asm volatile("mbarrier.arrive.expect_tx.shared.b64 _, [%0], %1;" ::"r"(b), "r"(bytes) : "memory");
}
__device__ __forceinline__ uint32_t opaque(uint32_t v) { return __shfl_sync(0xffffffffu, v, threadIdx.x); }
__device__ __forceinline__ bool elect() {
    uint32_t p;
    asm volatile("{.reg .pred q; elect.sync _|q, 0xffffffff; selp.u32 %0, 1, 0, q;}" : "=r"(p));
    return p;
}
__device__ __forceinline__ void tma2d(uint32_t dst, const CUtensorMap* m, uint32_t bar, int x, int y) {
    asm volatile(
        "cp.async.bulk.tensor.2d.shared::cluster.global.mbarrier::complete_tx::bytes [%0], [%1, {%3, %4}], [%2];" ::"r"(dst),
        "l"(m), "r"(bar), "r"(x), "r"(y)
        : "memory");
}
__device__ __forceinline__ void bulk(uint32_t dst, const void* src, uint32_t bytes, uint32_t bar) {
    asm volatile("cp.async.bulk.shared::cluster.global.mbarrier::complete_tx::bytes [%0], [%1], %2, [%3];" ::"r"(dst),
                 "l"(src), "r"(bytes), "r"(bar)
                 : "memory");
}
__device__ __forceinline__ void cp16(uint32_t dst, const void* src) {
    asm volatile("cp.async.cg.shared.global [%0], [%1], 16;" ::"r"(dst), "l"(src) : "memory");
}
__device__ __forceinline__ void lds128(uint32_t (&v)[4], uint32_t a) {
    asm volatile("ld.shared.v4.u32 {%0,%1,%2,%3}, [%4];" : "=r"(v[0]), "=r"(v[1]), "=r"(v[2]), "=r"(v[3]) : "r"(a) : "memory");
}
__device__ __forceinline__ void lds128_if(uint32_t (&v)[4], uint32_t a, uint32_t p) {
    asm volatile("{.reg .pred q; setp.ne.u32 q, %5, 0; @q ld.shared.v4.u32 {%0,%1,%2,%3}, [%4];}"
                 : "+r"(v[0]), "+r"(v[1]), "+r"(v[2]), "+r"(v[3])
                 : "r"(a), "r"(p)
                 : "memory");
}
__device__ __forceinline__ void lds64(uint32_t& x, uint32_t& y, uint32_t a) {
    asm volatile("ld.shared.v2.u32 {%0,%1}, [%2];" : "=r"(x), "=r"(y) : "r"(a) : "memory");
}
__device__ __forceinline__ void sts128(uint32_t a, uint32_t x, uint32_t y, uint32_t z, uint32_t w) {
    asm volatile("st.shared.v4.u32 [%0], {%1,%2,%3,%4};" ::"r"(a), "r"(x), "r"(y), "r"(z), "r"(w) : "memory");
}
__device__ __forceinline__ void sts64(uint32_t a, uint32_t x, uint32_t y) {
    asm volatile("st.shared.v2.u32 [%0], {%1,%2};" ::"r"(a), "r"(x), "r"(y) : "memory");
}
__device__ __forceinline__ uint32_t pack(float lo, float hi) {
    uint32_t r;
    asm volatile("cvt.rn.bf16x2.f32 %0, %1, %2;" : "=r"(r) : "f"(hi), "f"(lo));
    return r;
}
__device__ __forceinline__ uint32_t hmul2(uint32_t a, uint32_t b) {
    uint32_t r;
    asm volatile("mul.rn.bf16x2 %0, %1, %2;" : "=r"(r) : "r"(a), "r"(b));
    return r;
}
template <int H>
__device__ __forceinline__ uint32_t hfma2_bcast(uint32_t a, uint32_t x, uint32_t c) {
    uint32_t r;
    if (H)
        asm volatile("{.reg .b16 l, h; .reg .b32 s; mov.b32 {l, h}, %2; mov.b32 s, {h, h}; fma.rn.bf16x2 %0, %1, s, %3;}"
                     : "=r"(r)
                     : "r"(a), "r"(x), "r"(c));
    else
        asm volatile("{.reg .b16 l, h; .reg .b32 s; mov.b32 {l, h}, %2; mov.b32 s, {l, l}; fma.rn.bf16x2 %0, %1, s, %3;}"
                     : "=r"(r)
                     : "r"(a), "r"(x), "r"(c));
    return r;
}
__device__ __forceinline__ float ffma(float a, float b, float c) {
    float r;
    asm volatile("fma.rn.f32 %0, %1, %2, %3;" : "=f"(r) : "f"(a), "f"(b), "f"(c));
    return r;
}
__device__ __forceinline__ float tanh_fast(float x) {
    float r;
    asm volatile("tanh.approx.f32 %0, %1;" : "=f"(r) : "f"(x));
    return r;
}
__device__ __forceinline__ float gelu_tanh(float x) {
    float r;
    asm volatile(
        "{.reg .f32 a; mul.f32 a, %1, %1; fma.rn.f32 a, a, 0f3D122279, 0f3F4C422A; mul.f32 a, a, %1; tanh.approx.f32 %0, a;}"
        : "=f"(r)
        : "f"(x));
    return r;
}
__device__ __forceinline__ void mma16816(float (&d)[4], const uint32_t (&a)[4], uint32_t b0, uint32_t b1) {
    asm volatile("mma.sync.aligned.m16n8k16.row.col.f32.bf16.bf16.f32 {%0,%1,%2,%3}, {%4,%5,%6,%7}, {%8,%9}, {%0,%1,%2,%3};"
                 : "+f"(d[0]), "+f"(d[1]), "+f"(d[2]), "+f"(d[3])
                 : "r"(a[0]), "r"(a[1]), "r"(a[2]), "r"(a[3]), "r"(b0), "r"(b1));
}
__device__ __forceinline__ uint32_t clock32() {
    uint32_t c;
    asm volatile("mov.u32 %0, %%clock;" : "=r"(c)::"memory");
    return c;
}
#define WG_FENCE() asm volatile("wgmma.fence.sync.aligned;" ::: "memory")
#define WG_COMMIT() asm volatile("wgmma.commit_group.sync.aligned;" ::: "memory")
#define WG_WAIT0() asm volatile("wgmma.wait_group.sync.aligned 0;" ::: "memory")
#define WG_WAIT1() asm volatile("wgmma.wait_group.sync.aligned 1;" ::: "memory")
#define CP_COMMIT() asm volatile("cp.async.commit_group;" ::: "memory")
#define CP_WAIT(n) asm volatile("cp.async.wait_group %0;" ::"n"(n) : "memory")
#define SCHED_FENCE() asm volatile("pmevent 0;" ::: "memory")
#define PROXY_FENCE() asm volatile("fence.proxy.async.shared::cta;" ::: "memory")
template <int N>
__device__ __forceinline__ void pin(float (&d)[N]) {
#pragma unroll
    for (int i = 0; i < N; i++) asm volatile("" : "+f"(d[i])::"memory");
}
#define TS(k)
#define TS_DUMP(role)

__device__ __forceinline__ void wgmma_ss_n168_acc(float (&d)[84], uint64_t da, uint64_t db) {
    asm volatile(
        "wgmma.mma_async.sync.aligned.m64n168k16.f32.bf16.bf16 "
        "{%0,%1,%2,%3,%4,%5,%6,%7,%8,%9,%10,%11,%12,%13,%14,%15,"
        "%16,%17,%18,%19,%20,%21,%22,%23,%24,%25,%26,%27,%28,%29,%30,%31,"
        "%32,%33,%34,%35,%36,%37,%38,%39,%40,%41,%42,%43,%44,%45,%46,%47,"
        "%48,%49,%50,%51,%52,%53,%54,%55,%56,%57,%58,%59,%60,%61,%62,%63,"
        "%64,%65,%66,%67,%68,%69,%70,%71,%72,%73,%74,%75,%76,%77,%78,%79,"
        "%80,%81,%82,%83}, "
        "%84, %85, 1, 1, 1, 0, 1;"
        : "+f"(d[0]), "+f"(d[1]), "+f"(d[2]), "+f"(d[3]), "+f"(d[4]), "+f"(d[5]), "+f"(d[6]), "+f"(d[7]),
          "+f"(d[8]), "+f"(d[9]), "+f"(d[10]), "+f"(d[11]), "+f"(d[12]), "+f"(d[13]), "+f"(d[14]), "+f"(d[15]),
          "+f"(d[16]), "+f"(d[17]), "+f"(d[18]), "+f"(d[19]), "+f"(d[20]), "+f"(d[21]), "+f"(d[22]), "+f"(d[23]),
          "+f"(d[24]), "+f"(d[25]), "+f"(d[26]), "+f"(d[27]), "+f"(d[28]), "+f"(d[29]), "+f"(d[30]), "+f"(d[31]),
          "+f"(d[32]), "+f"(d[33]), "+f"(d[34]), "+f"(d[35]), "+f"(d[36]), "+f"(d[37]), "+f"(d[38]), "+f"(d[39]),
          "+f"(d[40]), "+f"(d[41]), "+f"(d[42]), "+f"(d[43]), "+f"(d[44]), "+f"(d[45]), "+f"(d[46]), "+f"(d[47]),
          "+f"(d[48]), "+f"(d[49]), "+f"(d[50]), "+f"(d[51]), "+f"(d[52]), "+f"(d[53]), "+f"(d[54]), "+f"(d[55]),
          "+f"(d[56]), "+f"(d[57]), "+f"(d[58]), "+f"(d[59]), "+f"(d[60]), "+f"(d[61]), "+f"(d[62]), "+f"(d[63]),
          "+f"(d[64]), "+f"(d[65]), "+f"(d[66]), "+f"(d[67]), "+f"(d[68]), "+f"(d[69]), "+f"(d[70]), "+f"(d[71]),
          "+f"(d[72]), "+f"(d[73]), "+f"(d[74]), "+f"(d[75]), "+f"(d[76]), "+f"(d[77]), "+f"(d[78]), "+f"(d[79]),
          "+f"(d[80]), "+f"(d[81]), "+f"(d[82]), "+f"(d[83])
        : "l"(da), "l"(db));
}

__device__ __forceinline__ void wgmma_rs_n32_set(float (&d)[16], const uint32_t (&a)[4], uint64_t db) {
    asm volatile(
        "wgmma.mma_async.sync.aligned.m64n32k16.f32.bf16.bf16 "
        "{%0,%1,%2,%3,%4,%5,%6,%7,%8,%9,%10,%11,%12,%13,%14,%15}, "
        "{%16,%17,%18,%19}, %20, 0, 1, 1, 0;"
        : "=f"(d[0]), "=f"(d[1]), "=f"(d[2]), "=f"(d[3]), "=f"(d[4]), "=f"(d[5]), "=f"(d[6]), "=f"(d[7]),
          "=f"(d[8]), "=f"(d[9]), "=f"(d[10]), "=f"(d[11]), "=f"(d[12]), "=f"(d[13]), "=f"(d[14]), "=f"(d[15])
        : "r"(a[0]), "r"(a[1]), "r"(a[2]), "r"(a[3]), "l"(db));
}

__device__ __forceinline__ void wgmma_rs_n32_acc(float (&d)[16], const uint32_t (&a)[4], uint64_t db) {
    asm volatile(
        "wgmma.mma_async.sync.aligned.m64n32k16.f32.bf16.bf16 "
        "{%0,%1,%2,%3,%4,%5,%6,%7,%8,%9,%10,%11,%12,%13,%14,%15}, "
        "{%16,%17,%18,%19}, %20, 1, 1, 1, 0;"
        : "+f"(d[0]), "+f"(d[1]), "+f"(d[2]), "+f"(d[3]), "+f"(d[4]), "+f"(d[5]), "+f"(d[6]), "+f"(d[7]),
          "+f"(d[8]), "+f"(d[9]), "+f"(d[10]), "+f"(d[11]), "+f"(d[12]), "+f"(d[13]), "+f"(d[14]), "+f"(d[15])
        : "r"(a[0]), "r"(a[1]), "r"(a[2]), "r"(a[3]), "l"(db));
}

__device__ __forceinline__ void wgmma_rs_n16_set(float (&d)[8], const uint32_t (&a)[4], uint64_t db) {
    asm volatile(
        "wgmma.mma_async.sync.aligned.m64n16k16.f32.bf16.bf16 "
        "{%0,%1,%2,%3,%4,%5,%6,%7}, "
        "{%8,%9,%10,%11}, %12, 0, 1, 1, 0;"
        : "=f"(d[0]), "=f"(d[1]), "=f"(d[2]), "=f"(d[3]), "=f"(d[4]), "=f"(d[5]), "=f"(d[6]), "=f"(d[7])
        : "r"(a[0]), "r"(a[1]), "r"(a[2]), "r"(a[3]), "l"(db));
}

__device__ __forceinline__ void wgmma_rs_n32_pred(float (&d)[16], const uint32_t (&a)[4], uint64_t db, uint32_t scale_d) {
    asm volatile(
        "{.reg .pred p; setp.ne.u32 p, %21, 0; wgmma.mma_async.sync.aligned.m64n32k16.f32.bf16.bf16 "
        "{%0,%1,%2,%3,%4,%5,%6,%7,%8,%9,%10,%11,%12,%13,%14,%15}, "
        "{%16,%17,%18,%19}, %20, p, 1, 1, 0;}"
        : "+f"(d[0]), "+f"(d[1]), "+f"(d[2]), "+f"(d[3]), "+f"(d[4]), "+f"(d[5]), "+f"(d[6]), "+f"(d[7]),
          "+f"(d[8]), "+f"(d[9]), "+f"(d[10]), "+f"(d[11]), "+f"(d[12]), "+f"(d[13]), "+f"(d[14]), "+f"(d[15])
        : "r"(a[0]), "r"(a[1]), "r"(a[2]), "r"(a[3]), "l"(db), "r"(scale_d));
}

__device__ __forceinline__ void prep_cta(uint32_t sb, int c, const __nv_bfloat16* __restrict__ wc,
                                         const __nv_bfloat16* __restrict__ se1, const __nv_bfloat16* __restrict__ se2,
                                         const __nv_bfloat16* __restrict__ w2) {
    const int tid = threadIdx.x, lane = tid & 31, warp = tid >> 5, s = c >> 1;
    constexpr int ZERO = 16 * NF * 128;
#pragma unroll
    for (int q = tid; q < 16 * NF * 8; q += 384) {
        const int i = q >> 7, nn = (q >> 3) & 15, j = fmap((16 * (c & 1) + nn) ^ s);
        cp16(sb + (q >> 3) * 128 + (((q & 7) ^ (i & 1) ^ ((i >> 3) << 1)) << 4), wc + ((s * NF + i) * NF + j) * ND + (q & 7) * 8);
    }
    if (tid < 8) sts128(sb + ZERO + tid * 16, 0, 0, 0, 0);
    if (tid < 256) {
        const int n = ((tid >> 2) & 1) * 8 + (tid >> 5) + (s ? (c & 1) * 16 : 0);
        const int k = ((tid >> 1) & 1) * 8 + ((tid >> 3) & 3) * 2 + (tid & 1), mm = k >> 1, u = k & 1;
        const int f = s ? fmap(n) : mm < 6 ? 4 * mm + 2 * c + u : (mm == 6 && u == 0) ? 24 + c : -1;
        float v = 0.f;
        if (f >= 0 && (s ? k : n) < NR) v = __bfloat162float(s ? se2[k * NF + f] : se1[f * NR + n]);
        reinterpret_cast<__nv_bfloat16*>(g_se)[c * 256 + tid] = __float2bfloat16(s ? 0.5f * v : v);
    } else if (tid < 320) {
        const int q = tid - 256;
        reinterpret_cast<__nv_bfloat16*>(g_w2)[c * 64 + q] =
            __float2bfloat16(0.5f * __bfloat162float(w2[c * 64 + (q & 32) + 4 * (q & 6) + ((q >> 2) & 6) + (q & 1)]));
    }
    asm volatile("cp.async.wait_all;" ::: "memory");
    __syncthreads();
    const int k = 4 * (lane & 6) + 2 * (lane >> 3) + (lane & 1), i = fmap(k);
    const int g = lane >> 2, t = lane & 3;
#pragma unroll 4
    for (int task = warp; task < 128; task += 12) {
        const int nn = task & 15, eg = task >> 4, n = 16 * (c & 1) + nn;
        const uint32_t a = sb + (k < 28 ? (i * 16 + nn) * 128 : ZERO) + ((eg ^ (i & 1) ^ ((i >> 3) << 1)) << 4);
        uint4 v;
        asm volatile("ldmatrix.sync.aligned.m8n8.x4.trans.shared.b16 {%0,%1,%2,%3}, [%4];"
                     : "=r"(v.x), "=r"(v.y), "=r"(v.z), "=r"(v.w)
                     : "r"(a));
        if (t == 3) {
            const uint32_t mask = (eg & 1) ? 0xffff0000u : 0xffffu;
            v.x &= mask;
            v.y &= mask;
        }
        const int ch = (t < 2 ? t ^ ((g >> 1) & 1) : t) ^ ((n >> 1) & 3);
        const int step = (g & 1) + 2 * (eg & 1) + 2 * (g & 6);
        g_wc[(eg >> 2) * 8192 + step * 512 + ((eg >> 1) & 1) * 256 + s * 128 + n * 4 + ch] = v;
    }
    __threadfence();
    __syncthreads();
    if (tid == 0) atomicAdd(&g_ready, 1u);
}

#define PACE1 2250
#define PACE2 2850
#define START_MIN 3400
#define WDELAY 1600
#define WSTEP 500
#define WPF_AT 2600
#define WPF_STEP 800
#define POLL_AT 6500
#define T_SHIFT 300
constexpr int DB0 = 6;

__global__ void __cluster_dims__(2, 1, 1) __launch_bounds__(384, 1)
fibinet_kernel(const int* __restrict__ idx, const uint4* __restrict__ table,
               const __nv_bfloat16* __restrict__ se1, const __nv_bfloat16* __restrict__ se2,
               const __nv_bfloat16* __restrict__ wc,
               const unsigned char* __restrict__ w1, const __nv_bfloat16* __restrict__ w2, __nv_bfloat16* __restrict__ out,
               const __grid_constant__ CUtensorMap tm_w1, const __grid_constant__ CUtensorMap tm_bi) {
    extern __shared__ __align__(1024) unsigned char smem[];
    const int tid = threadIdx.x;
    const int cta = blockIdx.x - NPREP, grp = cta >> 1, rank = cta & 1, lane = tid & 31;
    uint32_t ids[13][4], cid[3][2];
    const uint32_t idle = (tid >> 8) | (cta < 0);
    const uint32_t row = ((tid >> 5) & 3) * 16 + (lane >> 3);
    const unsigned char* ib = reinterpret_cast<const unsigned char*>(idx) + (int64_t)grp * (64 * NF * 4);
    {
        const unsigned char* ip = ib + (row * (NF * 4) + ((tid >> 4) & 8));
#pragma unroll
        for (int u = 0; u < 4; u++) {
            ids[0][u] = ids[1][u] = 0;
            asm volatile("{.reg .pred p; setp.eq.u32 p, %3, 0; @p ld.global.nc.L2::128B.v2.u32 {%0,%1}, [%2];}"
                         : "+r"(ids[0][u]), "+r"(ids[1][u])
                         : "l"(ip + 16 * NF * u), "r"(idle));
        }
    }
    const uint32_t t_0 = clock32();
    {
        const uint32_t co = ((tid & 127) >> 1) * (NF * 4) + ((tid >> 4) & 8) + 16 + 16 * (tid & 1);
#pragma unroll
        for (int k = 0; k < 3; k++) {
            cid[k][0] = cid[k][1] = 0;
            asm volatile("{.reg .pred p; setp.eq.u32 p, %3, 0; @p ld.global.nc.v2.u32 {%0,%1}, [%2];}"
                         : "+r"(cid[k][0]), "+r"(cid[k][1])
                         : "l"(ib + (co + 32 * k - (k == 2 ? 8 * ((tid >> 7) & tid & 1) : 0))), "r"(idle));
        }
    }
    const uint32_t t_start = (t_0 ^ (clock32() & blockIdx.y)) - T_SHIFT;
    const uint32_t sb = (uint32_t)__cvta_generic_to_shared(smem);
    uint32_t gd0 = sb + (tid >> 7) * XDELTA + row * 128 + (((lane & 7) ^ (lane >> 3) ^ ((tid >> 5) & 4)) << 4);
    const uint4* tp = table + (lane & 7);
    auto gather = [&](int i) {
#pragma unroll
        for (int u = 0; u < 4; u++)
            asm volatile(
                "{.reg .u64 a; .reg .pred p; setp.eq.u32 p, %3, 0; mad.wide.u32 a, %2, 128, %1; @p cp.async.cg.shared.global [%0], [a], 16;}" ::"r"(
                    (gd0 ^ ((u & 1) * 64)) + xpair(i) + u * 512),
                "l"(tp), "r"(ids[i][u]), "r"(i == 0 ? idle : 0u)
                : "memory");
        CP_COMMIT();
    };
    gather(0);
    if (cta < 0) {
        prep_cta(sb, blockIdx.x, wc, se1, se2, w2);
        return;
    }
    if (tid == 288) asm volatile("prefetch.tensormap [%0];" ::"l"(&tm_w1));
    const int warp = __reduce_max_sync(0xffffffffu, tid >> 5);
    const int w = warp >> 2;

    if (w == 2) {
        asm volatile("setmaxnreg.dec.sync.aligned.u32 40;");
        auto load_wc = [&](int gi) {
            if (elect()) {
                const unsigned char* src = reinterpret_cast<const unsigned char*>(g_wc) + rank * 131072;
                mbar_expect(sb + BAR_WC + gi * 8, (wcfirst(gi + 1) - wcfirst(gi)) * 8192);
#pragma unroll
                for (int c = wcfirst(gi); c < wcfirst(gi + 1); c++) bulk(sb + wcslot(c), src + c * 8192, 8192, sb + BAR_WC + gi * 8);
            }
            __syncwarp();
        };
        if (warp == 8) {
            if (elect()) {
                mbar_init(sb + BAR_Z, 1);
                mbar_expect(sb + BAR_Z, 8192);
                tma2d(sb + ZOFF, &tm_bi, sb + BAR_Z, 32 * rank, 0);
            }
#pragma unroll
            for (int f = 0; f < 26; f++) {
                if (f == 2) {
                    if (elect()) {
#pragma unroll
                        for (int k = 2; k < 8; k++) mbar_init(sb + BAR_FULL + k * 8, 1);
                        asm volatile("fence.mbarrier_init.release.cluster;" ::: "memory");
                    }
                    __syncwarp();
                    asm volatile("barrier.cluster.arrive.relaxed.aligned;" ::: "memory");
                    mbar_wait(sb + BAR_Z);
#pragma unroll
                    for (int k = 0; k < 2; k++)
                        sts128(sb + ZOFF + (k * 32 + lane) * 128 + ((4 ^ (lane & 7)) << 4), 0x3c803c80u, 0x3c803c80u, 0x3c803c80u, 0x3c803c80u);
                    PROXY_FENCE();
                    asm volatile("bar.arrive 0, 384;" ::: "memory");
                    TS(31);
                }
                if (f == 5) asm volatile("bar.sync 7, 64;" ::: "memory");
                if (f >= 5) mbar_wait(sb + bdone(f - 5), bpar(f - 5));
                if (f >= 2 && f < 5)
                    while (clock32() - t_start < WDELAY + (f - 2) * WSTEP) {
                    }
                if (elect()) {
                    if (f < 2) mbar_init(sb + BAR_FULL + f * 8, 1);
                    mbar_expect(sb + bfull(f), 16384);
                    tma2d(sb + slot(2 * wl(f)), &tm_w1, sb + bfull(f), 128 * rank + 64 * (f & 1), fieldof(f) * 64);
                    tma2d(sb + slot(wl(f)), &tm_w1, sb + bfull(f), 128 * rank + 64 - 64 * (f & 1), fieldof(f) * 64);
                }
                TS(f);
            }
            asm volatile("bar.arrive 8, 128;" ::: "memory");
            TS_DUMP(2);
        } else if (warp == 9) {
            if (elect()) {
#pragma unroll
                for (int k = 0; k < 8; k++) mbar_init(sb + BAR_WC + k * 8, k < 7 ? 1 : 8);
                asm volatile("fence.mbarrier_init.release.cluster;" ::: "memory");
            }
            __syncwarp();
            asm volatile("barrier.cluster.arrive.relaxed.aligned;" ::: "memory");
            asm volatile("bar.sync 0, 384;" ::: "memory");
            while (clock32() - t_start < POLL_AT) __nanosleep(100);
            if (elect()) {
                unsigned v, it = 0;
                do {
                    asm volatile("ld.acquire.gpu.global.u32 %0, [%1];" : "=r"(v) : "l"(&g_ready) : "memory");
                } while (v < NPREP && ++it < 4000000u);
                asm volatile("fence.proxy.async.global;" ::: "memory");
                mbar_expect(sb + BAR_SE, 2048 + 256);
                bulk(sb + SEOFF, g_se, 2048, sb + BAR_SE);
                bulk(sb + W2OFF, g_w2 + rank * 16, 256, sb + BAR_SE);
            }
            __syncwarp();
            TS(0);
            asm volatile("bar.sync 8, 128;" ::: "memory");
#pragma unroll
            for (int gi = 0; gi < 3; gi++) {
                mbar_wait(sb + bdone(21 + gi), bpar(21 + gi));
                load_wc(gi);
                TS(1 + gi);
            }
        } else if (warp == 10) {
            if (elect()) {
#pragma unroll
                for (int k = 0; k < 8; k++) mbar_init(sb + BAR_DONE + k * 8, 4);
                asm volatile("fence.mbarrier_init.release.cluster;" ::: "memory");
            }
            __syncwarp();
            asm volatile("barrier.cluster.arrive.relaxed.aligned;" ::: "memory");
            asm volatile("bar.arrive 7, 64;" ::: "memory");
            asm volatile("bar.sync 0, 384;" ::: "memory");
#pragma unroll 1
            for (int k = 0; k < 7; k++) {
                while (clock32() - t_start < (uint32_t)(WPF_AT + k * WPF_STEP)) __nanosleep(150);
                if (lane < 6)
                    asm volatile("prefetch.global.L2 [%0];" ::"l"(w1 + (5 + k * 3 + (lane >> 1)) * 32768 + cta * 256 + (lane & 1) * 128));
            }
            asm volatile("bar.sync 8, 128;" ::: "memory");
        } else {
            asm volatile("bar.sync 0, 384;" ::: "memory");
            asm volatile("bar.sync 8, 128;" ::: "memory");
        }
        {
            uint32_t bw[2][4], z0[4], z1[4];
            mbar_wait(sb + BAR_SE);
            lds128(bw[0], sb + SEOFF + lane * 16);
            lds128(bw[1], sb + SEOFF + 512 + lane * 16);
            asm volatile("bar.sync 2, 384;" ::: "memory");
            lds128(z0, sb + ZQOFF + (tid & 127) * 16);
            lds128(z1, sb + ZQOFF + 2048 + (tid & 127) * 16);
            TS(8);
            float s[2][4] = {};
#pragma unroll
            for (int n = 0; n < 2; n++) {
                mma16816(s[n], z0, bw[0][2 * n], bw[0][2 * n + 1]);
                mma16816(s[n], z1, bw[1][2 * n], bw[1][2 * n + 1]);
            }
            lds128(bw[0], sb + SEOFF + 1024 + lane * 16);
            lds128(bw[1], sb + SEOFF + 1536 + lane * 16);
            float th[8];
#pragma unroll
            for (int k = 0; k < 8; k++) th[k] = gelu_tanh(s[k >> 2][k & 3]);
            SCHED_FENCE();
            TS(9);
            uint32_t gq[4];
#pragma unroll
            for (int k = 0; k < 4; k++)
                gq[k] = pack(s[k >> 1][2 * (k & 1)] * ffma(th[2 * k], 0.5f, 0.5f), s[k >> 1][2 * (k & 1) + 1] * ffma(th[2 * k + 1], 0.5f, 0.5f));
            float a[4][4] = {};
#pragma unroll
            for (int n = 0; n < 4; n++) mma16816(a[n], gq, bw[n >> 1][2 * (n & 1)], bw[n >> 1][2 * (n & 1) + 1]);
#pragma unroll
            for (int k = 0; k < 16; k++)
                if (k < 13 || k == 14) a[k >> 2][k & 3] = tanh_fast(a[k >> 2][k & 3]);
            SCHED_FENCE();
            TS(10);
            uint32_t ap[8];
#pragma unroll
            for (int k = 0; k < 8; k++)
                ap[k] = pack(ffma(a[k >> 1][2 * (k & 1)], 0.5f, 0.5f), ffma(a[k >> 1][2 * (k & 1) + (k < 6)], 0.5f, 0.5f));
            sts128(sb + GOFF + (tid & 127) * 16, ap[0], ap[1], ap[2], ap[3]);
            sts128(sb + GOFF + 2048 + (tid & 127) * 16, ap[4], ap[5], ap[6], ap[7]);
            asm volatile("bar.arrive 3, 384;" ::: "memory");
            TS(11);
        }
        if (warp == 9) {
            load_wc(3);
            load_wc(4);
            mbar_wait(sb + BAR_TD);
            load_wc(5);
            if (lane == 0 && atomicAdd(&g_seen, 1u) == NMAIN - 1) {
                g_seen = 0;
                g_ready = 0;
            }
            if (lane < 16) TS_DUMP(3);
        } else if (warp == 11) {
            if (lane < 16) reinterpret_cast<uint32_t*>(out)[cta * 16 + lane] = 0;
            asm volatile("barrier.cluster.arrive.release.aligned;" ::: "memory");
        } else if (warp == 10) {
            uint32_t* dst = reinterpret_cast<uint32_t*>(out) + grp * 32 + lane;
            asm volatile("barrier.cluster.wait.acquire.aligned;" : "+l"(dst)::"memory");
            SCHED_FENCE();
            asm volatile("bar.sync 4, 288;" ::: "memory");
            uint32_t p[4];
            lds64(p[0], p[1], sb + PARTOFF + lane * 8);
            lds64(p[2], p[3], sb + PARTOFF + 256 + lane * 8);
            asm volatile("red.relaxed.gpu.global.add.noftz.bf16x2 [%0], %1;" ::"l"(dst),
                         "r"(pack(__uint_as_float(p[0]) + __uint_as_float(p[2]), __uint_as_float(p[1]) + __uint_as_float(p[3])))
                         : "memory");
        }
    } else {
        asm volatile("setmaxnreg.inc.sync.aligned.u32 232;");
        asm volatile("barrier.cluster.arrive.relaxed.aligned;" ::: "memory");
        const uint32_t sb = __reduce_max_sync(0xffffffffu, (uint32_t)__cvta_generic_to_shared(smem) | (tid >> 10));
        const int t128 = opaque(tid & 127), lane = t128 & 31;
        const int g = lane >> 2, t = lane & 3, wq = warp & 3;
        gd0 = opaque(gd0);
        TS(28);
        float acc[84];
#pragma unroll
        for (int k = 0; k < 84; k++) asm volatile("mov.b32 %0, 0;" : "=f"(acc[k]));
        uint32_t e0[9], e1[9], e2[9];
        uint32_t X[13][2][4];
        uint32_t zq[4] = {0, 0, 0, 0};
        const uint64_t dA = mkdesc(sb + w * XDELTA, 16, 1024, 1);
        uint32_t dBlo = (uint32_t)mkdesc(sb + ZOFF, 0, 0, 0);
        const uint32_t xl0 = opaque(sb + (t & 1) * XDELTA + (16 * wq + g) * 128 + (((4 * rank + 2 * w) ^ (4 * (t & 1)) ^ g) << 4));
        const uint32_t hi_half = t >> 1;
        const uint32_t sa0 = opaque(sb + AOFF + t * 4096 + (t >> 1) * 16 + (wq * 32 + g * 4 + w) * 16);
        const uint32_t sa1 = opaque(((g & 2) << 4) | ((t & 1) << 3));
        const uint32_t zero = __reduce_max_sync(0xffffffffu, blockIdx.y | (tid >> 10));
        auto expand = [&](int k0, int k1) {
#pragma unroll
            for (int k = k0; k < k1; k++)
#pragma unroll
                for (int u = 0; u < 4; u++)
                    asm volatile("shfl.sync.idx.b32 %0, %1, %2, 31, 0xffffffff;"
                                 : "=r"(ids[k][u])
                                 : "r"(k < 12 ? cid[(k - 2) >> 2][k & 1] : w ? cid[2][1] : cid[2][0]),
                                   "r"(2 * (lane >> 3) + 8 * u + (((k - 2) >> 1) & 1)));
        };
        auto twarm = [&]() {
            float s1[8];
            WG_FENCE();
            wgmma_rs_n16_set(s1, zq, mkdesc(sb + AOFF, 16, 512, 2));
            WG_COMMIT();
            WG_WAIT0();
            pin(s1);
            asm volatile("{.reg .pred p; setp.ne.u32 p, %1, 0; @p st.shared.f32 [%1], %0;}" ::"f"(s1[0]), "r"(zero));
        };
        expand(2, 8);
        twarm();
        TS(26);
        while (clock32() - t_start < PACE1) {
        }
        gather(1);
        expand(8, 13);
        twarm();
        TS(30);
        while (clock32() - t_start < PACE2) {
        }
        gather(2);
        twarm();
        asm volatile("bar.sync 0, 384;" ::: "memory");
        auto lift = [&](int i) {
            const int m = 2 * (i >> 2) + (i & 1);
#pragma unroll
            for (int r = 0; r < 2; r++)
#pragma unroll
                for (int cc = 0; cc < 2; cc++) {
                    const uint32_t a = (xl0 ^ (cc * 16)) + xpair(i) + r * 1024;
                    if (i == 12 ? r : (i & 2)) lds128_if(X[i == 12 ? 12 : 2 * m + r][cc], a, hi_half);
                    else lds128(X[2 * m + r][cc], a);
                }
        };
        auto store_pair = [&](int m, int half, const uint32_t (&ea)[9]) {
            uint32_t a;
            if (m < 4) a = sa0 + (sa1 ^ (((m & 1) << 5) | ((m >> 1) << 3)));
            else a = sb + BOFF + t * 2048 + (wq * 32 + g * 4 + ((2 * (m & 1) + w) ^ t)) * 8;
#pragma unroll
            for (int n = half; n < 4; n += 2)
#pragma unroll
                for (int u = 0; u < 2; u++)
                    sts64(a + (m < 4 ? (8 * n + u) * 2048 + n * 32 : (8 * n + u) * 1024),
                          __byte_perm(ea[2 * n], e1[2 * n], u ? 0x7632 : 0x5410),
                          __byte_perm(ea[2 * n + 1], e1[2 * n + 1], u ? 0x7632 : 0x5410));
        };
        auto z_pair = [&](int m, uint32_t a, uint32_t b) {
            asm volatile("{.reg .pred p; setp.eq.u32 p, %4, %5; @p prmt.b32 %0, %2, %3, 0x5410; @p prmt.b32 %1, %2, %3, 0x7632;}"
                         : "+r"(zq[2 * (m >> 2)]), "+r"(zq[2 * (m >> 2) + 1])
                         : "r"(a), "r"(b), "r"(t), "r"(m & 3));
        };

        TS(29);
        mbar_wait(sb + BAR_FULL + w * 8);
        CP_WAIT(2);
        while (clock32() - t_start < START_MIN) {
        }
        if (w == 1) {
            asm volatile("bar.arrive 6, 256;" ::: "memory");
            asm volatile("bar.sync 5, 256;" ::: "memory");
        }
#pragma unroll
        for (int i = 0; i < 13; i++) {
            const uint64_t da = dA + (xpair(i) >> 4) + ((uint64_t)i << 16);
            dBlo += (uint32_t)(w ? wl(2 * i + 1) - (i ? wl(2 * i - 1) : 0) : wl(2 * i) - (i ? wl(2 * i - 2) : 0)) *
                    (uint32_t)((SLOT << 12) - (SLOT >> 3));
            const uint64_t db = mkdesc(0, 0, 1024, 1) | dBlo;
            TS(i);
            WG_FENCE();
            wgmma_ss_n168_acc(acc, da, db + w * 256);
            wgmma_ss_n168_acc(acc, da + 2, db + w * 256 + 128);
            wgmma_ss_n168_acc(acc, da + 4, db + (w ^ 1) * 256);
            wgmma_ss_n168_acc(acc, da + 6, db + (w ^ 1) * 256 + 128);
            WG_COMMIT();
            if (i == 0) {
                if (w == 0) {
                    asm volatile("bar.arrive 5, 256;" ::: "memory");
                    asm volatile("bar.sync 6, 256;" ::: "memory");
                }
            } else {
                mbar_wait(sb + bdone(2 * i - 2) + (w ^ 1) * 8, bpar(2 * i - 2));
            }
            if (i < 10) gather(i + 3);
            if (i == 12) mbar_wait(sb + BAR_SE);
            lift(i);
            if (i == 10 || i == 11) mbar_wait(sb + bdone(2 * i - 2) + w * 8, bpar(2 * i - 2));
            if (i >= 2 && !(i & 1)) {
                z_pair((i - 2) >> 1, e0[8], e1[8]);
                store_pair((i - 2) >> 1, 0, e0);
#pragma unroll
                for (int k = 0; k < 8; k++) e2[k] = e0[k];
            } else if (i >= 3) {
                store_pair((i - 3) >> 1, 1, e2);
            }
            const uint32_t rdy = i < 12 ? mbar_test(sb + bfull(2 * i + 2) + w * 8, bpar(2 * i + 2)) : 0;
            WG_WAIT0();
            pin(acc);
            if (i == 12) TS(13);
            if (i == 0) TS(27);
            if (i < 10) CP_WAIT(2);
            else if (i == 10) CP_WAIT(1);
            else if (i == 11) CP_WAIT(0);
            if (i < 12 && lane == 0) mbar_arrive(sb + bdone(2 * i) + w * 8);
#pragma unroll
            for (int k = 0; k < 9; k++) {
                const int k0 = 64 + 2 * (k & 5) + ((k >> 1) & 1);
                const uint32_t v = k == 8 ? pack(acc[80], acc[82]) : i < 12 ? pack(acc[64 + 2 * k], acc[65 + 2 * k]) : pack(acc[k0], acc[k0 + 4]);
                if (i & 1) e1[k] = v;
                else e0[k] = v;
            }
            if (i < 12) {
#pragma unroll
                for (int k = 64; k < 83; k++)
                    if (k != 81) asm volatile("mov.b32 %0, %1;" : "+f"(acc[k]) : "r"(zero));
                mbar_wait_unless(rdy, sb + bfull(2 * i + 2) + w * 8, bpar(2 * i + 2));
            } else {
                z_pair(6, e0[8], 0);
                sts128(sb + ZQOFF + w * 2048 + t128 * 16, zq[0], zq[1], zq[2], zq[3]);
                asm volatile("bar.arrive 2, 384;" ::: "memory");
            }
        }
        TS(14);

        uint32_t ai[8];
        float rd[4] = {0.f, 0.f, 0.f, 0.f};
        float th[32];
        uint32_t hw[2][4];
        auto deep_issue = [&](int k2) {
            if (!(k2 & 1)) lds128(hw[k2 >> 1], sb + W2OFF + w * 128 + t * 16 + k2 * 32);
#pragma unroll
            for (int k = 8 * k2; k < 8 * k2 + 8; k++) th[k] = gelu_tanh(acc[k]);
        };
        uint32_t h[4];
        auto deep_use = [&](int k2) {
#pragma unroll
            for (int c = 0; c < 4; c++) {
                const int k = 8 * k2 + 2 * c;
                h[c] = pack(ffma(acc[k], th[k], acc[k]), ffma(acc[k + 1], th[k + 1], acc[k + 1]));
            }
            if (k2 < 3) mma16816(rd, h, hw[k2 >> 1][2 * (k2 & 1)], hw[k2 >> 1][2 * (k2 & 1) + 1]);
        };
        auto deep_send = [&](int k0, int k1) {
#pragma unroll
            for (int k = k0; k < k1; k++)
                sts128(sb + EXOFF + w * SLOT + t128 * 16 + k * 2048, pack(acc[32 + 8 * k], acc[33 + 8 * k]),
                       pack(acc[34 + 8 * k], acc[35 + 8 * k]), pack(acc[36 + 8 * k], acc[37 + 8 * k]), pack(acc[38 + 8 * k], acc[39 + 8 * k]));
        };
        uint32_t o[4][4];
        auto deep_recv = [&](int k0, int k1) {
#pragma unroll
            for (int k = k0; k < k1; k++) lds128(o[k], sb + EXOFF + (w ^ 1) * SLOT + t128 * 16 + k * 2048);
        };
        auto deep_add = [&](int k0, int k1) {
            const uint32_t eye = (g >> 1) == t ? ((g & 1) ? 0x3f800000u : 0x3f80u) : 0u;
#pragma unroll
            for (int k = 2 * k0; k < 2 * k1; k++)
                asm volatile("mma.sync.aligned.m16n8k8.row.col.f32.bf16.bf16.f32 {%0,%1,%2,%3}, {%4,%5}, {%6}, {%0,%1,%2,%3};"
                             : "+f"(acc[4 * k]), "+f"(acc[4 * k + 1]), "+f"(acc[4 * k + 2]), "+f"(acc[4 * k + 3])
                             : "r"(o[k >> 1][2 * (k & 1)]), "r"(o[k >> 1][2 * (k & 1) + 1]), "r"(eye));
        };
        auto store_last = [&]() {
#pragma unroll
            for (int n = 0; n < 4; n++) sts64(sb + COFF + w * 4096 + n * 1024 + (t128 ^ w) * 8, e0[2 * n], e0[2 * n + 1]);
            store_pair(5, 1, e2);
        };
        const uint32_t la = (sb + AOFF + w * (16 * 2048 + 64) + (wq * 32 + g * 4 + (t ^ (g & 2))) * 16);
        const uint32_t lb = (sb + BOFF + w * (16 * 1024) + t128 * 8);
        const uint32_t lc0 = (sb + COFF + (t & 1) * (4096 + 8) + w * 2048 + (wq * 8 + g) * 32), lc1 = lc0 ^ 8;
        uint32_t Ap[2][2][4];
        auto load_a = [&](int s) {
            const int e = estep(s);
            lds128(Ap[s & 1][0], la + e * 2048 + (e >> 2) * 16);
            lds64(Ap[s & 1][1][0], Ap[s & 1][1][1], (lb ^ ((e & 6) * 4)) + e * 1024);
            if (!(s & 2)) lds64(Ap[s & 1][1][2], Ap[s & 1][1][3], ((e & 2) ? lc1 : lc0) + (e & 1) * 1024 + (e & 4) * 4);
        };
        {
            uint32_t v[2][4];
            deep_send(0, 2);
            asm volatile("bar.sync 1, 256;" ::: "memory");
            deep_recv(0, 2);
            deep_send(2, 4);
            TS(15);
            deep_add(0, 2);
            deep_issue(0);
            asm volatile("bar.sync 1, 256;" ::: "memory");
            deep_recv(2, 4);
            SCHED_FENCE();
            deep_add(2, 4);
            TS(16);
            deep_issue(1);
            deep_use(0);
            store_last();
            SCHED_FENCE();
            TS(17);
            deep_issue(2);
            deep_use(1);
            mbar_wait(sb + BAR_WC);
            deep_use(2);
            TS(18);
            asm volatile("bar.sync 3, 384;" ::: "memory");
            lds128(v[0], sb + GOFF + t128 * 16);
            lds128(v[1], sb + GOFF + 2048 + t128 * 16);
            load_a(0);
            load_a(1);
            deep_issue(3);
#pragma unroll
            for (int k = 0; k < 8; k++) ai[k] = v[k >> 2][k & 3];
        }
        TS(19);

        uint32_t fin_a, tid2;
        float sum0, sum1;
        const uint32_t hi2 = lb & 16;
        {
            uint64_t dW[4];
#pragma unroll
            for (int k = 0; k < 4; k++) dW[k] = mkdesc(sb + w * 4096, 16, 512, 2) + ((uint64_t)zero << 32) + (wcslot(0) >> 4) + (k >> 1) * 128 + (k & 1) * 2;
            uint32_t Aq[2][2][4], pq[13], gate[13];
            float S[2][2][16];
            auto scale_a = [&](int s) {
#pragma unroll
                for (int k = 0; k < ((s & 2) ? 6 : 8); k++)
                    Aq[s & 1][k >> 2][k & 3] = hmul2(Ap[s & 1][k >> 2][k & 3], ai[k < 4 ? k ^ (estep(s) & 2) : k]);
            };
            auto sbuf = [](int s) { return s <= DB0 ? 0 : (s - DB0) & 1; };
            auto issue = [&](int s) {
                const bool first = s == 0 || s == DB0 + 1;
                WG_FENCE();
                if (first) wgmma_rs_n32_set(S[sbuf(s)][0], Ap[s & 1][0], dW[0]);
                else wgmma_rs_n32_pred(S[sbuf(s)][0], Ap[s & 1][0], dW[0], zero);
                wgmma_rs_n32_acc(S[sbuf(s)][0], Ap[s & 1][1], dW[1]);
                if (first) wgmma_rs_n32_set(S[sbuf(s)][1], Aq[s & 1][0], dW[2]);
                else wgmma_rs_n32_pred(S[sbuf(s)][1], Aq[s & 1][0], dW[2], zero);
                wgmma_rs_n32_acc(S[sbuf(s)][1], Aq[s & 1][1], dW[3]);
                WG_COMMIT();
                if (s < 15) {
#pragma unroll
                    for (int k = 0; k < 4; k++)
                        asm volatile("add.s64 %0, %0, %1;" : "+l"(dW[k]) : "l"((int64_t)((wcslot(s + 1) - wcslot(s)) / 16)));
                }
            };
            scale_a(0);
            issue(0);
            SCHED_FENCE();
            deep_use(3);
            scale_a(1);
            mbar_wait(sb + BAR_WC + 8);
#pragma unroll
            for (int e = 0; e < 16; e++) {
                if (e >= DB0 && e < 15) {
                    issue(e + 1);
                    WG_WAIT1();
                } else {
                    WG_WAIT0();
                }
                pin(S[sbuf(e)][0]);
                pin(S[sbuf(e)][1]);
                if (e == 0 && (lb & 0xf8) == 0) mbar_arrive(sb + BAR_TD);
                if (e == 0) TS(20);
                if (e + 2 < 16) load_a(e + 2);
#pragma unroll
                for (int q = 0; q < 13; q++) {
                    const int ix = 4 * (q >> 2) + 2 * (q & 1) + ((q >> 1) & 1);
                    uint32_t v = pack(S[sbuf(e)][0][ix], S[sbuf(e)][1][ix ^ 1]);
                    if (q == 12)
                        asm volatile("{.reg .pred p; setp.ne.u32 p, %3, 0; @p cvt.rn.bf16x2.f32 %0, %2, %1;}"
                                     : "+r"(v)
                                     : "f"(S[sbuf(e)][0][14]), "f"(S[sbuf(e)][1][15]), "r"(hi2));
                    const uint32_t x = X[q][(e >> 1) & 1][e >> 2];
                    pq[q] = (e & 1) ? hfma2_bcast<1>(v, x, pq[q]) : hfma2_bcast<0>(v, x, e ? pq[q] : 0u);
                }
                if (e < DB0) {
                    issue(e + 1);
                    SCHED_FENCE();
                }
                if (e == 13) {
                    asm volatile("mov.u32 %0, %%tid.x;" : "=r"(tid2));
                    fin_a = sb + PARTOFF + (tid2 >> 5) * 64 + (tid2 & 28);
                }
                if (e == 14) {
#pragma unroll
                    for (int q = 0; q < 13; q++)
                        asm volatile("prmt.b32 %0, %1, 0x3f80, %2;"
                                     : "=r"(gate[q])
                                     : "r"(q < 12 ? ai[2 * (q >> 2) + (q & 1)] : hi2 ? ai[7] : ai[6]), "r"((q & 2) ? 0x3254 : 0x1054));
                }
                if (e + 2 < 16) scale_a(e + 2);
                if (e == 0 || e == 3 || e == 6 || e == 9) mbar_wait(sb + BAR_WC + (e / 3 + 2) * 8);
                else if (e < 15) SCHED_FENCE();
                if (e == 7) TS(21);
            }
            float r0[4] = {0.f, 0.f, 0.f, 0.f}, r1[4] = {0.f, 0.f, 0.f, 0.f}, r2[4] = {rd[0], rd[0], rd[2], rd[2]};
            mma16816(r2, h, hw[1][2], hw[1][3]);
#pragma unroll
            for (int c = 0; c < 3; c++) {
                const uint32_t a[4] = {pq[4 * c], pq[4 * c + 1], pq[4 * c + 2], pq[4 * c + 3]};
                mma16816(r0, a, gate[4 * c], gate[4 * c + 2]);
                mma16816(r1, a, gate[4 * c + 1], gate[4 * c + 3]);
            }
            asm volatile("mma.sync.aligned.m16n8k8.row.col.f32.bf16.bf16.f32 {%0,%1,%2,%3}, {%4,%5}, {%6}, {%0,%1,%2,%3};"
                         : "+f"(r2[0]), "+f"(r2[1]), "+f"(r2[2]), "+f"(r2[3])
                         : "r"(hi2 ? 0u : pq[12]), "r"(hi2 ? pq[12] : 0u), "r"(gate[12]));
            sum0 = (tid2 & 4) ? r0[1] + r2[1] : r0[0] + r2[0];
            sum1 = (tid2 & 4) ? r1[3] + r2[3] : r1[2] + r2[2];
        }
        TS(22);
        {
            asm volatile("{.reg .pred p; setp.eq.u32 p, %3, %4; @p st.shared.f32 [%0], %1; @p st.shared.f32 [%0 + 32], %2;}" ::"r"(fin_a),
                         "f"(sum0), "f"(sum1), "r"(tid2 & 3), "r"((tid2 >> 3) & 3)
                         : "memory");
            asm volatile("bar.arrive 4, 288;" ::: "memory");
            if (wq == 0) TS_DUMP(w);
        }
    }
}

typedef CUresult (*EncodeFn)(CUtensorMap*, CUtensorMapDataType, cuuint32_t, void*, const cuuint64_t*, const cuuint64_t*,
                             const cuuint32_t*, const cuuint32_t*, CUtensorMapInterleave, CUtensorMapSwizzle,
                             CUtensorMapL2promotion, CUtensorMapFloatOOBfill);

}

extern "C" void kernel_launch(void* const* d_in, const int* in_sizes, int n_in, void* d_out, int out_size) {
    static EncodeFn encode = nullptr;
    if (!encode) {
        void* fn = nullptr;
        cudaDriverEntryPointQueryResult qr;
        cudaGetDriverEntryPoint("cuTensorMapEncodeTiled", &fn, cudaEnableDefault, &qr);
        encode = (EncodeFn)fn;
        cudaFuncSetAttribute(fibinet_kernel, cudaFuncAttributeMaxDynamicSharedMemorySize, SMEM_BYTES);
    }
    CUtensorMap tm;
    const cuuint64_t gd[2] = {NH, NF * ND};
    const cuuint64_t gs[1] = {NH * 2};
    const cuuint32_t bd[2] = {64, 64}, es[2] = {1, 1};
    encode(&tm, CU_TENSOR_MAP_DATA_TYPE_BFLOAT16, 2, d_in[6], gd, gs, bd, es, CU_TENSOR_MAP_INTERLEAVE_NONE,
           CU_TENSOR_MAP_SWIZZLE_128B, CU_TENSOR_MAP_L2_PROMOTION_L2_256B, CU_TENSOR_MAP_FLOAT_OOB_FILL_NONE);
    CUtensorMap tb;
    const cuuint64_t gd2[2] = {ND, ND};
    const cuuint64_t gs2[1] = {ND * 2};
    encode(&tb, CU_TENSOR_MAP_DATA_TYPE_BFLOAT16, 2, d_in[4], gd2, gs2, bd, es, CU_TENSOR_MAP_INTERLEAVE_NONE,
           CU_TENSOR_MAP_SWIZZLE_128B, CU_TENSOR_MAP_L2_PROMOTION_L2_256B, CU_TENSOR_MAP_FLOAT_OOB_FILL_NONE);
    fibinet_kernel<<<NPREP + NMAIN, 384, SMEM_BYTES>>>(
        (const int*)d_in[0], (const uint4*)d_in[1], (const __nv_bfloat16*)d_in[2], (const __nv_bfloat16*)d_in[3],
        (const __nv_bfloat16*)d_in[5], (const unsigned char*)d_in[6], (const __nv_bfloat16*)d_in[7], (__nv_bfloat16*)d_out, tm, tb);
}
```

```cpp
#include <cuda_runtime.h>
#include <cuda_bf16.h>
#include <cuda.h>
#include <stdint.h>

namespace {

constexpr int NF = 26, ND = 64, NH = 256, NR = 13;
constexpr int NPREP = 4;
constexpr int NMAIN = 128;

constexpr int SLOT = 8192;
constexpr int ZOFF = 15 * SLOT;
__host__ __device__ constexpr int slot(int s) { return ZOFF - s * SLOT; }
constexpr int BOFF = ZOFF + SLOT;
constexpr int AOFF = BOFF + 32768;
constexpr int COFF = slot(12);
constexpr int MOFF = AOFF + 65536 + 128;
constexpr int BAR_FULL = MOFF, BAR_DONE = MOFF + 64, BAR_WC = MOFF + 128, BAR_SE = MOFF + 176, BAR_TD = MOFF + 184,
              BAR_Z = MOFF + 192;
__host__ __device__ constexpr int bfull(int f) { return BAR_FULL + (f & 7) * 8; }
__host__ __device__ constexpr int bdone(int f) { return BAR_DONE + (f & 7) * 8; }
__host__ __device__ constexpr int bpar(int f) { return (f >> 3) & 1; }
constexpr int W2OFF = MOFF + 256, SEOFF = MOFF + 768;
constexpr int PARTOFF = SEOFF;
constexpr int SMEM_BYTES = MOFF + 2944;
constexpr int XDELTA = 2 * SLOT;
__host__ __device__ constexpr int xpair(int i) {
    return (i & 3) == 0 ? slot(11) : (i & 3) == 1 ? BOFF : (i & 3) == 2 ? BOFF + SLOT : slot(15);
}
__host__ __device__ constexpr int wl(int f) { return f % 5 == 0 ? 1 : f % 5 == 4 ? 7 : f % 5 + 2; }
__host__ __device__ constexpr int wcslot(int c) {
    return c == 0 ? slot(3) : c == 1 ? slot(8) : c == 2 ? slot(10) : c == 3 ? slot(15) : c == 4 ? slot(13)
         : c == 5 ? slot(11) : c == 6 ? slot(9) : c == 7 ? slot(14) : c == 8 ? slot(7) : c == 9 ? slot(2)
         : c == 10 ? slot(1) : c == 11 ? slot(4) : c == 12 ? slot(5) : c == 13 ? slot(6) : c == 14 ? ZOFF : slot(3);
}
__host__ __device__ constexpr int wcfirst(int gi) { return gi < 3 ? gi : gi == 3 ? 5 : gi == 4 ? 8 : gi == 5 ? 11 : 16; }
constexpr int EXOFF = slot(5);
constexpr int ZQOFF = slot(6);
constexpr int GOFF = ZQOFF + 4096;

__device__ uint4 g_wc[2 * 16 * 8192 / 16];
__device__ uint4 g_se[2048 / 16];
__device__ uint4 g_w2[NH / 8];
__device__ unsigned g_ready;
__device__ unsigned g_seen;

__host__ __device__ constexpr int fieldof(int f) { return f < 24 ? 4 * (f >> 2) + 2 * (f & 1) + ((f >> 1) & 1) : f; }
__device__ __forceinline__ int fmap(int n) { return n < 24 ? n : 24 + ((n >> 1) & 1); }
__host__ __device__ constexpr int estep(int s) { return (s & 1) + 2 * (s >> 2) + 4 * (s & 2); }

__device__ __forceinline__ uint64_t mkdesc(uint32_t addr, uint32_t lbo, uint32_t sbo, int sw) {
    return (uint64_t)((addr & 0x3ffff) >> 4) | ((uint64_t)(lbo >> 4) << 16) | ((uint64_t)(sbo >> 4) << 32) |
           ((uint64_t)sw << 62);
}
__device__ __forceinline__ void mbar_init(uint32_t b, uint32_t n) {
    asm volatile("mbarrier.init.shared.b64 [%0], %1;" ::"r"(b), "r"(n) : "memory");
}
__device__ __forceinline__ void mbar_wait(uint32_t b, uint32_t par = 0) {
    asm volatile(
        "{\n.reg .pred p, q;\n.reg .u32 n;\n"
        "mbarrier.try_wait.parity.shared.b64 p, [%0], %1;\n@p bra.uni WD%=;\nmov.u32 n, 0;\n"
        "WL%=:\nmbarrier.try_wait.parity.shared.b64 p, [%0], %1;\n@p bra.uni WD%=;\n"
        "add.u32 n, n, 1;\nsetp.lt.u32 q, n, 4000000;\n@q bra.uni WL%=;\nWD%=:\n}\n" ::"r"(b), "r"(par)
        : "memory");
}
__device__ __forceinline__ uint32_t mbar_test(uint32_t b, uint32_t par) {
    uint32_t ok;
    asm volatile("{.reg .pred p; mbarrier.test_wait.parity.shared.b64 p, [%1], %2; selp.u32 %0, 1, 0, p;}"
                 : "=r"(ok)
                 : "r"(b), "r"(par)
                 : "memory");
    return ok;
}
__device__ __forceinline__ void mbar_wait_unless(uint32_t ok, uint32_t b, uint32_t par) {
    asm volatile(
        "{\n.reg .pred p, q;\n.reg .u32 n;\n"
        "setp.ne.u32 p, %1, 0;\n@p bra.uni WD%=;\nmov.u32 n, 0;\n"
        "WL%=:\nmbarrier.try_wait.parity.shared.b64 p, [%0], %2;\n@p bra.uni WD%=;\n"
        "add.u32 n, n, 1;\nsetp.lt.u32 q, n, 4000000;\n@q bra.uni WL%=;\nWD%=:\n}\n" ::"r"(b), "r"(ok), "r"(par)
        : "memory");
}
__device__ __forceinline__ void mbar_arrive(uint32_t b) {
    asm volatile("mbarrier.arrive.shared.b64 _, [%0];" ::"r"(b) : "memory");
}
__device__ __forceinline__ void mbar_expect(uint32_t b, uint32_t bytes) {
    asm volatile("mbarrier.arrive.expect_tx.shared.b64 _, [%0], %1;" ::"r"(b), "r"(bytes) : "memory");
}
__device__ __forceinline__ uint32_t opaque(uint32_t v) { return __shfl_sync(0xffffffffu, v, threadIdx.x); }
__device__ __forceinline__ bool elect() {
    uint32_t p;
    asm volatile("{.reg .pred q; elect.sync _|q, 0xffffffff; selp.u32 %0, 1, 0, q;}" : "=r"(p));
    return p;
}
__device__ __forceinline__ void tma2d(uint32_t dst, const CUtensorMap* m, uint32_t bar, int x, int y) {
    asm volatile(
        "cp.async.bulk.tensor.2d.shared::cluster.global.mbarrier::complete_tx::bytes [%0], [%1, {%3, %4}], [%2];" ::"r"(dst),
        "l"(m), "r"(bar), "r"(x), "r"(y)
        : "memory");
}
__device__ __forceinline__ void bulk(uint32_t dst, const void* src, uint32_t bytes, uint32_t bar) {
    asm volatile("cp.async.bulk.shared::cluster.global.mbarrier::complete_tx::bytes [%0], [%1], %2, [%3];" ::"r"(dst),
                 "l"(src), "r"(bytes), "r"(bar)
                 : "memory");
}
__device__ __forceinline__ void cp16(uint32_t dst, const void* src) {
    asm volatile("cp.async.cg.shared.global [%0], [%1], 16;" ::"r"(dst), "l"(src) : "memory");
}
__device__ __forceinline__ void lds128(uint32_t (&v)[4], uint32_t a) {
    asm volatile("ld.shared.v4.u32 {%0,%1,%2,%3}, [%4];" : "=r"(v[0]), "=r"(v[1]), "=r"(v[2]), "=r"(v[3]) : "r"(a) : "memory");
}
__device__ __forceinline__ void lds128_if(uint32_t (&v)[4], uint32_t a, uint32_t p) {
    asm volatile("{.reg .pred q; setp.ne.u32 q, %5, 0; @q ld.shared.v4.u32 {%0,%1,%2,%3}, [%4];}"
                 : "+r"(v[0]), "+r"(v[1]), "+r"(v[2]), "+r"(v[3])
                 : "r"(a), "r"(p)
                 : "memory");
}
__device__ __forceinline__ void lds64(uint32_t& x, uint32_t& y, uint32_t a) {
    asm volatile("ld.shared.v2.u32 {%0,%1}, [%2];" : "=r"(x), "=r"(y) : "r"(a) : "memory");
}
__device__ __forceinline__ void sts128(uint32_t a, uint32_t x, uint32_t y, uint32_t z, uint32_t w) {
    asm volatile("st.shared.v4.u32 [%0], {%1,%2,%3,%4};" ::"r"(a), "r"(x), "r"(y), "r"(z), "r"(w) : "memory");
}
__device__ __forceinline__ void sts64(uint32_t a, uint32_t x, uint32_t y) {
    asm volatile("st.shared.v2.u32 [%0], {%1,%2};" ::"r"(a), "r"(x), "r"(y) : "memory");
}
__device__ __forceinline__ uint32_t pack(float lo, float hi) {
    uint32_t r;
    asm volatile("cvt.rn.bf16x2.f32 %0, %1, %2;" : "=r"(r) : "f"(hi), "f"(lo));
    return r;
}
__device__ __forceinline__ uint32_t hmul2(uint32_t a, uint32_t b) {
    uint32_t r;
    asm volatile("mul.rn.bf16x2 %0, %1, %2;" : "=r"(r) : "r"(a), "r"(b));
    return r;
}
template <int H>
__device__ __forceinline__ uint32_t hfma2_bcast(uint32_t a, uint32_t x, uint32_t c) {
    uint32_t r;
    if (H)
        asm volatile("{.reg .b16 l, h; .reg .b32 s; mov.b32 {l, h}, %2; mov.b32 s, {h, h}; fma.rn.bf16x2 %0, %1, s, %3;}"
                     : "=r"(r)
                     : "r"(a), "r"(x), "r"(c));
    else
        asm volatile("{.reg .b16 l, h; .reg .b32 s; mov.b32 {l, h}, %2; mov.b32 s, {l, l}; fma.rn.bf16x2 %0, %1, s, %3;}"
                     : "=r"(r)
                     : "r"(a), "r"(x), "r"(c));
    return r;
}
__device__ __forceinline__ float ffma(float a, float b, float c) {
    float r;
    asm volatile("fma.rn.f32 %0, %1, %2, %3;" : "=f"(r) : "f"(a), "f"(b), "f"(c));
    return r;
}
__device__ __forceinline__ float tanh_fast(float x) {
    float r;
    asm volatile("tanh.approx.f32 %0, %1;" : "=f"(r) : "f"(x));
    return r;
}
__device__ __forceinline__ float gelu_tanh(float x) {
    float r;
    asm volatile(
        "{.reg .f32 a; mul.f32 a, %1, %1; fma.rn.f32 a, a, 0f3D122279, 0f3F4C422A; mul.f32 a, a, %1; tanh.approx.f32 %0, a;}"
        : "=f"(r)
        : "f"(x));
    return r;
}
__device__ __forceinline__ void mma16816(float (&d)[4], const uint32_t (&a)[4], uint32_t b0, uint32_t b1) {
    asm volatile("mma.sync.aligned.m16n8k16.row.col.f32.bf16.bf16.f32 {%0,%1,%2,%3}, {%4,%5,%6,%7}, {%8,%9}, {%0,%1,%2,%3};"
                 : "+f"(d[0]), "+f"(d[1]), "+f"(d[2]), "+f"(d[3])
                 : "r"(a[0]), "r"(a[1]), "r"(a[2]), "r"(a[3]), "r"(b0), "r"(b1));
}
__device__ __forceinline__ uint32_t clock32() {
    uint32_t c;
    asm volatile("mov.u32 %0, %%clock;" : "=r"(c)::"memory");
    return c;
}
#define WG_FENCE() asm volatile("wgmma.fence.sync.aligned;" ::: "memory")
#define WG_COMMIT() asm volatile("wgmma.commit_group.sync.aligned;" ::: "memory")
#define WG_WAIT0() asm volatile("wgmma.wait_group.sync.aligned 0;" ::: "memory")
#define WG_WAIT1() asm volatile("wgmma.wait_group.sync.aligned 1;" ::: "memory")
#define CP_COMMIT() asm volatile("cp.async.commit_group;" ::: "memory")
#define CP_WAIT(n) asm volatile("cp.async.wait_group %0;" ::"n"(n) : "memory")
#define SCHED_FENCE() asm volatile("pmevent 0;" ::: "memory")
#define PROXY_FENCE() asm volatile("fence.proxy.async.shared::cta;" ::: "memory")
template <int N>
__device__ __forceinline__ void pin(float (&d)[N]) {
#pragma unroll
    for (int i = 0; i < N; i++) asm volatile("" : "+f"(d[i])::"memory");
}
#define TS(k)
#define TS_DUMP(role)

__device__ __forceinline__ void wgmma_ss_n168_acc(float (&d)[84], uint64_t da, uint64_t db) {
    asm volatile(
        "wgmma.mma_async.sync.aligned.m64n168k16.f32.bf16.bf16 "
        "{%0,%1,%2,%3,%4,%5,%6,%7,%8,%9,%10,%11,%12,%13,%14,%15,"
        "%16,%17,%18,%19,%20,%21,%22,%23,%24,%25,%26,%27,%28,%29,%30,%31,"
        "%32,%33,%34,%35,%36,%37,%38,%39,%40,%41,%42,%43,%44,%45,%46,%47,"
        "%48,%49,%50,%51,%52,%53,%54,%55,%56,%57,%58,%59,%60,%61,%62,%63,"
        "%64,%65,%66,%67,%68,%69,%70,%71,%72,%73,%74,%75,%76,%77,%78,%79,"
        "%80,%81,%82,%83}, "
        "%84, %85, 1, 1, 1, 0, 1;"
        : "+f"(d[0]), "+f"(d[1]), "+f"(d[2]), "+f"(d[3]), "+f"(d[4]), "+f"(d[5]), "+f"(d[6]), "+f"(d[7]),
          "+f"(d[8]), "+f"(d[9]), "+f"(d[10]), "+f"(d[11]), "+f"(d[12]), "+f"(d[13]), "+f"(d[14]), "+f"(d[15]),
          "+f"(d[16]), "+f"(d[17]), "+f"(d[18]), "+f"(d[19]), "+f"(d[20]), "+f"(d[21]), "+f"(d[22]), "+f"(d[23]),
          "+f"(d[24]), "+f"(d[25]), "+f"(d[26]), "+f"(d[27]), "+f"(d[28]), "+f"(d[29]), "+f"(d[30]), "+f"(d[31]),
          "+f"(d[32]), "+f"(d[33]), "+f"(d[34]), "+f"(d[35]), "+f"(d[36]), "+f"(d[37]), "+f"(d[38]), "+f"(d[39]),
          "+f"(d[40]), "+f"(d[41]), "+f"(d[42]), "+f"(d[43]), "+f"(d[44]), "+f"(d[45]), "+f"(d[46]), "+f"(d[47]),
          "+f"(d[48]), "+f"(d[49]), "+f"(d[50]), "+f"(d[51]), "+f"(d[52]), "+f"(d[53]), "+f"(d[54]), "+f"(d[55]),
          "+f"(d[56]), "+f"(d[57]), "+f"(d[58]), "+f"(d[59]), "+f"(d[60]), "+f"(d[61]), "+f"(d[62]), "+f"(d[63]),
          "+f"(d[64]), "+f"(d[65]), "+f"(d[66]), "+f"(d[67]), "+f"(d[68]), "+f"(d[69]), "+f"(d[70]), "+f"(d[71]),
          "+f"(d[72]), "+f"(d[73]), "+f"(d[74]), "+f"(d[75]), "+f"(d[76]), "+f"(d[77]), "+f"(d[78]), "+f"(d[79]),
          "+f"(d[80]), "+f"(d[81]), "+f"(d[82]), "+f"(d[83])
        : "l"(da), "l"(db));
}

__device__ __forceinline__ void wgmma_rs_n32_set(float (&d)[16], const uint32_t (&a)[4], uint64_t db) {
    asm volatile(
        "wgmma.mma_async.sync.aligned.m64n32k16.f32.bf16.bf16 "
        "{%0,%1,%2,%3,%4,%5,%6,%7,%8,%9,%10,%11,%12,%13,%14,%15}, "
        "{%16,%17,%18,%19}, %20, 0, 1, 1, 0;"
        : "=f"(d[0]), "=f"(d[1]), "=f"(d[2]), "=f"(d[3]), "=f"(d[4]), "=f"(d[5]), "=f"(d[6]), "=f"(d[7]),
          "=f"(d[8]), "=f"(d[9]), "=f"(d[10]), "=f"(d[11]), "=f"(d[12]), "=f"(d[13]), "=f"(d[14]), "=f"(d[15])
        : "r"(a[0]), "r"(a[1]), "r"(a[2]), "r"(a[3]), "l"(db));
}

__device__ __forceinline__ void wgmma_rs_n32_acc(float (&d)[16], const uint32_t (&a)[4], uint64_t db) {
    asm volatile(
        "wgmma.mma_async.sync.aligned.m64n32k16.f32.bf16.bf16 "
        "{%0,%1,%2,%3,%4,%5,%6,%7,%8,%9,%10,%11,%12,%13,%14,%15}, "
        "{%16,%17,%18,%19}, %20, 1, 1, 1, 0;"
        : "+f"(d[0]), "+f"(d[1]), "+f"(d[2]), "+f"(d[3]), "+f"(d[4]), "+f"(d[5]), "+f"(d[6]), "+f"(d[7]),
          "+f"(d[8]), "+f"(d[9]), "+f"(d[10]), "+f"(d[11]), "+f"(d[12]), "+f"(d[13]), "+f"(d[14]), "+f"(d[15])
        : "r"(a[0]), "r"(a[1]), "r"(a[2]), "r"(a[3]), "l"(db));
}

__device__ __forceinline__ void wgmma_rs_n16_set(float (&d)[8], const uint32_t (&a)[4], uint64_t db) {
    asm volatile(
        "wgmma.mma_async.sync.aligned.m64n16k16.f32.bf16.bf16 "
        "{%0,%1,%2,%3,%4,%5,%6,%7}, "
        "{%8,%9,%10,%11}, %12, 0, 1, 1, 0;"
        : "=f"(d[0]), "=f"(d[1]), "=f"(d[2]), "=f"(d[3]), "=f"(d[4]), "=f"(d[5]), "=f"(d[6]), "=f"(d[7])
        : "r"(a[0]), "r"(a[1]), "r"(a[2]), "r"(a[3]), "l"(db));
}

__device__ __forceinline__ void wgmma_rs_n32_pred(float (&d)[16], const uint32_t (&a)[4], uint64_t db, uint32_t scale_d) {
    asm volatile(
        "{.reg .pred p; setp.ne.u32 p, %21, 0; wgmma.mma_async.sync.aligned.m64n32k16.f32.bf16.bf16 "
        "{%0,%1,%2,%3,%4,%5,%6,%7,%8,%9,%10,%11,%12,%13,%14,%15}, "
        "{%16,%17,%18,%19}, %20, p, 1, 1, 0;}"
        : "+f"(d[0]), "+f"(d[1]), "+f"(d[2]), "+f"(d[3]), "+f"(d[4]), "+f"(d[5]), "+f"(d[6]), "+f"(d[7]),
          "+f"(d[8]), "+f"(d[9]), "+f"(d[10]), "+f"(d[11]), "+f"(d[12]), "+f"(d[13]), "+f"(d[14]), "+f"(d[15])
        : "r"(a[0]), "r"(a[1]), "r"(a[2]), "r"(a[3]), "l"(db), "r"(scale_d));
}

__device__ __forceinline__ void prep_cta(uint32_t sb, int c, const __nv_bfloat16* __restrict__ wc,
                                         const __nv_bfloat16* __restrict__ se1, const __nv_bfloat16* __restrict__ se2,
                                         const __nv_bfloat16* __restrict__ w2) {
    const int tid = threadIdx.x, lane = tid & 31, warp = tid >> 5, s = c >> 1;
    constexpr int ZERO = 16 * NF * 128;
#pragma unroll
    for (int q = tid; q < 16 * NF * 8; q += 384) {
        const int i = q >> 7, nn = (q >> 3) & 15, j = fmap((16 * (c & 1) + nn) ^ s);
        cp16(sb + (q >> 3) * 128 + (((q & 7) ^ (i & 1) ^ ((i >> 3) << 1)) << 4), wc + ((s * NF + i) * NF + j) * ND + (q & 7) * 8);
    }
    if (tid < 8) sts128(sb + ZERO + tid * 16, 0, 0, 0, 0);
    if (tid < 256) {
        const int n = ((tid >> 2) & 1) * 8 + (tid >> 5) + (s ? (c & 1) * 16 : 0);
        const int k = ((tid >> 1) & 1) * 8 + ((tid >> 3) & 3) * 2 + (tid & 1), mm = k >> 1, u = k & 1;
        const int f = s ? fmap(n) : mm < 6 ? 4 * mm + 2 * c + u : (mm == 6 && u == 0) ? 24 + c : -1;
        float v = 0.f;
        if (f >= 0 && (s ? k : n) < NR) v = __bfloat162float(s ? se2[k * NF + f] : se1[f * NR + n]);
        reinterpret_cast<__nv_bfloat16*>(g_se)[c * 256 + tid] = __float2bfloat16(s ? 0.5f * v : v);
    } else if (tid < 320) {
        const int q = tid - 256;
        reinterpret_cast<__nv_bfloat16*>(g_w2)[c * 64 + q] =
            __float2bfloat16(0.5f * __bfloat162float(w2[c * 64 + (q & 32) + 4 * (q & 6) + ((q >> 2) & 6) + (q & 1)]));
    }
    asm volatile("cp.async.wait_all;" ::: "memory");
    __syncthreads();
    const int k = 4 * (lane & 6) + 2 * (lane >> 3) + (lane & 1), i = fmap(k);
    const int g = lane >> 2, t = lane & 3;
#pragma unroll 4
    for (int task = warp; task < 128; task += 12) {
        const int nn = task & 15, eg = task >> 4, n = 16 * (c & 1) + nn;
        const uint32_t a = sb + (k < 28 ? (i * 16 + nn) * 128 : ZERO) + ((eg ^ (i & 1) ^ ((i >> 3) << 1)) << 4);
        uint4 v;
        asm volatile("ldmatrix.sync.aligned.m8n8.x4.trans.shared.b16 {%0,%1,%2,%3}, [%4];"
                     : "=r"(v.x), "=r"(v.y), "=r"(v.z), "=r"(v.w)
                     : "r"(a));
        if (t == 3) {
            const uint32_t mask = (eg & 1) ? 0xffff0000u : 0xffffu;
            v.x &= mask;
            v.y &= mask;
        }
        const int ch = (t < 2 ? t ^ ((g >> 1) & 1) : t) ^ ((n >> 1) & 3);
        const int step = (g & 1) + 2 * (eg & 1) + 2 * (g & 6);
        g_wc[(eg >> 2) * 8192 + step * 512 + ((eg >> 1) & 1) * 256 + s * 128 + n * 4 + ch] = v;
    }
    __threadfence();
    __syncthreads();
    if (tid == 0) atomicAdd(&g_ready, 1u);
}

#define PACE1 2250
#define PACE2 2850
#define START_MIN 3400
#define WDELAY 1600
#define WSTEP 500
#define WPF_AT 2600
#define WPF_STEP 800
#define POLL_AT 6500
#define T_SHIFT 300
constexpr int DB0 = 6;

__global__ void __cluster_dims__(2, 1, 1) __launch_bounds__(384, 1)
fibinet_kernel(const int* __restrict__ idx, const uint4* __restrict__ table,
               const __nv_bfloat16* __restrict__ se1, const __nv_bfloat16* __restrict__ se2,
               const __nv_bfloat16* __restrict__ wc,
               const unsigned char* __restrict__ w1, const __nv_bfloat16* __restrict__ w2, __nv_bfloat16* __restrict__ out,
               const __grid_constant__ CUtensorMap tm_w1, const __grid_constant__ CUtensorMap tm_bi) {
    extern __shared__ __align__(1024) unsigned char smem[];
    const int tid = threadIdx.x;
    const int cta = blockIdx.x - NPREP, grp = cta >> 1, rank = cta & 1, lane = tid & 31;
    uint32_t ids[13][4], cid[3][2];
    const uint32_t idle = (tid >> 8) | (cta < 0);
    const uint32_t row = ((tid >> 5) & 3) * 16 + (lane >> 3);
    const unsigned char* ib = reinterpret_cast<const unsigned char*>(idx) + (int64_t)grp * (64 * NF * 4);
    {
        const unsigned char* ip = ib + (row * (NF * 4) + ((tid >> 4) & 8));
#pragma unroll
        for (int u = 0; u < 4; u++) {
            ids[0][u] = ids[1][u] = 0;
            asm volatile("{.reg .pred p; setp.eq.u32 p, %3, 0; @p ld.global.nc.L2::128B.v2.u32 {%0,%1}, [%2];}"
                         : "+r"(ids[0][u]), "+r"(ids[1][u])
                         : "l"(ip + 16 * NF * u), "r"(idle));
        }
    }
    const uint32_t t_0 = clock32();
    {
        const uint32_t co = ((tid & 127) >> 1) * (NF * 4) + ((tid >> 4) & 8) + 16 + 16 * (tid & 1);
#pragma unroll
        for (int k = 0; k < 3; k++) {
            cid[k][0] = cid[k][1] = 0;
            asm volatile("{.reg .pred p; setp.eq.u32 p, %3, 0; @p ld.global.nc.v2.u32 {%0,%1}, [%2];}"
                         : "+r"(cid[k][0]), "+r"(cid[k][1])
                         : "l"(ib + (co + 32 * k - (k == 2 ? 8 * ((tid >> 7) & tid & 1) : 0))), "r"(idle));
        }
    }
    const uint32_t t_start = (t_0 ^ (clock32() & blockIdx.y)) - T_SHIFT;
    const uint32_t sb = (uint32_t)__cvta_generic_to_shared(smem);
    uint32_t gd0 = sb + (tid >> 7) * XDELTA + row * 128 + (((lane & 7) ^ (lane >> 3) ^ ((tid >> 5) & 4)) << 4);
    const uint4* tp = table + (lane & 7);
    auto gather = [&](int i) {
#pragma unroll
        for (int u = 0; u < 4; u++)
            asm volatile(
                "{.reg .u64 a; .reg .pred p; setp.eq.u32 p, %3, 0; mad.wide.u32 a, %2, 128, %1; @p cp.async.cg.shared.global [%0], [a], 16;}" ::"r"(
                    (gd0 ^ ((u & 1) * 64)) + xpair(i) + u * 512),
                "l"(tp), "r"(ids[i][u]), "r"(i == 0 ? idle : 0u)
                : "memory");
        CP_COMMIT();
    };
    gather(0);
    if (cta < 0) {
        prep_cta(sb, blockIdx.x, wc, se1, se2, w2);
        return;
    }
    if (tid == 288) asm volatile("prefetch.tensormap [%0];" ::"l"(&tm_w1));
    const int warp = __reduce_max_sync(0xffffffffu, tid >> 5);
    const int w = warp >> 2;

    if (w == 2) {
        asm volatile("setmaxnreg.dec.sync.aligned.u32 40;");
        auto load_wc = [&](int gi) {
            if (elect()) {
                const unsigned char* src = reinterpret_cast<const unsigned char*>(g_wc) + rank * 131072;
                mbar_expect(sb + BAR_WC + gi * 8, (wcfirst(gi + 1) - wcfirst(gi)) * 8192);
#pragma unroll
                for (int c = wcfirst(gi); c < wcfirst(gi + 1); c++) bulk(sb + wcslot(c), src + c * 8192, 8192, sb + BAR_WC + gi * 8);
            }
            __syncwarp();
        };
        if (warp == 8) {
            if (elect()) {
                mbar_init(sb + BAR_Z, 1);
                mbar_expect(sb + BAR_Z, 8192);
                tma2d(sb + ZOFF, &tm_bi, sb + BAR_Z, 32 * rank, 0);
            }
#pragma unroll
            for (int f = 0; f < 26; f++) {
                if (f == 2) {
                    if (elect()) {
#pragma unroll
                        for (int k = 2; k < 8; k++) mbar_init(sb + BAR_FULL + k * 8, 1);
                        asm volatile("fence.mbarrier_init.release.cluster;" ::: "memory");
                    }
                    __syncwarp();
                    asm volatile("barrier.cluster.arrive.relaxed.aligned;" ::: "memory");
                    mbar_wait(sb + BAR_Z);
#pragma unroll
                    for (int k = 0; k < 2; k++)
                        sts128(sb + ZOFF + (k * 32 + lane) * 128 + ((4 ^ (lane & 7)) << 4), 0x3c803c80u, 0x3c803c80u, 0x3c803c80u, 0x3c803c80u);
                    PROXY_FENCE();
                    asm volatile("bar.arrive 0, 384;" ::: "memory");
                    TS(31);
                }
                if (f == 5) asm volatile("bar.sync 7, 64;" ::: "memory");
                if (f >= 5) mbar_wait(sb + bdone(f - 5), bpar(f - 5));
                if (f >= 2 && f < 5)
                    while (clock32() - t_start < WDELAY + (f - 2) * WSTEP) {
                    }
                if (elect()) {
                    if (f < 2) mbar_init(sb + BAR_FULL + f * 8, 1);
                    mbar_expect(sb + bfull(f), 16384);
                    tma2d(sb + slot(2 * wl(f)), &tm_w1, sb + bfull(f), 128 * rank + 64 * (f & 1), fieldof(f) * 64);
                    tma2d(sb + slot(wl(f)), &tm_w1, sb + bfull(f), 128 * rank + 64 - 64 * (f & 1), fieldof(f) * 64);
                }
                TS(f);
            }
            asm volatile("bar.arrive 8, 128;" ::: "memory");
            TS_DUMP(2);
        } else if (warp == 9) {
            if (elect()) {
#pragma unroll
                for (int k = 0; k < 8; k++) mbar_init(sb + BAR_WC + k * 8, k < 7 ? 1 : 8);
                asm volatile("fence.mbarrier_init.release.cluster;" ::: "memory");
            }
            __syncwarp();
            asm volatile("barrier.cluster.arrive.relaxed.aligned;" ::: "memory");
            asm volatile("bar.sync 0, 384;" ::: "memory");
            while (clock32() - t_start < POLL_AT) __nanosleep(100);
            if (elect()) {
                unsigned v, it = 0;
                do {
                    asm volatile("ld.acquire.gpu.global.u32 %0, [%1];" : "=r"(v) : "l"(&g_ready) : "memory");
                } while (v < NPREP && ++it < 4000000u);
                asm volatile("fence.proxy.async.global;" ::: "memory");
                mbar_expect(sb + BAR_SE, 2048 + 256);
                bulk(sb + SEOFF, g_se, 2048, sb + BAR_SE);
                bulk(sb + W2OFF, g_w2 + rank * 16, 256, sb + BAR_SE);
            }
            __syncwarp();
            TS(0);
            asm volatile("bar.sync 8, 128;" ::: "memory");
#pragma unroll
            for (int gi = 0; gi < 3; gi++) {
                mbar_wait(sb + bdone(21 + gi), bpar(21 + gi));
                load_wc(gi);
                TS(1 + gi);
            }
        } else if (warp == 10) {
            if (elect()) {
#pragma unroll
                for (int k = 0; k < 8; k++) mbar_init(sb + BAR_DONE + k * 8, 4);
                asm volatile("fence.mbarrier_init.release.cluster;" ::: "memory");
            }
            __syncwarp();
            asm volatile("barrier.cluster.arrive.relaxed.aligned;" ::: "memory");
            asm volatile("bar.arrive 7, 64;" ::: "memory");
            asm volatile("bar.sync 0, 384;" ::: "memory");
#pragma unroll 1
            for (int k = 0; k < 7; k++) {
                while (clock32() - t_start < (uint32_t)(WPF_AT + k * WPF_STEP)) __nanosleep(150);
                if (lane < 6)
                    asm volatile("prefetch.global.L2 [%0];" ::"l"(w1 + (5 + k * 3 + (lane >> 1)) * 32768 + cta * 256 + (lane & 1) * 128));
            }
            asm volatile("bar.sync 8, 128;" ::: "memory");
        } else {
            asm volatile("bar.sync 0, 384;" ::: "memory");
            asm volatile("bar.sync 8, 128;" ::: "memory");
        }
        {
            uint32_t bw[2][4], z0[4], z1[4];
            mbar_wait(sb + BAR_SE);
            lds128(bw[0], sb + SEOFF + lane * 16);
            lds128(bw[1], sb + SEOFF + 512 + lane * 16);
            asm volatile("bar.sync 2, 384;" ::: "memory");
            lds128(z0, sb + ZQOFF + (tid & 127) * 16);
            lds128(z1, sb + ZQOFF + 2048 + (tid & 127) * 16);
            TS(8);
            float s[2][4] = {};
#pragma unroll
            for (int n = 0; n < 2; n++) {
                mma16816(s[n], z0, bw[0][2 * n], bw[0][2 * n + 1]);
                mma16816(s[n], z1, bw[1][2 * n], bw[1][2 * n + 1]);
            }
            lds128(bw[0], sb + SEOFF + 1024 + lane * 16);
            lds128(bw[1], sb + SEOFF + 1536 + lane * 16);
            float th[8];
#pragma unroll
            for (int k = 0; k < 8; k++) th[k] = gelu_tanh(s[k >> 2][k & 3]);
            SCHED_FENCE();
            TS(9);
            uint32_t gq[4];
#pragma unroll
            for (int k = 0; k < 4; k++)
                gq[k] = pack(s[k >> 1][2 * (k & 1)] * ffma(th[2 * k], 0.5f, 0.5f), s[k >> 1][2 * (k & 1) + 1] * ffma(th[2 * k + 1], 0.5f, 0.5f));
            float a[4][4] = {};
#pragma unroll
            for (int n = 0; n < 4; n++) mma16816(a[n], gq, bw[n >> 1][2 * (n & 1)], bw[n >> 1][2 * (n & 1) + 1]);
#pragma unroll
            for (int k = 0; k < 16; k++)
                if (k < 13 || k == 14) a[k >> 2][k & 3] = tanh_fast(a[k >> 2][k & 3]);
            SCHED_FENCE();
            TS(10);
            uint32_t ap[8];
#pragma unroll
            for (int k = 0; k < 8; k++)
                ap[k] = pack(ffma(a[k >> 1][2 * (k & 1)], 0.5f, 0.5f), ffma(a[k >> 1][2 * (k & 1) + (k < 6)], 0.5f, 0.5f));
            sts128(sb + GOFF + (tid & 127) * 16, ap[0], ap[1], ap[2], ap[3]);
            sts128(sb + GOFF + 2048 + (tid & 127) * 16, ap[4], ap[5], ap[6], ap[7]);
            if (warp != 9) mbar_wait(sb + BAR_WC + (warp == 8 ? 0 : warp - 9) * 8);
            asm volatile("bar.arrive 3, 384;" ::: "memory");
            TS(11);
        }
        if (warp == 9) {
            load_wc(3);
            load_wc(4);
            mbar_wait(sb + BAR_TD);
            load_wc(5);
            if (lane == 0 && atomicAdd(&g_seen, 1u) == NMAIN - 1) {
                g_seen = 0;
                g_ready = 0;
            }
            if (lane < 16) TS_DUMP(3);
        } else if (warp == 11) {
            if (lane < 16) reinterpret_cast<uint32_t*>(out)[cta * 16 + lane] = 0;
            asm volatile("barrier.cluster.arrive.release.aligned;" ::: "memory");
        } else if (warp == 10) {
            uint32_t* dst = reinterpret_cast<uint32_t*>(out) + grp * 32 + lane;
            asm volatile("barrier.cluster.wait.acquire.aligned;" : "+l"(dst)::"memory");
            SCHED_FENCE();
            asm volatile("bar.sync 4, 288;" ::: "memory");
            uint32_t p[4];
            lds64(p[0], p[1], sb + PARTOFF + lane * 8);
            lds64(p[2], p[3], sb + PARTOFF + 256 + lane * 8);
            asm volatile("red.relaxed.gpu.global.add.noftz.bf16x2 [%0], %1;" ::"l"(dst),
                         "r"(pack(__uint_as_float(p[0]) + __uint_as_float(p[2]), __uint_as_float(p[1]) + __uint_as_float(p[3])))
                         : "memory");
        }
    } else {
        asm volatile("setmaxnreg.inc.sync.aligned.u32 232;");
        asm volatile("barrier.cluster.arrive.relaxed.aligned;" ::: "memory");
        const uint32_t sb = __reduce_max_sync(0xffffffffu, (uint32_t)__cvta_generic_to_shared(smem) | (tid >> 10));
        const int t128 = opaque(tid & 127), lane = t128 & 31;
        const int g = lane >> 2, t = lane & 3, wq = warp & 3;
        gd0 = opaque(gd0);
        TS(28);
        float acc[84];
#pragma unroll
        for (int k = 0; k < 84; k++) asm volatile("mov.b32 %0, 0;" : "=f"(acc[k]));
        uint32_t e0[9], e1[9], e2[9];
        uint32_t X[13][2][4];
        uint32_t zq[4] = {0, 0, 0, 0};
        const uint64_t dA = mkdesc(sb + w * XDELTA, 16, 1024, 1);
        uint32_t dBlo = (uint32_t)mkdesc(sb + ZOFF, 0, 0, 0);
        const uint32_t xl0 = opaque(sb + (t & 1) * XDELTA + (16 * wq + g) * 128 + (((4 * rank + 2 * w) ^ (4 * (t & 1)) ^ g) << 4));
        const uint32_t hi_half = t >> 1;
        const uint32_t sa0 = opaque(sb + AOFF + t * 4096 + (t >> 1) * 16 + (wq * 32 + g * 4 + w) * 16);
        const uint32_t sa1 = opaque(((g & 2) << 4) | ((t & 1) << 3));
        const uint32_t zero = __reduce_max_sync(0xffffffffu, blockIdx.y | (tid >> 10));
        auto expand = [&](int k0, int k1) {
#pragma unroll
            for (int k = k0; k < k1; k++)
#pragma unroll
                for (int u = 0; u < 4; u++)
                    asm volatile("shfl.sync.idx.b32 %0, %1, %2, 31, 0xffffffff;"
                                 : "=r"(ids[k][u])
                                 : "r"(k < 12 ? cid[(k - 2) >> 2][k & 1] : w ? cid[2][1] : cid[2][0]),
                                   "r"(2 * (lane >> 3) + 8 * u + (((k - 2) >> 1) & 1)));
        };
        auto twarm = [&]() {
            float s1[8];
            WG_FENCE();
            wgmma_rs_n16_set(s1, zq, mkdesc(sb + AOFF, 16, 512, 2));
            WG_COMMIT();
            WG_WAIT0();
            pin(s1);
            asm volatile("{.reg .pred p; setp.ne.u32 p, %1, 0; @p st.shared.f32 [%1], %0;}" ::"f"(s1[0]), "r"(zero));
        };
        expand(2, 8);
        twarm();
        TS(26);
        while (clock32() - t_start < PACE1) {
        }
        gather(1);
        expand(8, 13);
        twarm();
        TS(30);
        while (clock32() - t_start < PACE2) {
        }
        gather(2);
        twarm();
        asm volatile("bar.sync 0, 384;" ::: "memory");
        auto lift = [&](int i) {
            const int m = 2 * (i >> 2) + (i & 1);
#pragma unroll
            for (int r = 0; r < 2; r++)
#pragma unroll
                for (int cc = 0; cc < 2; cc++) {
                    const uint32_t a = (xl0 ^ (cc * 16)) + xpair(i) + r * 1024;
                    if (i == 12 ? r : (i & 2)) lds128_if(X[i == 12 ? 12 : 2 * m + r][cc], a, hi_half);
                    else lds128(X[2 * m + r][cc], a);
                }
        };
        auto store_pair = [&](int m, int half, const uint32_t (&ea)[9]) {
            uint32_t a;
            if (m < 4) a = sa0 + (sa1 ^ (((m & 1) << 5) | ((m >> 1) << 3)));
            else a = sb + BOFF + t * 2048 + (wq * 32 + g * 4 + ((2 * (m & 1) + w) ^ t)) * 8;
#pragma unroll
            for (int n = half; n < 4; n += 2)
#pragma unroll
                for (int u = 0; u < 2; u++)
                    sts64(a + (m < 4 ? (8 * n + u) * 2048 + n * 32 : (8 * n + u) * 1024),
                          __byte_perm(ea[2 * n], e1[2 * n], u ? 0x7632 : 0x5410),
                          __byte_perm(ea[2 * n + 1], e1[2 * n + 1], u ? 0x7632 : 0x5410));
        };
        auto z_pair = [&](int m, uint32_t a, uint32_t b) {
            asm volatile("{.reg .pred p; setp.eq.u32 p, %4, %5; @p prmt.b32 %0, %2, %3, 0x5410; @p prmt.b32 %1, %2, %3, 0x7632;}"
                         : "+r"(zq[2 * (m >> 2)]), "+r"(zq[2 * (m >> 2) + 1])
                         : "r"(a), "r"(b), "r"(t), "r"(m & 3));
        };

        TS(29);
        mbar_wait(sb + BAR_FULL + w * 8);
        CP_WAIT(2);
        while (clock32() - t_start < START_MIN) {
        }
        if (w == 1) {
            asm volatile("bar.arrive 6, 256;" ::: "memory");
            asm volatile("bar.sync 5, 256;" ::: "memory");
        }
#pragma unroll
        for (int i = 0; i < 13; i++) {
            const uint64_t da = dA + (xpair(i) >> 4) + ((uint64_t)i << 16);
            dBlo += (uint32_t)(w ? wl(2 * i + 1) - (i ? wl(2 * i - 1) : 0) : wl(2 * i) - (i ? wl(2 * i - 2) : 0)) *
                    (uint32_t)((SLOT << 12) - (SLOT >> 3));
            const uint64_t db = mkdesc(0, 0, 1024, 1) | dBlo;
            TS(i);
            WG_FENCE();
            wgmma_ss_n168_acc(acc, da, db + w * 256);
            wgmma_ss_n168_acc(acc, da + 2, db + w * 256 + 128);
            wgmma_ss_n168_acc(acc, da + 4, db + (w ^ 1) * 256);
            wgmma_ss_n168_acc(acc, da + 6, db + (w ^ 1) * 256 + 128);
            WG_COMMIT();
            if (i == 0) {
                if (w == 0) {
                    asm volatile("bar.arrive 5, 256;" ::: "memory");
                    asm volatile("bar.sync 6, 256;" ::: "memory");
                }
            } else {
                mbar_wait(sb + bdone(2 * i - 2) + (w ^ 1) * 8, bpar(2 * i - 2));
            }
            if (i < 10) gather(i + 3);
            if (i == 12) mbar_wait(sb + BAR_SE);
            lift(i);
            if (i == 10 || i == 11) mbar_wait(sb + bdone(2 * i - 2) + w * 8, bpar(2 * i - 2));
            if (i >= 2 && !(i & 1)) {
                z_pair((i - 2) >> 1, e0[8], e1[8]);
                store_pair((i - 2) >> 1, 0, e0);
#pragma unroll
                for (int k = 0; k < 8; k++) e2[k] = e0[k];
            } else if (i >= 3) {
                store_pair((i - 3) >> 1, 1, e2);
            }
            const uint32_t rdy = i < 12 ? mbar_test(sb + bfull(2 * i + 2) + w * 8, bpar(2 * i + 2)) : 0;
            WG_WAIT0();
            pin(acc);
            if (i == 12) TS(13);
            if (i == 0) TS(27);
            if (i < 10) CP_WAIT(2);
            else if (i == 10) CP_WAIT(1);
            else if (i == 11) CP_WAIT(0);
            if (i < 12 && lane == 0) mbar_arrive(sb + bdone(2 * i) + w * 8);
#pragma unroll
            for (int k = 0; k < 9; k++) {
                const int k0 = 64 + 2 * (k & 5) + ((k >> 1) & 1);
                const uint32_t v = k == 8 ? pack(acc[80], acc[82]) : i < 12 ? pack(acc[64 + 2 * k], acc[65 + 2 * k]) : pack(acc[k0], acc[k0 + 4]);
                if (i & 1) e1[k] = v;
                else e0[k] = v;
            }
            if (i < 12) {
#pragma unroll
                for (int k = 64; k < 83; k++)
                    if (k != 81) asm volatile("mov.b32 %0, %1;" : "+f"(acc[k]) : "r"(zero));
                mbar_wait_unless(rdy, sb + bfull(2 * i + 2) + w * 8, bpar(2 * i + 2));
            } else {
                z_pair(6, e0[8], 0);
                sts128(sb + ZQOFF + w * 2048 + t128 * 16, zq[0], zq[1], zq[2], zq[3]);
                asm volatile("bar.arrive 2, 384;" ::: "memory");
            }
        }
        TS(14);

        uint32_t ai[8];
        float rd[4] = {0.f, 0.f, 0.f, 0.f};
        float th[32];
        uint32_t hw[2][4];
        auto deep_issue = [&](int k2) {
            if (!(k2 & 1)) lds128(hw[k2 >> 1], sb + W2OFF + w * 128 + t * 16 + k2 * 32);
#pragma unroll
            for (int k = 8 * k2; k < 8 * k2 + 8; k++) th[k] = gelu_tanh(acc[k]);
        };
        uint32_t h[4];
        auto deep_use = [&](int k2) {
#pragma unroll
            for (int c = 0; c < 4; c++) {
                const int k = 8 * k2 + 2 * c;
                h[c] = pack(ffma(acc[k], th[k], acc[k]), ffma(acc[k + 1], th[k + 1], acc[k + 1]));
            }
            if (k2 < 3) mma16816(rd, h, hw[k2 >> 1][2 * (k2 & 1)], hw[k2 >> 1][2 * (k2 & 1) + 1]);
        };
        auto deep_send = [&](int k0, int k1) {
#pragma unroll
            for (int k = k0; k < k1; k++)
                sts128(sb + EXOFF + w * SLOT + t128 * 16 + k * 2048, pack(acc[32 + 8 * k], acc[33 + 8 * k]),
                       pack(acc[34 + 8 * k], acc[35 + 8 * k]), pack(acc[36 + 8 * k], acc[37 + 8 * k]), pack(acc[38 + 8 * k], acc[39 + 8 * k]));
        };
        uint32_t o[4][4];
        auto deep_recv = [&](int k0, int k1) {
#pragma unroll
            for (int k = k0; k < k1; k++) lds128(o[k], sb + EXOFF + (w ^ 1) * SLOT + t128 * 16 + k * 2048);
        };
        auto deep_add = [&](int k0, int k1) {
            const uint32_t eye = (g >> 1) == t ? ((g & 1) ? 0x3f800000u : 0x3f80u) : 0u;
#pragma unroll
            for (int k = 2 * k0; k < 2 * k1; k++)
                asm volatile("mma.sync.aligned.m16n8k8.row.col.f32.bf16.bf16.f32 {%0,%1,%2,%3}, {%4,%5}, {%6}, {%0,%1,%2,%3};"
                             : "+f"(acc[4 * k]), "+f"(acc[4 * k + 1]), "+f"(acc[4 * k + 2]), "+f"(acc[4 * k + 3])
                             : "r"(o[k >> 1][2 * (k & 1)]), "r"(o[k >> 1][2 * (k & 1) + 1]), "r"(eye));
        };
        auto store_last = [&]() {
#pragma unroll
            for (int n = 0; n < 4; n++) sts64(sb + COFF + w * 4096 + n * 1024 + (t128 ^ w) * 8, e0[2 * n], e0[2 * n + 1]);
            store_pair(5, 1, e2);
        };
        const uint32_t la = (sb + AOFF + w * (16 * 2048 + 64) + (wq * 32 + g * 4 + (t ^ (g & 2))) * 16);
        const uint32_t lb = (sb + BOFF + w * (16 * 1024) + t128 * 8);
        const uint32_t lc0 = (sb + COFF + (t & 1) * (4096 + 8) + w * 2048 + (wq * 8 + g) * 32), lc1 = lc0 ^ 8;
        uint32_t Ap[2][2][4];
        auto load_a = [&](int s) {
            const int e = estep(s);
            lds128(Ap[s & 1][0], la + e * 2048 + (e >> 2) * 16);
            lds64(Ap[s & 1][1][0], Ap[s & 1][1][1], (lb ^ ((e & 6) * 4)) + e * 1024);
            if (!(s & 2)) lds64(Ap[s & 1][1][2], Ap[s & 1][1][3], ((e & 2) ? lc1 : lc0) + (e & 1) * 1024 + (e & 4) * 4);
        };
        {
            uint32_t v[2][4];
            deep_send(0, 2);
            asm volatile("bar.sync 1, 256;" ::: "memory");
            deep_recv(0, 2);
            deep_send(2, 4);
            TS(15);
            deep_add(0, 2);
            deep_issue(0);
            asm volatile("bar.sync 1, 256;" ::: "memory");
            deep_recv(2, 4);
            SCHED_FENCE();
            deep_add(2, 4);
            TS(16);
            deep_issue(1);
            deep_use(0);
            store_last();
            SCHED_FENCE();
            TS(17);
            deep_issue(2);
            deep_use(1);
            SCHED_FENCE();
            deep_use(2);
            TS(18);
            asm volatile("bar.sync 3, 384;" ::: "memory");
            lds128(v[0], sb + GOFF + t128 * 16);
            lds128(v[1], sb + GOFF + 2048 + t128 * 16);
            load_a(0);
            load_a(1);
            deep_issue(3);
#pragma unroll
            for (int k = 0; k < 8; k++) ai[k] = v[k >> 2][k & 3];
        }
        TS(19);

        uint32_t fin_a, tid2;
        float sum0, sum1;
        const uint32_t hi2 = lb & 16;
        {
            uint64_t dW[4];
#pragma unroll
            for (int k = 0; k < 4; k++) dW[k] = mkdesc(sb + w * 4096, 16, 512, 2) + ((uint64_t)zero << 32) + (wcslot(0) >> 4) + (k >> 1) * 128 + (k & 1) * 2;
            uint32_t Aq[2][2][4], pq[13], gate[13];
            float S[2][2][16];
            auto scale_a = [&](int s) {
#pragma unroll
                for (int k = 0; k < ((s & 2) ? 6 : 8); k++)
                    Aq[s & 1][k >> 2][k & 3] = hmul2(Ap[s & 1][k >> 2][k & 3], ai[k < 4 ? k ^ (estep(s) & 2) : k]);
            };
            auto sbuf = [](int s) { return s <= DB0 ? 0 : (s - DB0) & 1; };
            auto issue = [&](int s) {
                const bool first = s == 0 || s == DB0 + 1;
                WG_FENCE();
                if (first) wgmma_rs_n32_set(S[sbuf(s)][0], Ap[s & 1][0], dW[0]);
                else wgmma_rs_n32_pred(S[sbuf(s)][0], Ap[s & 1][0], dW[0], zero);
                wgmma_rs_n32_acc(S[sbuf(s)][0], Ap[s & 1][1], dW[1]);
                if (first) wgmma_rs_n32_set(S[sbuf(s)][1], Aq[s & 1][0], dW[2]);
                else wgmma_rs_n32_pred(S[sbuf(s)][1], Aq[s & 1][0], dW[2], zero);
                wgmma_rs_n32_acc(S[sbuf(s)][1], Aq[s & 1][1], dW[3]);
                WG_COMMIT();
                if (s <= DB0) SCHED_FENCE();
                if (s < 15) {
#pragma unroll
                    for (int k = 0; k < 4; k++)
                        asm volatile("add.s64 %0, %0, %1;" : "+l"(dW[k]) : "l"((int64_t)((wcslot(s + 1) - wcslot(s)) / 16)));
                }
            };
            scale_a(0);
            issue(0);
            deep_use(3);
            scale_a(1);
            SCHED_FENCE();
#pragma unroll
            for (int e = 0; e < 16; e++) {
                if (e >= DB0 && e < 15) {
                    issue(e + 1);
                    WG_WAIT1();
                } else {
                    WG_WAIT0();
                }
                pin(S[sbuf(e)][0]);
                pin(S[sbuf(e)][1]);
                if (e == 0 && (lb & 0xf8) == 0) mbar_arrive(sb + BAR_TD);
                if (e == 0) TS(20);
                if (e + 2 < 16) load_a(e + 2);
#pragma unroll
                for (int q = 0; q < 13; q++) {
                    const int ix = 4 * (q >> 2) + 2 * (q & 1) + ((q >> 1) & 1);
                    uint32_t v = pack(S[sbuf(e)][0][ix], S[sbuf(e)][1][ix ^ 1]);
                    if (q == 12)
                        asm volatile("{.reg .pred p; setp.ne.u32 p, %3, 0; @p cvt.rn.bf16x2.f32 %0, %2, %1;}"
                                     : "+r"(v)
                                     : "f"(S[sbuf(e)][0][14]), "f"(S[sbuf(e)][1][15]), "r"(hi2));
                    const uint32_t x = X[q][(e >> 1) & 1][e >> 2];
                    pq[q] = (e & 1) ? hfma2_bcast<1>(v, x, pq[q]) : hfma2_bcast<0>(v, x, e ? pq[q] : 0u);
                }
                if (e < DB0) issue(e + 1);
                if (e == 13) {
                    asm volatile("mov.u32 %0, %%tid.x;" : "=r"(tid2));
                    fin_a = sb + PARTOFF + (tid2 >> 5) * 64 + (tid2 & 28) + ((tid2 ^ (tid2 >> 3)) & 3) * 512;
                }
                if (e == 14) {
#pragma unroll
                    for (int q = 0; q < 13; q++)
                        asm volatile("prmt.b32 %0, %1, 0x3f80, %2;"
                                     : "=r"(gate[q])
                                     : "r"(q < 12 ? ai[2 * (q >> 2) + (q & 1)] : hi2 ? ai[7] : ai[6]), "r"((q & 2) ? 0x3254 : 0x1054));
                }
                if (e + 2 < 16) scale_a(e + 2);
                if (e == 3 || e == 6 || e == 9) mbar_wait(sb + BAR_WC + (e / 3 + 2) * 8);
                else if (e < 15) SCHED_FENCE();
                if (e == 7) TS(21);
            }
            float r0[4] = {0.f, 0.f, 0.f, 0.f}, r1[4] = {0.f, 0.f, 0.f, 0.f}, r2[4] = {rd[0], rd[0], rd[2], rd[2]};
            mma16816(r2, h, hw[1][2], hw[1][3]);
#pragma unroll
            for (int c = 0; c < 3; c++) {
                const uint32_t a[4] = {pq[4 * c], pq[4 * c + 1], pq[4 * c + 2], pq[4 * c + 3]};
                mma16816(r0, a, gate[4 * c], gate[4 * c + 2]);
                mma16816(r1, a, gate[4 * c + 1], gate[4 * c + 3]);
            }
            asm volatile("mma.sync.aligned.m16n8k8.row.col.f32.bf16.bf16.f32 {%0,%1,%2,%3}, {%4,%5}, {%6}, {%0,%1,%2,%3};"
                         : "+f"(r2[0]), "+f"(r2[1]), "+f"(r2[2]), "+f"(r2[3])
                         : "r"(hi2 ? 0u : pq[12]), "r"(hi2 ? pq[12] : 0u), "r"(gate[12]));
            sum0 = (tid2 & 4) ? r0[1] + r2[1] : r0[0] + r2[0];
            sum1 = (tid2 & 4) ? r1[3] + r2[3] : r1[2] + r2[2];
        }
        TS(22);
        {
            asm volatile("st.shared.f32 [%0], %1; st.shared.f32 [%0 + 32], %2;" ::"r"(fin_a), "f"(sum0), "f"(sum1) : "memory");
            asm volatile("bar.arrive 4, 288;" ::: "memory");
            if (wq == 0) TS_DUMP(w);
        }
    }
}

typedef CUresult (*EncodeFn)(CUtensorMap*, CUtensorMapDataType, cuuint32_t, void*, const cuuint64_t*, const cuuint64_t*,
                             const cuuint32_t*, const cuuint32_t*, CUtensorMapInterleave, CUtensorMapSwizzle,
                             CUtensorMapL2promotion, CUtensorMapFloatOOBfill);

}

extern "C" void kernel_launch(void* const* d_in, const int* in_sizes, int n_in, void* d_out, int out_size) {
    static EncodeFn encode = nullptr;
    if (!encode) {
        void* fn = nullptr;
        cudaDriverEntryPointQueryResult qr;
        cudaGetDriverEntryPoint("cuTensorMapEncodeTiled", &fn, cudaEnableDefault, &qr);
        encode = (EncodeFn)fn;
        cudaFuncSetAttribute(fibinet_kernel, cudaFuncAttributeMaxDynamicSharedMemorySize, SMEM_BYTES);
    }
    CUtensorMap tm;
    const cuuint64_t gd[2] = {NH, NF * ND};
    const cuuint64_t gs[1] = {NH * 2};
    const cuuint32_t bd[2] = {64, 64}, es[2] = {1, 1};
    encode(&tm, CU_TENSOR_MAP_DATA_TYPE_BFLOAT16, 2, d_in[6], gd, gs, bd, es, CU_TENSOR_MAP_INTERLEAVE_NONE,
           CU_TENSOR_MAP_SWIZZLE_128B, CU_TENSOR_MAP_L2_PROMOTION_L2_256B, CU_TENSOR_MAP_FLOAT_OOB_FILL_NONE);
    CUtensorMap tb;
    const cuuint64_t gd2[2] = {ND, ND};
    const cuuint64_t gs2[1] = {ND * 2};
    encode(&tb, CU_TENSOR_MAP_DATA_TYPE_BFLOAT16, 2, d_in[4], gd2, gs2, bd, es, CU_TENSOR_MAP_INTERLEAVE_NONE,
           CU_TENSOR_MAP_SWIZZLE_128B, CU_TENSOR_MAP_L2_PROMOTION_L2_256B, CU_TENSOR_MAP_FLOAT_OOB_FILL_NONE);
    fibinet_kernel<<<NPREP + NMAIN, 384, SMEM_BYTES>>>(
        (const int*)d_in[0], (const uint4*)d_in[1], (const __nv_bfloat16*)d_in[2], (const __nv_bfloat16*)d_in[3],
        (const __nv_bfloat16*)d_in[5], (const unsigned char*)d_in[6], (const __nv_bfloat16*)d_in[7], (__nv_bfloat16*)d_out, tm, tb);
}
```

```cpp
#include <cuda_runtime.h>
#include <cuda_bf16.h>
#include <cuda.h>
#include <stdint.h>

namespace {

constexpr int NF = 26, ND = 64, NH = 256, NR = 13;
constexpr int NPREP = 4;
constexpr int NMAIN = 128;

constexpr int SLOT = 8192;
constexpr int ZOFF = 15 * SLOT;
__host__ __device__ constexpr int slot(int s) { return ZOFF - s * SLOT; }
constexpr int BOFF = ZOFF + SLOT;
constexpr int AOFF = BOFF + 32768;
constexpr int COFF = slot(12);
constexpr int MOFF = AOFF + 65536 + 128;
constexpr int BAR_FULL = MOFF, BAR_DONE = MOFF + 64, BAR_WC = MOFF + 128, BAR_SE = MOFF + 176, BAR_TD = MOFF + 184,
              BAR_Z = MOFF + 192;
__host__ __device__ constexpr int bfull(int f) { return BAR_FULL + (f & 7) * 8; }
__host__ __device__ constexpr int bdone(int f) { return BAR_DONE + (f & 7) * 8; }
__host__ __device__ constexpr int bpar(int f) { return (f >> 3) & 1; }
constexpr int W2OFF = MOFF + 256, SEOFF = MOFF + 768;
constexpr int PARTOFF = SEOFF;
constexpr int SMEM_BYTES = MOFF + 2944;
constexpr int XDELTA = 2 * SLOT;
__host__ __device__ constexpr int xpair(int i) {
    return (i & 3) == 0 ? slot(11) : (i & 3) == 1 ? BOFF : (i & 3) == 2 ? BOFF + SLOT : slot(15);
}
__host__ __device__ constexpr int wl(int f) { return f % 5 == 0 ? 1 : f % 5 == 4 ? 7 : f % 5 + 2; }
__host__ __device__ constexpr int wcslot(int c) {
    return c == 0 ? slot(3) : c == 1 ? slot(8) : c == 2 ? slot(10) : c == 3 ? slot(15) : c == 4 ? slot(13)
         : c == 5 ? slot(11) : c == 6 ? slot(9) : c == 7 ? slot(14) : c == 8 ? slot(7) : c == 9 ? slot(2)
         : c == 10 ? slot(1) : c == 11 ? slot(4) : c == 12 ? slot(5) : c == 13 ? slot(6) : c == 14 ? ZOFF : slot(3);
}
__host__ __device__ constexpr int wcfirst(int gi) { return gi < 3 ? gi : gi == 3 ? 5 : gi == 4 ? 8 : gi == 5 ? 11 : 16; }
constexpr int EXOFF = slot(5);
constexpr int ZQOFF = slot(6);
constexpr int GOFF = ZQOFF + 4096;

__device__ uint4 g_wc[2 * 16 * 8192 / 16];
__device__ uint4 g_se[2048 / 16];
__device__ uint4 g_w2[NH / 8];
__device__ unsigned g_ready;
__device__ unsigned g_seen;

__host__ __device__ constexpr int fieldof(int f) { return f < 24 ? 4 * (f >> 2) + 2 * (f & 1) + ((f >> 1) & 1) : f; }
__device__ __forceinline__ int fmap(int n) { return n < 24 ? n : 24 + ((n >> 1) & 1); }
__host__ __device__ constexpr int estep(int s) { return (s & 1) + 2 * (s >> 2) + 4 * (s & 2); }

__device__ __forceinline__ uint64_t mkdesc(uint32_t addr, uint32_t lbo, uint32_t sbo, int sw) {
    return (uint64_t)((addr & 0x3ffff) >> 4) | ((uint64_t)(lbo >> 4) << 16) | ((uint64_t)(sbo >> 4) << 32) |
           ((uint64_t)sw << 62);
}
__device__ __forceinline__ void mbar_init(uint32_t b, uint32_t n) {
    asm volatile("mbarrier.init.shared.b64 [%0], %1;" ::"r"(b), "r"(n) : "memory");
}
__device__ __forceinline__ void mbar_wait(uint32_t b, uint32_t par = 0) {
    asm volatile(
        "{\n.reg .pred p, q;\n.reg .u32 n;\n"
        "mbarrier.try_wait.parity.shared.b64 p, [%0], %1;\n@p bra.uni WD%=;\nmov.u32 n, 0;\n"
        "WL%=:\nmbarrier.try_wait.parity.shared.b64 p, [%0], %1;\n@p bra.uni WD%=;\n"
        "add.u32 n, n, 1;\nsetp.lt.u32 q, n, 4000000;\n@q bra.uni WL%=;\nWD%=:\n}\n" ::"r"(b), "r"(par)
        : "memory");
}
__device__ __forceinline__ uint32_t mbar_test(uint32_t b, uint32_t par) {
    uint32_t ok;
    asm volatile("{.reg .pred p; mbarrier.test_wait.parity.shared.b64 p, [%1], %2; selp.u32 %0, 1, 0, p;}"
                 : "=r"(ok)
                 : "r"(b), "r"(par)
                 : "memory");
    return ok;
}
__device__ __forceinline__ void mbar_wait_unless(uint32_t ok, uint32_t b, uint32_t par) {
    asm volatile(
        "{\n.reg .pred p, q;\n.reg .u32 n;\n"
        "setp.ne.u32 p, %1, 0;\n@p bra.uni WD%=;\nmov.u32 n, 0;\n"
        "WL%=:\nmbarrier.try_wait.parity.shared.b64 p, [%0], %2;\n@p bra.uni WD%=;\n"
        "add.u32 n, n, 1;\nsetp.lt.u32 q, n, 4000000;\n@q bra.uni WL%=;\nWD%=:\n}\n" ::"r"(b), "r"(ok), "r"(par)
        : "memory");
}
__device__ __forceinline__ void mbar_arrive(uint32_t b) {
    asm volatile("mbarrier.arrive.shared.b64 _, [%0];" ::"r"(b) : "memory");
}
__device__ __forceinline__ void mbar_expect(uint32_t b, uint32_t bytes) {
    asm volatile("mbarrier.arrive.expect_tx.shared.b64 _, [%0], %1;" ::"r"(b), "r"(bytes) : "memory");
}
__device__ __forceinline__ uint32_t opaque(uint32_t v) { return __shfl_sync(0xffffffffu, v, threadIdx.x); }
__device__ __forceinline__ bool elect() {
    uint32_t p;
    asm volatile("{.reg .pred q; elect.sync _|q, 0xffffffff; selp.u32 %0, 1, 0, q;}" : "=r"(p));
    return p;
}
__device__ __forceinline__ void tma2d(uint32_t dst, const CUtensorMap* m, uint32_t bar, int x, int y) {
    asm volatile(
        "cp.async.bulk.tensor.2d.shared::cluster.global.mbarrier::complete_tx::bytes [%0], [%1, {%3, %4}], [%2];" ::"r"(dst),
        "l"(m), "r"(bar), "r"(x), "r"(y)
        : "memory");
}
__device__ __forceinline__ void bulk(uint32_t dst, const void* src, uint32_t bytes, uint32_t bar) {
    asm volatile("cp.async.bulk.shared::cluster.global.mbarrier::complete_tx::bytes [%0], [%1], %2, [%3];" ::"r"(dst),
                 "l"(src), "r"(bytes), "r"(bar)
                 : "memory");
}
__device__ __forceinline__ void cp16(uint32_t dst, const void* src) {
    asm volatile("cp.async.cg.shared.global [%0], [%1], 16;" ::"r"(dst), "l"(src) : "memory");
}
__device__ __forceinline__ void lds128(uint32_t (&v)[4], uint32_t a) {
    asm volatile("ld.shared.v4.u32 {%0,%1,%2,%3}, [%4];" : "=r"(v[0]), "=r"(v[1]), "=r"(v[2]), "=r"(v[3]) : "r"(a) : "memory");
}
__device__ __forceinline__ void lds128_if(uint32_t (&v)[4], uint32_t a, uint32_t p) {
    asm volatile("{.reg .pred q; setp.ne.u32 q, %5, 0; @q ld.shared.v4.u32 {%0,%1,%2,%3}, [%4];}"
                 : "+r"(v[0]), "+r"(v[1]), "+r"(v[2]), "+r"(v[3])
                 : "r"(a), "r"(p)
                 : "memory");
}
__device__ __forceinline__ void lds64(uint32_t& x, uint32_t& y, uint32_t a) {
    asm volatile("ld.shared.v2.u32 {%0,%1}, [%2];" : "=r"(x), "=r"(y) : "r"(a) : "memory");
}
__device__ __forceinline__ void sts128(uint32_t a, uint32_t x, uint32_t y, uint32_t z, uint32_t w) {
    asm volatile("st.shared.v4.u32 [%0], {%1,%2,%3,%4};" ::"r"(a), "r"(x), "r"(y), "r"(z), "r"(w) : "memory");
}
__device__ __forceinline__ void sts64(uint32_t a, uint32_t x, uint32_t y) {
    asm volatile("st.shared.v2.u32 [%0], {%1,%2};" ::"r"(a), "r"(x), "r"(y) : "memory");
}
__device__ __forceinline__ uint32_t pack(float lo, float hi) {
    uint32_t r;
    asm volatile("cvt.rn.bf16x2.f32 %0, %1, %2;" : "=r"(r) : "f"(hi), "f"(lo));
    return r;
}
__device__ __forceinline__ uint32_t hmul2(uint32_t a, uint32_t b) {
    uint32_t r;
    asm volatile("mul.rn.bf16x2 %0, %1, %2;" : "=r"(r) : "r"(a), "r"(b));
    return r;
}
template <int H>
__device__ __forceinline__ uint32_t hfma2_bcast(uint32_t a, uint32_t x, uint32_t c) {
    uint32_t r;
    if (H)
        asm volatile("{.reg .b16 l, h; .reg .b32 s; mov.b32 {l, h}, %2; mov.b32 s, {h, h}; fma.rn.bf16x2 %0, %1, s, %3;}"
                     : "=r"(r)
                     : "r"(a), "r"(x), "r"(c));
    else
        asm volatile("{.reg .b16 l, h; .reg .b32 s; mov.b32 {l, h}, %2; mov.b32 s, {l, l}; fma.rn.bf16x2 %0, %1, s, %3;}"
                     : "=r"(r)
                     : "r"(a), "r"(x), "r"(c));
    return r;
}
__device__ __forceinline__ float ffma(float a, float b, float c) {
    float r;
    asm volatile("fma.rn.f32 %0, %1, %2, %3;" : "=f"(r) : "f"(a), "f"(b), "f"(c));
    return r;
}
__device__ __forceinline__ float tanh_fast(float x) {
    float r;
    asm volatile("tanh.approx.f32 %0, %1;" : "=f"(r) : "f"(x));
    return r;
}
__device__ __forceinline__ float gelu_tanh(float x) {
    float r;
    asm volatile(
        "{.reg .f32 a; mul.f32 a, %1, %1; fma.rn.f32 a, a, 0f3D122279, 0f3F4C422A; mul.f32 a, a, %1; tanh.approx.f32 %0, a;}"
        : "=f"(r)
        : "f"(x));
    return r;
}
__device__ __forceinline__ void mma16816(float (&d)[4], const uint32_t (&a)[4], uint32_t b0, uint32_t b1) {
    asm volatile("mma.sync.aligned.m16n8k16.row.col.f32.bf16.bf16.f32 {%0,%1,%2,%3}, {%4,%5,%6,%7}, {%8,%9}, {%0,%1,%2,%3};"
                 : "+f"(d[0]), "+f"(d[1]), "+f"(d[2]), "+f"(d[3])
                 : "r"(a[0]), "r"(a[1]), "r"(a[2]), "r"(a[3]), "r"(b0), "r"(b1));
}
__device__ __forceinline__ uint32_t clock32() {
    uint32_t c;
    asm volatile("mov.u32 %0, %%clock;" : "=r"(c)::"memory");
    return c;
}
#define WG_FENCE() asm volatile("wgmma.fence.sync.aligned;" ::: "memory")
#define WG_COMMIT() asm volatile("wgmma.commit_group.sync.aligned;" ::: "memory")
#define WG_WAIT0() asm volatile("wgmma.wait_group.sync.aligned 0;" ::: "memory")
#define WG_WAIT1() asm volatile("wgmma.wait_group.sync.aligned 1;" ::: "memory")
#define CP_COMMIT() asm volatile("cp.async.commit_group;" ::: "memory")
#define CP_WAIT(n) asm volatile("cp.async.wait_group %0;" ::"n"(n) : "memory")
#define SCHED_FENCE() asm volatile("pmevent 0;" ::: "memory")
#define PROXY_FENCE() asm volatile("fence.proxy.async.shared::cta;" ::: "memory")
template <int N>
__device__ __forceinline__ void pin(float (&d)[N]) {
#pragma unroll
    for (int i = 0; i < N; i++) asm volatile("" : "+f"(d[i])::"memory");
}
#define TS(k)
#define TS_DUMP(role)

__device__ __forceinline__ void wgmma_ss_n168_acc(float (&d)[84], uint64_t da, uint64_t db) {
    asm volatile(
        "wgmma.mma_async.sync.aligned.m64n168k16.f32.bf16.bf16 "
        "{%0,%1,%2,%3,%4,%5,%6,%7,%8,%9,%10,%11,%12,%13,%14,%15,"
        "%16,%17,%18,%19,%20,%21,%22,%23,%24,%25,%26,%27,%28,%29,%30,%31,"
        "%32,%33,%34,%35,%36,%37,%38,%39,%40,%41,%42,%43,%44,%45,%46,%47,"
        "%48,%49,%50,%51,%52,%53,%54,%55,%56,%57,%58,%59,%60,%61,%62,%63,"
        "%64,%65,%66,%67,%68,%69,%70,%71,%72,%73,%74,%75,%76,%77,%78,%79,"
        "%80,%81,%82,%83}, "
        "%84, %85, 1, 1, 1, 0, 1;"
        : "+f"(d[0]), "+f"(d[1]), "+f"(d[2]), "+f"(d[3]), "+f"(d[4]), "+f"(d[5]), "+f"(d[6]), "+f"(d[7]),
          "+f"(d[8]), "+f"(d[9]), "+f"(d[10]), "+f"(d[11]), "+f"(d[12]), "+f"(d[13]), "+f"(d[14]), "+f"(d[15]),
          "+f"(d[16]), "+f"(d[17]), "+f"(d[18]), "+f"(d[19]), "+f"(d[20]), "+f"(d[21]), "+f"(d[22]), "+f"(d[23]),
          "+f"(d[24]), "+f"(d[25]), "+f"(d[26]), "+f"(d[27]), "+f"(d[28]), "+f"(d[29]), "+f"(d[30]), "+f"(d[31]),
          "+f"(d[32]), "+f"(d[33]), "+f"(d[34]), "+f"(d[35]), "+f"(d[36]), "+f"(d[37]), "+f"(d[38]), "+f"(d[39]),
          "+f"(d[40]), "+f"(d[41]), "+f"(d[42]), "+f"(d[43]), "+f"(d[44]), "+f"(d[45]), "+f"(d[46]), "+f"(d[47]),
          "+f"(d[48]), "+f"(d[49]), "+f"(d[50]), "+f"(d[51]), "+f"(d[52]), "+f"(d[53]), "+f"(d[54]), "+f"(d[55]),
          "+f"(d[56]), "+f"(d[57]), "+f"(d[58]), "+f"(d[59]), "+f"(d[60]), "+f"(d[61]), "+f"(d[62]), "+f"(d[63]),
          "+f"(d[64]), "+f"(d[65]), "+f"(d[66]), "+f"(d[67]), "+f"(d[68]), "+f"(d[69]), "+f"(d[70]), "+f"(d[71]),
          "+f"(d[72]), "+f"(d[73]), "+f"(d[74]), "+f"(d[75]), "+f"(d[76]), "+f"(d[77]), "+f"(d[78]), "+f"(d[79]),
          "+f"(d[80]), "+f"(d[81]), "+f"(d[82]), "+f"(d[83])
        : "l"(da), "l"(db));
}

__device__ __forceinline__ void wgmma_rs_n32_set(float (&d)[16], const uint32_t (&a)[4], uint64_t db) {
    asm volatile(
        "wgmma.mma_async.sync.aligned.m64n32k16.f32.bf16.bf16 "
        "{%0,%1,%2,%3,%4,%5,%6,%7,%8,%9,%10,%11,%12,%13,%14,%15}, "
        "{%16,%17,%18,%19}, %20, 0, 1, 1, 0;"
        : "=f"(d[0]), "=f"(d[1]), "=f"(d[2]), "=f"(d[3]), "=f"(d[4]), "=f"(d[5]), "=f"(d[6]), "=f"(d[7]),
          "=f"(d[8]), "=f"(d[9]), "=f"(d[10]), "=f"(d[11]), "=f"(d[12]), "=f"(d[13]), "=f"(d[14]), "=f"(d[15])
        : "r"(a[0]), "r"(a[1]), "r"(a[2]), "r"(a[3]), "l"(db));
}

__device__ __forceinline__ void wgmma_rs_n32_acc(float (&d)[16], const uint32_t (&a)[4], uint64_t db) {
    asm volatile(
        "wgmma.mma_async.sync.aligned.m64n32k16.f32.bf16.bf16 "
        "{%0,%1,%2,%3,%4,%5,%6,%7,%8,%9,%10,%11,%12,%13,%14,%15}, "
        "{%16,%17,%18,%19}, %20, 1, 1, 1, 0;"
        : "+f"(d[0]), "+f"(d[1]), "+f"(d[2]), "+f"(d[3]), "+f"(d[4]), "+f"(d[5]), "+f"(d[6]), "+f"(d[7]),
          "+f"(d[8]), "+f"(d[9]), "+f"(d[10]), "+f"(d[11]), "+f"(d[12]), "+f"(d[13]), "+f"(d[14]), "+f"(d[15])
        : "r"(a[0]), "r"(a[1]), "r"(a[2]), "r"(a[3]), "l"(db));
}

__device__ __forceinline__ void wgmma_rs_n16_set(float (&d)[8], const uint32_t (&a)[4], uint64_t db) {
    asm volatile(
        "wgmma.mma_async.sync.aligned.m64n16k16.f32.bf16.bf16 "
        "{%0,%1,%2,%3,%4,%5,%6,%7}, "
        "{%8,%9,%10,%11}, %12, 0, 1, 1, 0;"
        : "=f"(d[0]), "=f"(d[1]), "=f"(d[2]), "=f"(d[3]), "=f"(d[4]), "=f"(d[5]), "=f"(d[6]), "=f"(d[7])
        : "r"(a[0]), "r"(a[1]), "r"(a[2]), "r"(a[3]), "l"(db));
}

__device__ __forceinline__ void wgmma_rs_n32_pred(float (&d)[16], const uint32_t (&a)[4], uint64_t db, uint32_t scale_d) {
    asm volatile(
        "{.reg .pred p; setp.ne.u32 p, %21, 0; wgmma.mma_async.sync.aligned.m64n32k16.f32.bf16.bf16 "
        "{%0,%1,%2,%3,%4,%5,%6,%7,%8,%9,%10,%11,%12,%13,%14,%15}, "
        "{%16,%17,%18,%19}, %20, p, 1, 1, 0;}"
        : "+f"(d[0]), "+f"(d[1]), "+f"(d[2]), "+f"(d[3]), "+f"(d[4]), "+f"(d[5]), "+f"(d[6]), "+f"(d[7]),
          "+f"(d[8]), "+f"(d[9]), "+f"(d[10]), "+f"(d[11]), "+f"(d[12]), "+f"(d[13]), "+f"(d[14]), "+f"(d[15])
        : "r"(a[0]), "r"(a[1]), "r"(a[2]), "r"(a[3]), "l"(db), "r"(scale_d));
}

__device__ __forceinline__ void prep_cta(uint32_t sb, int c, const __nv_bfloat16* __restrict__ wc,
                                         const __nv_bfloat16* __restrict__ se1, const __nv_bfloat16* __restrict__ se2,
                                         const __nv_bfloat16* __restrict__ w2) {
    const int tid = threadIdx.x, lane = tid & 31, warp = tid >> 5, s = c >> 1;
    constexpr int ZERO = 16 * NF * 128;
#pragma unroll
    for (int q = tid; q < 16 * NF * 8; q += 384) {
        const int i = q >> 7, nn = (q >> 3) & 15, j = fmap((16 * (c & 1) + nn) ^ s);
        cp16(sb + (q >> 3) * 128 + (((q & 7) ^ (i & 1) ^ ((i >> 3) << 1)) << 4), wc + ((s * NF + i) * NF + j) * ND + (q & 7) * 8);
    }
    if (tid < 8) sts128(sb + ZERO + tid * 16, 0, 0, 0, 0);
    if (tid < 256) {
        const int n = ((tid >> 2) & 1) * 8 + (tid >> 5) + (s ? (c & 1) * 16 : 0);
        const int k = ((tid >> 1) & 1) * 8 + ((tid >> 3) & 3) * 2 + (tid & 1), mm = k >> 1, u = k & 1;
        const int f = s ? fmap(n) : mm < 6 ? 4 * mm + 2 * c + u : (mm == 6 && u == 0) ? 24 + c : -1;
        float v = 0.f;
        if (f >= 0 && (s ? k : n) < NR) v = __bfloat162float(s ? se2[k * NF + f] : se1[f * NR + n]);
        reinterpret_cast<__nv_bfloat16*>(g_se)[c * 256 + tid] = __float2bfloat16(s ? 0.5f * v : v);
    } else if (tid < 320) {
        const int q = tid - 256;
        reinterpret_cast<__nv_bfloat16*>(g_w2)[c * 64 + q] =
            __float2bfloat16(0.5f * __bfloat162float(w2[c * 64 + (q & 32) + 4 * (q & 6) + ((q >> 2) & 6) + (q & 1)]));
    }
    asm volatile("cp.async.wait_all;" ::: "memory");
    __syncthreads();
    const int k = 4 * (lane & 6) + 2 * (lane >> 3) + (lane & 1), i = fmap(k);
    const int g = lane >> 2, t = lane & 3;
#pragma unroll 4
    for (int task = warp; task < 128; task += 12) {
        const int nn = task & 15, eg = task >> 4, n = 16 * (c & 1) + nn;
        const uint32_t a = sb + (k < 28 ? (i * 16 + nn) * 128 : ZERO) + ((eg ^ (i & 1) ^ ((i >> 3) << 1)) << 4);
        uint4 v;
        asm volatile("ldmatrix.sync.aligned.m8n8.x4.trans.shared.b16 {%0,%1,%2,%3}, [%4];"
                     : "=r"(v.x), "=r"(v.y), "=r"(v.z), "=r"(v.w)
                     : "r"(a));
        if (t == 3) {
            const uint32_t mask = (eg & 1) ? 0xffff0000u : 0xffffu;
            v.x &= mask;
            v.y &= mask;
        }
        const int ch = (t < 2 ? t ^ ((g >> 1) & 1) : t) ^ ((n >> 1) & 3);
        const int step = (g & 1) + 2 * (eg & 1) + 2 * (g & 6);
        g_wc[(eg >> 2) * 8192 + step * 512 + ((eg >> 1) & 1) * 256 + s * 128 + n * 4 + ch] = v;
    }
    __threadfence();
    __syncthreads();
    if (tid == 0) atomicAdd(&g_ready, 1u);
}

#define PACE1 2250
#define PACE2 2850
#define START_MIN 3400
#define WDELAY 1600
#define WSTEP 500
#define WPF_AT 2600
#define WPF_STEP 800
#define POLL_AT 6500
#define T_SHIFT 300
constexpr int DB0 = 6;

__global__ void __cluster_dims__(2, 1, 1) __launch_bounds__(384, 1)
fibinet_kernel(const int* __restrict__ idx, const uint4* __restrict__ table,
               const __nv_bfloat16* __restrict__ se1, const __nv_bfloat16* __restrict__ se2,
               const __nv_bfloat16* __restrict__ wc,
               const unsigned char* __restrict__ w1, const __nv_bfloat16* __restrict__ w2, __nv_bfloat16* __restrict__ out,
               const __grid_constant__ CUtensorMap tm_w1, const __grid_constant__ CUtensorMap tm_bi) {
    extern __shared__ __align__(1024) unsigned char smem[];
    const int tid = threadIdx.x;
    const int cta = blockIdx.x - NPREP, grp = cta >> 1, rank = cta & 1, lane = tid & 31;
    uint32_t ids[13][4], cid[3][2];
    const uint32_t idle = (tid >> 8) | (cta < 0);
    const uint32_t row = ((tid >> 5) & 3) * 16 + (lane >> 3);
    const unsigned char* ib = reinterpret_cast<const unsigned char*>(idx) + (int64_t)grp * (64 * NF * 4);
    {
        const unsigned char* ip = ib + (row * (NF * 4) + ((tid >> 4) & 8));
#pragma unroll
        for (int u = 0; u < 4; u++) {
            ids[0][u] = ids[1][u] = 0;
            asm volatile("{.reg .pred p; setp.eq.u32 p, %3, 0; @p ld.global.nc.L2::128B.v2.u32 {%0,%1}, [%2];}"
                         : "+r"(ids[0][u]), "+r"(ids[1][u])
                         : "l"(ip + 16 * NF * u), "r"(idle));
        }
    }
    const uint32_t t_0 = clock32();
    {
        const uint32_t co = ((tid & 127) >> 1) * (NF * 4) + ((tid >> 4) & 8) + 16 + 16 * (tid & 1);
#pragma unroll
        for (int k = 0; k < 3; k++) {
            cid[k][0] = cid[k][1] = 0;
            asm volatile("{.reg .pred p; setp.eq.u32 p, %3, 0; @p ld.global.nc.v2.u32 {%0,%1}, [%2];}"
                         : "+r"(cid[k][0]), "+r"(cid[k][1])
                         : "l"(ib + (co + 32 * k - (k == 2 ? 8 * ((tid >> 7) & tid & 1) : 0))), "r"(idle));
        }
    }
    const uint32_t t_start = (t_0 ^ (clock32() & blockIdx.y)) - T_SHIFT;
    const uint32_t sb = (uint32_t)__cvta_generic_to_shared(smem);
    uint32_t gd0 = sb + (tid >> 7) * XDELTA + row * 128 + (((lane & 7) ^ (lane >> 3) ^ ((tid >> 5) & 4)) << 4);
    const uint4* tp = table + (lane & 7);
    auto gather = [&](int i) {
#pragma unroll
        for (int u = 0; u < 4; u++)
            asm volatile(
                "{.reg .u64 a; .reg .pred p; setp.eq.u32 p, %3, 0; mad.wide.u32 a, %2, 128, %1; @p cp.async.cg.shared.global [%0], [a], 16;}" ::"r"(
                    (gd0 ^ ((u & 1) * 64)) + xpair(i) + u * 512),
                "l"(tp), "r"(ids[i][u]), "r"(i == 0 ? idle : 0u)
                : "memory");
        CP_COMMIT();
    };
    gather(0);
    if (cta < 0) {
        prep_cta(sb, blockIdx.x, wc, se1, se2, w2);
        return;
    }
    if (tid == 288) asm volatile("prefetch.tensormap [%0];" ::"l"(&tm_w1));
    const int warp = __reduce_max_sync(0xffffffffu, tid >> 5);
    const int w = warp >> 2;

    if (w == 2) {
        asm volatile("setmaxnreg.dec.sync.aligned.u32 40;");
        auto load_wc = [&](int gi) {
            if (elect()) {
                const unsigned char* src = reinterpret_cast<const unsigned char*>(g_wc) + rank * 131072;
                mbar_expect(sb + BAR_WC + gi * 8, (wcfirst(gi + 1) - wcfirst(gi)) * 8192);
#pragma unroll
                for (int c = wcfirst(gi); c < wcfirst(gi + 1); c++) bulk(sb + wcslot(c), src + c * 8192, 8192, sb + BAR_WC + gi * 8);
            }
            __syncwarp();
        };
        if (warp == 8) {
            if (elect()) {
                mbar_init(sb + BAR_Z, 1);
                mbar_expect(sb + BAR_Z, 8192);
                tma2d(sb + ZOFF, &tm_bi, sb + BAR_Z, 32 * rank, 0);
            }
#pragma unroll
            for (int f = 0; f < 26; f++) {
                if (f == 2) {
                    if (elect()) {
#pragma unroll
                        for (int k = 2; k < 8; k++) mbar_init(sb + BAR_FULL + k * 8, 1);
                        asm volatile("fence.mbarrier_init.release.cluster;" ::: "memory");
                    }
                    __syncwarp();
                    asm volatile("barrier.cluster.arrive.relaxed.aligned;" ::: "memory");
                    mbar_wait(sb + BAR_Z);
#pragma unroll
                    for (int k = 0; k < 2; k++)
                        sts128(sb + ZOFF + (k * 32 + lane) * 128 + ((4 ^ (lane & 7)) << 4), 0x3c803c80u, 0x3c803c80u, 0x3c803c80u, 0x3c803c80u);
                    PROXY_FENCE();
                    asm volatile("bar.arrive 0, 384;" ::: "memory");
                    TS(31);
                }
                if (f == 5) asm volatile("bar.sync 7, 64;" ::: "memory");
                if (f >= 5) mbar_wait(sb + bdone(f - 5), bpar(f - 5));
                if (f >= 2 && f < 5)
                    while (clock32() - t_start < WDELAY + (f - 2) * WSTEP) {
                    }
                if (elect()) {
                    if (f < 2) mbar_init(sb + BAR_FULL + f * 8, 1);
                    mbar_expect(sb + bfull(f), 16384);
                    tma2d(sb + slot(2 * wl(f)), &tm_w1, sb + bfull(f), 128 * rank + 64 * (f & 1), fieldof(f) * 64);
                    tma2d(sb + slot(wl(f)), &tm_w1, sb + bfull(f), 128 * rank + 64 - 64 * (f & 1), fieldof(f) * 64);
                }
                TS(f);
            }
            asm volatile("bar.arrive 8, 128;" ::: "memory");
            TS_DUMP(2);
        } else if (warp == 9) {
            if (elect()) {
#pragma unroll
                for (int k = 0; k < 8; k++) mbar_init(sb + BAR_WC + k * 8, k < 7 ? 1 : 8);
                asm volatile("fence.mbarrier_init.release.cluster;" ::: "memory");
            }
            __syncwarp();
            asm volatile("barrier.cluster.arrive.relaxed.aligned;" ::: "memory");
            asm volatile("bar.sync 0, 384;" ::: "memory");
            while (clock32() - t_start < POLL_AT) __nanosleep(100);
            if (elect()) {
                unsigned v, it = 0;
                do {
                    asm volatile("ld.acquire.gpu.global.u32 %0, [%1];" : "=r"(v) : "l"(&g_ready) : "memory");
                } while (v < NPREP && ++it < 4000000u);
                asm volatile("fence.proxy.async.global;" ::: "memory");
                mbar_expect(sb + BAR_SE, 2048 + 256);
                bulk(sb + SEOFF, g_se, 2048, sb + BAR_SE);
                bulk(sb + W2OFF, g_w2 + rank * 16, 256, sb + BAR_SE);
            }
            __syncwarp();
            TS(0);
            asm volatile("bar.sync 8, 128;" ::: "memory");
#pragma unroll
            for (int gi = 0; gi < 3; gi++) {
                mbar_wait(sb + bdone(21 + gi), bpar(21 + gi));
                load_wc(gi);
                TS(1 + gi);
            }
        } else if (warp == 10) {
            if (elect()) {
#pragma unroll
                for (int k = 0; k < 8; k++) mbar_init(sb + BAR_DONE + k * 8, 4);
                asm volatile("fence.mbarrier_init.release.cluster;" ::: "memory");
            }
            __syncwarp();
            asm volatile("barrier.cluster.arrive.relaxed.aligned;" ::: "memory");
            asm volatile("bar.arrive 7, 64;" ::: "memory");
            asm volatile("bar.sync 0, 384;" ::: "memory");
#pragma unroll 1
            for (int k = 0; k < 7; k++) {
                while (clock32() - t_start < (uint32_t)(WPF_AT + k * WPF_STEP)) __nanosleep(150);
                if (lane < 6)
                    asm volatile("prefetch.global.L2 [%0];" ::"l"(w1 + (5 + k * 3 + (lane >> 1)) * 32768 + cta * 256 + (lane & 1) * 128));
            }
            asm volatile("bar.sync 8, 128;" ::: "memory");
        } else {
            asm volatile("bar.sync 0, 384;" ::: "memory");
            asm volatile("bar.sync 8, 128;" ::: "memory");
        }
        {
            uint32_t bw[2][4], z0[4], z1[4];
            mbar_wait(sb + BAR_SE);
            lds128(bw[0], sb + SEOFF + lane * 16);
            lds128(bw[1], sb + SEOFF + 512 + lane * 16);
            asm volatile("bar.sync 2, 384;" ::: "memory");
            lds128(z0, sb + ZQOFF + (tid & 127) * 16);
            lds128(z1, sb + ZQOFF + 2048 + (tid & 127) * 16);
            TS(8);
            float s[2][4] = {};
#pragma unroll
            for (int n = 0; n < 2; n++) {
                mma16816(s[n], z0, bw[0][2 * n], bw[0][2 * n + 1]);
                mma16816(s[n], z1, bw[1][2 * n], bw[1][2 * n + 1]);
            }
            lds128(bw[0], sb + SEOFF + 1024 + lane * 16);
            lds128(bw[1], sb + SEOFF + 1536 + lane * 16);
            float th[8];
#pragma unroll
            for (int k = 0; k < 8; k++) th[k] = gelu_tanh(s[k >> 2][k & 3]);
            SCHED_FENCE();
            TS(9);
            uint32_t gq[4];
#pragma unroll
            for (int k = 0; k < 4; k++)
                gq[k] = pack(s[k >> 1][2 * (k & 1)] * ffma(th[2 * k], 0.5f, 0.5f), s[k >> 1][2 * (k & 1) + 1] * ffma(th[2 * k + 1], 0.5f, 0.5f));
            float a[4][4] = {};
#pragma unroll
            for (int n = 0; n < 4; n++) mma16816(a[n], gq, bw[n >> 1][2 * (n & 1)], bw[n >> 1][2 * (n & 1) + 1]);
#pragma unroll
            for (int k = 0; k < 16; k++)
                if (k < 13 || k == 14) a[k >> 2][k & 3] = tanh_fast(a[k >> 2][k & 3]);
            SCHED_FENCE();
            TS(10);
            uint32_t ap[8];
#pragma unroll
            for (int k = 0; k < 8; k++)
                ap[k] = pack(ffma(a[k >> 1][2 * (k & 1)], 0.5f, 0.5f), ffma(a[k >> 1][2 * (k & 1) + (k < 6)], 0.5f, 0.5f));
            sts128(sb + GOFF + (tid & 127) * 16, ap[0], ap[1], ap[2], ap[3]);
            sts128(sb + GOFF + 2048 + (tid & 127) * 16, ap[4], ap[5], ap[6], ap[7]);
            if (warp != 9) mbar_wait(sb + BAR_WC + (warp == 8 ? 0 : warp - 9) * 8);
            asm volatile("bar.arrive 3, 384;" ::: "memory");
            TS(11);
        }
        if (warp == 9) {
            load_wc(3);
            load_wc(4);
            mbar_wait(sb + BAR_TD);
            load_wc(5);
            if (lane == 0 && atomicAdd(&g_seen, 1u) == NMAIN - 1) {
                g_seen = 0;
                g_ready = 0;
            }
            if (lane < 16) TS_DUMP(3);
        } else if (warp == 11) {
            if (lane < 16) reinterpret_cast<uint32_t*>(out)[cta * 16 + lane] = 0;
            asm volatile("barrier.cluster.arrive.release.aligned;" ::: "memory");
        } else if (warp == 10) {
            uint32_t* dst = reinterpret_cast<uint32_t*>(out) + grp * 32 + lane;
            asm volatile("barrier.cluster.wait.acquire.aligned;" : "+l"(dst)::"memory");
            SCHED_FENCE();
            asm volatile("bar.sync 4, 288;" ::: "memory");
            uint32_t p[4];
            lds64(p[0], p[1], sb + PARTOFF + lane * 8);
            lds64(p[2], p[3], sb + PARTOFF + 256 + lane * 8);
            asm volatile("red.relaxed.gpu.global.add.noftz.bf16x2 [%0], %1;" ::"l"(dst),
                         "r"(pack(__uint_as_float(p[0]) + __uint_as_float(p[2]), __uint_as_float(p[1]) + __uint_as_float(p[3])))
                         : "memory");
        }
    } else {
        asm volatile("setmaxnreg.inc.sync.aligned.u32 232;");
        asm volatile("barrier.cluster.arrive.relaxed.aligned;" ::: "memory");
        const uint32_t sb = __reduce_max_sync(0xffffffffu, (uint32_t)__cvta_generic_to_shared(smem) | (tid >> 10));
        const int t128 = opaque(tid & 127), lane = t128 & 31;
        const int g = lane >> 2, t = lane & 3, wq = warp & 3;
        gd0 = opaque(gd0);
        TS(28);
        float acc[84];
#pragma unroll
        for (int k = 0; k < 84; k++) asm volatile("mov.b32 %0, 0;" : "=f"(acc[k]));
        uint32_t e0[9], e1[9], e2[9];
        uint32_t X[13][2][4];
        uint32_t zq[4] = {0, 0, 0, 0};
        const uint64_t dA = mkdesc(sb + w * XDELTA, 16, 1024, 1);
        uint32_t dBlo = (uint32_t)mkdesc(sb + ZOFF, 0, 0, 0);
        const uint32_t xl0 = opaque(sb + (t & 1) * XDELTA + (16 * wq + g) * 128 + (((4 * rank + 2 * w) ^ (4 * (t & 1)) ^ g) << 4));
        const uint32_t hi_half = t >> 1;
        const uint32_t sa0 = opaque(sb + AOFF + t * 4096 + (t >> 1) * 16 + (wq * 32 + g * 4 + w) * 16);
        const uint32_t sa1 = opaque(((g & 2) << 4) | ((t & 1) << 3));
        const uint32_t zero = __reduce_max_sync(0xffffffffu, blockIdx.y | (tid >> 10));
        auto expand = [&](int k0, int k1) {
#pragma unroll
            for (int k = k0; k < k1; k++)
#pragma unroll
                for (int u = 0; u < 4; u++)
                    asm volatile("shfl.sync.idx.b32 %0, %1, %2, 31, 0xffffffff;"
                                 : "=r"(ids[k][u])
                                 : "r"(k < 12 ? cid[(k - 2) >> 2][k & 1] : w ? cid[2][1] : cid[2][0]),
                                   "r"(2 * (lane >> 3) + 8 * u + (((k - 2) >> 1) & 1)));
        };
        auto twarm = [&]() {
            float s1[8];
            WG_FENCE();
            wgmma_rs_n16_set(s1, zq, mkdesc(sb + AOFF, 16, 512, 2));
            WG_COMMIT();
            WG_WAIT0();
            pin(s1);
            asm volatile("{.reg .pred p; setp.ne.u32 p, %1, 0; @p st.shared.f32 [%1], %0;}" ::"f"(s1[0]), "r"(zero));
        };
        expand(2, 8);
        twarm();
        TS(26);
        while (clock32() - t_start < PACE1) {
        }
        gather(1);
        expand(8, 13);
        twarm();
        TS(30);
        while (clock32() - t_start < PACE2) {
        }
        gather(2);
        twarm();
        asm volatile("bar.sync 0, 384;" ::: "memory");
        auto lift = [&](int i) {
            const int m = 2 * (i >> 2) + (i & 1);
#pragma unroll
            for (int r = 0; r < 2; r++)
#pragma unroll
                for (int cc = 0; cc < 2; cc++) {
                    const uint32_t a = (xl0 ^ (cc * 16)) + xpair(i) + r * 1024;
                    if (i == 12 ? r : (i & 2)) lds128_if(X[i == 12 ? 12 : 2 * m + r][cc], a, hi_half);
                    else lds128(X[2 * m + r][cc], a);
                }
        };
        auto store_pair = [&](int m, int half, const uint32_t (&ea)[9]) {
            uint32_t a;
            if (m < 4) a = sa0 + (sa1 ^ (((m & 1) << 5) | ((m >> 1) << 3)));
            else a = sb + BOFF + t * 2048 + (wq * 32 + g * 4 + ((2 * (m & 1) + w) ^ t)) * 8;
#pragma unroll
            for (int n = half; n < 4; n += 2)
#pragma unroll
                for (int u = 0; u < 2; u++)
                    sts64(a + (m < 4 ? (8 * n + u) * 2048 + n * 32 : (8 * n + u) * 1024),
                          __byte_perm(ea[2 * n], e1[2 * n], u ? 0x7632 : 0x5410),
                          __byte_perm(ea[2 * n + 1], e1[2 * n + 1], u ? 0x7632 : 0x5410));
        };
        auto z_pair = [&](int m, uint32_t a, uint32_t b) {
            asm volatile("{.reg .pred p; setp.eq.u32 p, %4, %5; @p prmt.b32 %0, %2, %3, 0x5410; @p prmt.b32 %1, %2, %3, 0x7632;}"
                         : "+r"(zq[2 * (m >> 2)]), "+r"(zq[2 * (m >> 2) + 1])
                         : "r"(a), "r"(b), "r"(t), "r"(m & 3));
        };

        TS(29);
        mbar_wait(sb + BAR_FULL + w * 8);
        CP_WAIT(2);
        while (clock32() - t_start < START_MIN) {
        }
        if (w == 1) {
            asm volatile("bar.arrive 6, 256;" ::: "memory");
            asm volatile("bar.sync 5, 256;" ::: "memory");
        }
#pragma unroll
        for (int i = 0; i < 13; i++) {
            const uint64_t da = dA + (xpair(i) >> 4) + ((uint64_t)i << 16);
            dBlo += (uint32_t)(w ? wl(2 * i + 1) - (i ? wl(2 * i - 1) : 0) : wl(2 * i) - (i ? wl(2 * i - 2) : 0)) *
                    (uint32_t)((SLOT << 12) - (SLOT >> 3));
            const uint64_t db = mkdesc(0, 0, 1024, 1) | dBlo;
            TS(i);
            WG_FENCE();
            wgmma_ss_n168_acc(acc, da, db + w * 256);
            wgmma_ss_n168_acc(acc, da + 2, db + w * 256 + 128);
            wgmma_ss_n168_acc(acc, da + 4, db + (w ^ 1) * 256);
            wgmma_ss_n168_acc(acc, da + 6, db + (w ^ 1) * 256 + 128);
            WG_COMMIT();
            if (i == 0) {
                if (w == 0) {
                    asm volatile("bar.arrive 5, 256;" ::: "memory");
                    asm volatile("bar.sync 6, 256;" ::: "memory");
                }
            } else {
                mbar_wait(sb + bdone(2 * i - 2) + (w ^ 1) * 8, bpar(2 * i - 2));
            }
            if (i < 10) gather(i + 3);
            if (i == 12) mbar_wait(sb + BAR_SE);
            lift(i);
            if (i == 10 || i == 11) mbar_wait(sb + bdone(2 * i - 2) + w * 8, bpar(2 * i - 2));
            if (i >= 2 && !(i & 1)) {
                z_pair((i - 2) >> 1, e0[8], e1[8]);
                store_pair((i - 2) >> 1, 0, e0);
#pragma unroll
                for (int k = 0; k < 8; k++) e2[k] = e0[k];
            } else if (i >= 3) {
                store_pair((i - 3) >> 1, 1, e2);
            }
            const uint32_t rdy = i < 12 ? mbar_test(sb + bfull(2 * i + 2) + w * 8, bpar(2 * i + 2)) : 0;
            WG_WAIT0();
            pin(acc);
            if (i == 12) TS(13);
            if (i == 0) TS(27);
            if (i < 10) CP_WAIT(2);
            else if (i == 10) CP_WAIT(1);
            else if (i == 11) CP_WAIT(0);
            if (i < 12 && lane == 0) mbar_arrive(sb + bdone(2 * i) + w * 8);
#pragma unroll
            for (int k = 0; k < 9; k++) {
                const int k0 = 64 + 2 * (k & 5) + ((k >> 1) & 1);
                const uint32_t v = k == 8 ? pack(acc[80], acc[82]) : i < 12 ? pack(acc[64 + 2 * k], acc[65 + 2 * k]) : pack(acc[k0], acc[k0 + 4]);
                if (i & 1) e1[k] = v;
                else e0[k] = v;
            }
            if (i < 12) {
#pragma unroll
                for (int k = 64; k < 83; k++)
                    if (k != 81) asm volatile("mov.b32 %0, %1;" : "+f"(acc[k]) : "r"(zero));
                mbar_wait_unless(rdy, sb + bfull(2 * i + 2) + w * 8, bpar(2 * i + 2));
            } else {
                z_pair(6, e0[8], 0);
                sts128(sb + ZQOFF + w * 2048 + t128 * 16, zq[0], zq[1], zq[2], zq[3]);
                asm volatile("bar.arrive 2, 384;" ::: "memory");
            }
        }
        TS(14);

        uint32_t ai[8];
        float rd[4] = {0.f, 0.f, 0.f, 0.f};
        float th[32];
        uint32_t hw[2][4];
        auto deep_issue = [&](int k2) {
            if (!(k2 & 1)) lds128(hw[k2 >> 1], sb + W2OFF + w * 128 + t * 16 + k2 * 32);
#pragma unroll
            for (int k = 8 * k2; k < 8 * k2 + 8; k++) th[k] = gelu_tanh(acc[k]);
        };
        uint32_t h[4];
        auto deep_use = [&](int k2) {
#pragma unroll
            for (int c = 0; c < 4; c++) {
                const int k = 8 * k2 + 2 * c;
                h[c] = pack(ffma(acc[k], th[k], acc[k]), ffma(acc[k + 1], th[k + 1], acc[k + 1]));
            }
            if (k2 < 3) mma16816(rd, h, hw[k2 >> 1][2 * (k2 & 1)], hw[k2 >> 1][2 * (k2 & 1) + 1]);
        };
        auto deep_send = [&](int k0, int k1) {
#pragma unroll
            for (int k = k0; k < k1; k++)
                sts128(sb + EXOFF + w * SLOT + t128 * 16 + k * 2048, pack(acc[32 + 8 * k], acc[33 + 8 * k]),
                       pack(acc[34 + 8 * k], acc[35 + 8 * k]), pack(acc[36 + 8 * k], acc[37 + 8 * k]), pack(acc[38 + 8 * k], acc[39 + 8 * k]));
        };
        uint32_t o[4][4];
        auto deep_recv = [&](int k0, int k1) {
#pragma unroll
            for (int k = k0; k < k1; k++) lds128(o[k], sb + EXOFF + (w ^ 1) * SLOT + t128 * 16 + k * 2048);
        };
        auto deep_add = [&](int k0, int k1) {
            const uint32_t eye = (g >> 1) == t ? ((g & 1) ? 0x3f800000u : 0x3f80u) : 0u;
#pragma unroll
            for (int k = 2 * k0; k < 2 * k1; k++)
                asm volatile("mma.sync.aligned.m16n8k8.row.col.f32.bf16.bf16.f32 {%0,%1,%2,%3}, {%4,%5}, {%6}, {%0,%1,%2,%3};"
                             : "+f"(acc[4 * k]), "+f"(acc[4 * k + 1]), "+f"(acc[4 * k + 2]), "+f"(acc[4 * k + 3])
                             : "r"(o[k >> 1][2 * (k & 1)]), "r"(o[k >> 1][2 * (k & 1) + 1]), "r"(eye));
        };
        auto store_last = [&]() {
#pragma unroll
            for (int n = 0; n < 4; n++) sts64(sb + COFF + w * 4096 + n * 1024 + (t128 ^ w) * 8, e0[2 * n], e0[2 * n + 1]);
            store_pair(5, 1, e2);
        };
        const uint32_t la = (sb + AOFF + w * (16 * 2048 + 64) + (wq * 32 + g * 4 + (t ^ (g & 2))) * 16);
        const uint32_t lb = (sb + BOFF + w * (16 * 1024) + t128 * 8);
        const uint32_t lc0 = (sb + COFF + (t & 1) * (4096 + 8) + w * 2048 + (wq * 8 + g) * 32), lc1 = lc0 ^ 8;
        uint32_t Ap[2][2][4];
        auto load_a = [&](int s) {
            const int e = estep(s);
            lds128(Ap[s & 1][0], la + e * 2048 + (e >> 2) * 16);
            lds64(Ap[s & 1][1][0], Ap[s & 1][1][1], (lb ^ ((e & 6) * 4)) + e * 1024);
            if (!(s & 2)) lds64(Ap[s & 1][1][2], Ap[s & 1][1][3], ((e & 2) ? lc1 : lc0) + (e & 1) * 1024 + (e & 4) * 4);
        };
        {
            uint32_t v[2][4];
            deep_send(0, 2);
            asm volatile("bar.sync 1, 256;" ::: "memory");
            deep_recv(0, 2);
            deep_send(2, 4);
            TS(15);
            deep_add(0, 2);
            deep_issue(0);
            asm volatile("bar.sync 1, 256;" ::: "memory");
            deep_recv(2, 4);
            SCHED_FENCE();
            deep_add(2, 4);
            TS(16);
            deep_issue(1);
            deep_use(0);
            store_last();
            SCHED_FENCE();
            TS(17);
            asm volatile("bar.sync 1, 256;" ::: "memory");
            load_a(0);
            deep_issue(2);
            deep_use(1);
            SCHED_FENCE();
            deep_use(2);
            TS(18);
            asm volatile("bar.sync 3, 384;" ::: "memory");
            lds128(v[0], sb + GOFF + t128 * 16);
            lds128(v[1], sb + GOFF + 2048 + t128 * 16);
            load_a(1);
            deep_issue(3);
#pragma unroll
            for (int k = 0; k < 8; k++) ai[k] = v[k >> 2][k & 3];
        }
        TS(19);

        uint32_t fin_a, tid2;
        float sum0, sum1;
        const uint32_t hi2 = lb & 16;
        {
            uint64_t dW[4];
#pragma unroll
            for (int k = 0; k < 4; k++) dW[k] = mkdesc(sb + w * 4096, 16, 512, 2) + ((uint64_t)zero << 32) + (wcslot(0) >> 4) + (k >> 1) * 128 + (k & 1) * 2;
            uint32_t Aq[2][2][4], pq[13], gate[13];
            float S[2][2][16];
            auto scale_a = [&](int s) {
#pragma unroll
                for (int k = 0; k < ((s & 2) ? 6 : 8); k++)
                    Aq[s & 1][k >> 2][k & 3] = hmul2(Ap[s & 1][k >> 2][k & 3], ai[k < 4 ? k ^ (estep(s) & 2) : k]);
            };
            auto sbuf = [](int s) { return s <= DB0 ? 0 : (s - DB0) & 1; };
            auto issue = [&](int s) {
                const bool first = s == 0 || s == DB0 + 1;
                WG_FENCE();
                if (first) wgmma_rs_n32_set(S[sbuf(s)][0], Ap[s & 1][0], dW[0]);
                else wgmma_rs_n32_pred(S[sbuf(s)][0], Ap[s & 1][0], dW[0], zero);
                wgmma_rs_n32_acc(S[sbuf(s)][0], Ap[s & 1][1], dW[1]);
                if (first) wgmma_rs_n32_set(S[sbuf(s)][1], Aq[s & 1][0], dW[2]);
                else wgmma_rs_n32_pred(S[sbuf(s)][1], Aq[s & 1][0], dW[2], zero);
                wgmma_rs_n32_acc(S[sbuf(s)][1], Aq[s & 1][1], dW[3]);
                WG_COMMIT();
                if (s <= DB0 || s >= 14) SCHED_FENCE();
                if (s < 15) {
#pragma unroll
                    for (int k = 0; k < 4; k++)
                        asm volatile("add.s64 %0, %0, %1;" : "+l"(dW[k]) : "l"((int64_t)((wcslot(s + 1) - wcslot(s)) / 16)));
                }
            };
            scale_a(0);
            issue(0);
            deep_use(3);
            scale_a(1);
            SCHED_FENCE();
#pragma unroll
            for (int e = 0; e < 16; e++) {
                if (e >= DB0 && e < 15) {
                    issue(e + 1);
                    WG_WAIT1();
                } else {
                    WG_WAIT0();
                }
                pin(S[sbuf(e)][0]);
                pin(S[sbuf(e)][1]);
                if (e == 0 && (lb & 0xf8) == 0) mbar_arrive(sb + BAR_TD);
                if (e == 0) TS(20);
                if (e + 2 < 16) load_a(e + 2);
#pragma unroll
                for (int qq = 0; qq < 13; qq++) {
                    const int q = (qq + 12) % 13;
                    const int ix = 4 * (q >> 2) + 2 * (q & 1) + ((q >> 1) & 1);
                    uint32_t v = pack(S[sbuf(e)][0][ix], S[sbuf(e)][1][ix ^ 1]);
                    if (q == 12)
                        asm volatile("{.reg .pred p; setp.ne.u32 p, %3, 0; @p cvt.rn.bf16x2.f32 %0, %2, %1;}"
                                     : "+r"(v)
                                     : "f"(S[sbuf(e)][0][14]), "f"(S[sbuf(e)][1][15]), "r"(hi2));
                    const uint32_t x = X[q][(e >> 1) & 1][e >> 2];
                    pq[q] = (e & 1) ? hfma2_bcast<1>(v, x, pq[q]) : hfma2_bcast<0>(v, x, e ? pq[q] : 0u);
                }
                if (e < DB0) issue(e + 1);
                if (e == 14) {
                    asm volatile("mov.u32 %0, %%tid.x;" : "=r"(tid2));
                    fin_a = sb + PARTOFF + (tid2 >> 5) * 64 + (tid2 & 28) + ((tid2 ^ (tid2 >> 3)) & 3) * 512;
                }
                if (e == 14) {
#pragma unroll
                    for (int q = 0; q < 13; q++)
                        asm volatile("prmt.b32 %0, %1, 0x3f80, %2;"
                                     : "=r"(gate[q])
                                     : "r"(q < 12 ? ai[2 * (q >> 2) + (q & 1)] : hi2 ? ai[7] : ai[6]), "r"((q & 2) ? 0x3254 : 0x1054));
                }
                if (e + 2 < 16) scale_a(e + 2);
                if (e == 3 || e == 6 || e == 9) mbar_wait(sb + BAR_WC + (e / 3 + 2) * 8);
                else if (e < 15) SCHED_FENCE();
                if (e == 7) TS(21);
            }
            float r0[4] = {0.f, 0.f, 0.f, 0.f}, r1[4] = {0.f, 0.f, 0.f, 0.f}, r2[4] = {rd[0], rd[0], rd[2], rd[2]};
            mma16816(r2, h, hw[1][2], hw[1][3]);
#pragma unroll
            for (int c = 0; c < 3; c++) {
                const uint32_t a[4] = {pq[4 * c], pq[4 * c + 1], pq[4 * c + 2], pq[4 * c + 3]};
                mma16816(r0, a, gate[4 * c], gate[4 * c + 2]);
                mma16816(r1, a, gate[4 * c + 1], gate[4 * c + 3]);
            }
            asm volatile("mma.sync.aligned.m16n8k8.row.col.f32.bf16.bf16.f32 {%0,%1,%2,%3}, {%4,%5}, {%6}, {%0,%1,%2,%3};"
                         : "+f"(r2[0]), "+f"(r2[1]), "+f"(r2[2]), "+f"(r2[3])
                         : "r"(hi2 ? 0u : pq[12]), "r"(hi2 ? pq[12] : 0u), "r"(gate[12]));
            sum0 = (tid2 & 4) ? r0[1] + r2[1] : r0[0] + r2[0];
            sum1 = (tid2 & 4) ? r1[3] + r2[3] : r1[2] + r2[2];
        }
        TS(22);
        {
            asm volatile("st.shared.f32 [%0], %1; st.shared.f32 [%0 + 32], %2;" ::"r"(fin_a), "f"(sum0), "f"(sum1) : "memory");
            asm volatile("bar.arrive 4, 288;" ::: "memory");
            if (wq == 0) TS_DUMP(w);
        }
    }
}

typedef CUresult (*EncodeFn)(CUtensorMap*, CUtensorMapDataType, cuuint32_t, void*, const cuuint64_t*, const cuuint64_t*,
                             const cuuint32_t*, const cuuint32_t*, CUtensorMapInterleave, CUtensorMapSwizzle,
                             CUtensorMapL2promotion, CUtensorMapFloatOOBfill);

}

extern "C" void kernel_launch(void* const* d_in, const int* in_sizes, int n_in, void* d_out, int out_size) {
    static EncodeFn encode = nullptr;
    if (!encode) {
        void* fn = nullptr;
        cudaDriverEntryPointQueryResult qr;
        cudaGetDriverEntryPoint("cuTensorMapEncodeTiled", &fn, cudaEnableDefault, &qr);
        encode = (EncodeFn)fn;
        cudaFuncSetAttribute(fibinet_kernel, cudaFuncAttributeMaxDynamicSharedMemorySize, SMEM_BYTES);
    }
    CUtensorMap tm;
    const cuuint64_t gd[2] = {NH, NF * ND};
    const cuuint64_t gs[1] = {NH * 2};
    const cuuint32_t bd[2] = {64, 64}, es[2] = {1, 1};
    encode(&tm, CU_TENSOR_MAP_DATA_TYPE_BFLOAT16, 2, d_in[6], gd, gs, bd, es, CU_TENSOR_MAP_INTERLEAVE_NONE,
           CU_TENSOR_MAP_SWIZZLE_128B, CU_TENSOR_MAP_L2_PROMOTION_L2_256B, CU_TENSOR_MAP_FLOAT_OOB_FILL_NONE);
    CUtensorMap tb;
    const cuuint64_t gd2[2] = {ND, ND};
    const cuuint64_t gs2[1] = {ND * 2};
    encode(&tb, CU_TENSOR_MAP_DATA_TYPE_BFLOAT16, 2, d_in[4], gd2, gs2, bd, es, CU_TENSOR_MAP_INTERLEAVE_NONE,
           CU_TENSOR_MAP_SWIZZLE_128B, CU_TENSOR_MAP_L2_PROMOTION_L2_256B, CU_TENSOR_MAP_FLOAT_OOB_FILL_NONE);
    fibinet_kernel<<<NPREP + NMAIN, 384, SMEM_BYTES>>>(
        (const int*)d_in[0], (const uint4*)d_in[1], (const __nv_bfloat16*)d_in[2], (const __nv_bfloat16*)d_in[3],
        (const __nv_bfloat16*)d_in[5], (const unsigned char*)d_in[6], (const __nv_bfloat16*)d_in[7], (__nv_bfloat16*)d_out, tm, tb);
}
```

```cpp
#include <cuda_runtime.h>
#include <cuda_bf16.h>
#include <cuda.h>
#include <stdint.h>

namespace {

constexpr int NF = 26, ND = 64, NH = 256, NR = 13;
constexpr int NPREP = 4;
constexpr int NMAIN = 128;

constexpr int SLOT = 8192;
constexpr int ZOFF = 15 * SLOT;
__host__ __device__ constexpr int slot(int s) { return ZOFF - s * SLOT; }
constexpr int BOFF = ZOFF + SLOT;
constexpr int AOFF = BOFF + 32768;
constexpr int COFF = slot(12);
constexpr int MOFF = AOFF + 65536 + 128;
constexpr int BAR_FULL = MOFF, BAR_DONE = MOFF + 64, BAR_WC = MOFF + 128, BAR_SE = MOFF + 176, BAR_TD = MOFF + 184,
              BAR_Z = MOFF + 192;
__host__ __device__ constexpr int bfull(int f) { return BAR_FULL + (f & 7) * 8; }
__host__ __device__ constexpr int bdone(int f) { return BAR_DONE + (f & 7) * 8; }
__host__ __device__ constexpr int bpar(int f) { return (f >> 3) & 1; }
constexpr int W2OFF = MOFF + 256, SEOFF = MOFF + 768;
constexpr int PARTOFF = SEOFF;
constexpr int SMEM_BYTES = MOFF + 2944;
constexpr int XDELTA = 2 * SLOT;
__host__ __device__ constexpr int xpair(int i) {
    return (i & 3) == 0 ? slot(11) : (i & 3) == 1 ? BOFF : (i & 3) == 2 ? BOFF + SLOT : slot(15);
}
__host__ __device__ constexpr int wl(int f) { return f % 5 == 0 ? 1 : f % 5 == 4 ? 7 : f % 5 + 2; }
__host__ __device__ constexpr int wcslot(int c) {
    return c == 0 ? slot(3) : c == 1 ? slot(8) : c == 2 ? slot(10) : c == 3 ? slot(15) : c == 4 ? slot(13)
         : c == 5 ? slot(11) : c == 6 ? slot(9) : c == 7 ? slot(14) : c == 8 ? slot(7) : c == 9 ? slot(2)
         : c == 10 ? slot(1) : c == 11 ? slot(4) : c == 12 ? slot(5) : c == 13 ? slot(6) : c == 14 ? ZOFF : slot(3);
}
__host__ __device__ constexpr int wcfirst(int gi) { return gi < 3 ? gi : gi == 3 ? 5 : gi == 4 ? 8 : gi == 5 ? 11 : 16; }
constexpr int EXOFF = slot(5);
constexpr int ZQOFF = slot(6);
constexpr int GOFF = ZQOFF + 4096;

__device__ uint4 g_wc[2 * 16 * 8192 / 16];
__device__ uint4 g_se[2048 / 16];
__device__ uint4 g_w2[NH / 8];
__device__ unsigned g_ready;
__device__ unsigned g_seen;

__host__ __device__ constexpr int fieldof(int f) { return f < 24 ? 4 * (f >> 2) + 2 * (f & 1) + ((f >> 1) & 1) : f; }
__device__ __forceinline__ int fmap(int n) { return n < 24 ? n : 24 + ((n >> 1) & 1); }
__host__ __device__ constexpr int estep(int s) { return (s & 1) + 2 * (s >> 2) + 4 * (s & 2); }

__device__ __forceinline__ uint64_t mkdesc(uint32_t addr, uint32_t lbo, uint32_t sbo, int sw) {
    return (uint64_t)((addr & 0x3ffff) >> 4) | ((uint64_t)(lbo >> 4) << 16) | ((uint64_t)(sbo >> 4) << 32) |
           ((uint64_t)sw << 62);
}
__device__ __forceinline__ void mbar_init(uint32_t b, uint32_t n) {
    asm volatile("mbarrier.init.shared.b64 [%0], %1;" ::"r"(b), "r"(n) : "memory");
}
__device__ __forceinline__ void mbar_wait(uint32_t b, uint32_t par = 0) {
    asm volatile(
        "{\n.reg .pred p, q;\n.reg .u32 n;\n"
        "mbarrier.try_wait.parity.shared.b64 p, [%0], %1;\n@p bra.uni WD%=;\nmov.u32 n, 0;\n"
        "WL%=:\nmbarrier.try_wait.parity.shared.b64 p, [%0], %1;\n@p bra.uni WD%=;\n"
        "add.u32 n, n, 1;\nsetp.lt.u32 q, n, 4000000;\n@q bra.uni WL%=;\nWD%=:\n}\n" ::"r"(b), "r"(par)
        : "memory");
}
__device__ __forceinline__ uint32_t mbar_test(uint32_t b, uint32_t par) {
    uint32_t ok;
    asm volatile("{.reg .pred p; mbarrier.test_wait.parity.shared.b64 p, [%1], %2; selp.u32 %0, 1, 0, p;}"
                 : "=r"(ok)
                 : "r"(b), "r"(par)
                 : "memory");
    return ok;
}
__device__ __forceinline__ void mbar_wait_unless(uint32_t ok, uint32_t b, uint32_t par) {
    asm volatile(
        "{\n.reg .pred p, q;\n.reg .u32 n;\n"
        "setp.ne.u32 p, %1, 0;\n@p bra.uni WD%=;\nmov.u32 n, 0;\n"
        "WL%=:\nmbarrier.try_wait.parity.shared.b64 p, [%0], %2;\n@p bra.uni WD%=;\n"
        "add.u32 n, n, 1;\nsetp.lt.u32 q, n, 4000000;\n@q bra.uni WL%=;\nWD%=:\n}\n" ::"r"(b), "r"(ok), "r"(par)
        : "memory");
}
__device__ __forceinline__ void mbar_arrive(uint32_t b) {
    asm volatile("mbarrier.arrive.shared.b64 _, [%0];" ::"r"(b) : "memory");
}
__device__ __forceinline__ void mbar_expect(uint32_t b, uint32_t bytes) {
    asm volatile("mbarrier.arrive.expect_tx.shared.b64 _, [%0], %1;" ::"r"(b), "r"(bytes) : "memory");
}
__device__ __forceinline__ uint32_t opaque(uint32_t v) { return __shfl_sync(0xffffffffu, v, threadIdx.x); }
__device__ __forceinline__ bool elect() {
    uint32_t p;
    asm volatile("{.reg .pred q; elect.sync _|q, 0xffffffff; selp.u32 %0, 1, 0, q;}" : "=r"(p));
    return p;
}
__device__ __forceinline__ void tma2d(uint32_t dst, const CUtensorMap* m, uint32_t bar, int x, int y) {
    asm volatile(
        "cp.async.bulk.tensor.2d.shared::cluster.global.mbarrier::complete_tx::bytes [%0], [%1, {%3, %4}], [%2];" ::"r"(dst),
        "l"(m), "r"(bar), "r"(x), "r"(y)
        : "memory");
}
__device__ __forceinline__ void bulk(uint32_t dst, const void* src, uint32_t bytes, uint32_t bar) {
    asm volatile("cp.async.bulk.shared::cluster.global.mbarrier::complete_tx::bytes [%0], [%1], %2, [%3];" ::"r"(dst),
                 "l"(src), "r"(bytes), "r"(bar)
                 : "memory");
}
__device__ __forceinline__ void cp16(uint32_t dst, const void* src) {
    asm volatile("cp.async.cg.shared.global [%0], [%1], 16;" ::"r"(dst), "l"(src) : "memory");
}
__device__ __forceinline__ void lds128(uint32_t (&v)[4], uint32_t a) {
    asm volatile("ld.shared.v4.u32 {%0,%1,%2,%3}, [%4];" : "=r"(v[0]), "=r"(v[1]), "=r"(v[2]), "=r"(v[3]) : "r"(a) : "memory");
}
__device__ __forceinline__ void lds128_if(uint32_t (&v)[4], uint32_t a, uint32_t p) {
    asm volatile("{.reg .pred q; setp.ne.u32 q, %5, 0; @q ld.shared.v4.u32 {%0,%1,%2,%3}, [%4];}"
                 : "+r"(v[0]), "+r"(v[1]), "+r"(v[2]), "+r"(v[3])
                 : "r"(a), "r"(p)
                 : "memory");
}
__device__ __forceinline__ void lds64(uint32_t& x, uint32_t& y, uint32_t a) {
    asm volatile("ld.shared.v2.u32 {%0,%1}, [%2];" : "=r"(x), "=r"(y) : "r"(a) : "memory");
}
__device__ __forceinline__ void sts128(uint32_t a, uint32_t x, uint32_t y, uint32_t z, uint32_t w) {
    asm volatile("st.shared.v4.u32 [%0], {%1,%2,%3,%4};" ::"r"(a), "r"(x), "r"(y), "r"(z), "r"(w) : "memory");
}
__device__ __forceinline__ void sts64(uint32_t a, uint32_t x, uint32_t y) {
    asm volatile("st.shared.v2.u32 [%0], {%1,%2};" ::"r"(a), "r"(x), "r"(y) : "memory");
}
__device__ __forceinline__ uint32_t pack(float lo, float hi) {
    uint32_t r;
    asm volatile("cvt.rn.bf16x2.f32 %0, %1, %2;" : "=r"(r) : "f"(hi), "f"(lo));
    return r;
}
__device__ __forceinline__ uint32_t hmul2(uint32_t a, uint32_t b) {
    uint32_t r;
    asm volatile("mul.rn.bf16x2 %0, %1, %2;" : "=r"(r) : "r"(a), "r"(b));
    return r;
}
template <int H>
__device__ __forceinline__ uint32_t hfma2_bcast(uint32_t a, uint32_t x, uint32_t c) {
    uint32_t r;
    if (H)
        asm volatile("{.reg .b16 l, h; .reg .b32 s; mov.b32 {l, h}, %2; mov.b32 s, {h, h}; fma.rn.bf16x2 %0, %1, s, %3;}"
                     : "=r"(r)
                     : "r"(a), "r"(x), "r"(c));
    else
        asm volatile("{.reg .b16 l, h; .reg .b32 s; mov.b32 {l, h}, %2; mov.b32 s, {l, l}; fma.rn.bf16x2 %0, %1, s, %3;}"
                     : "=r"(r)
                     : "r"(a), "r"(x), "r"(c));
    return r;
}
__device__ __forceinline__ float ffma(float a, float b, float c) {
    float r;
    asm volatile("fma.rn.f32 %0, %1, %2, %3;" : "=f"(r) : "f"(a), "f"(b), "f"(c));
    return r;
}
__device__ __forceinline__ float tanh_fast(float x) {
    float r;
    asm volatile("tanh.approx.f32 %0, %1;" : "=f"(r) : "f"(x));
    return r;
}
__device__ __forceinline__ float gelu_tanh(float x) {
    float r;
    asm volatile(
        "{.reg .f32 a; mul.f32 a, %1, %1; fma.rn.f32 a, a, 0f3D122279, 0f3F4C422A; mul.f32 a, a, %1; tanh.approx.f32 %0, a;}"
        : "=f"(r)
        : "f"(x));
    return r;
}
__device__ __forceinline__ void mma16816(float (&d)[4], const uint32_t (&a)[4], uint32_t b0, uint32_t b1) {
    asm volatile("mma.sync.aligned.m16n8k16.row.col.f32.bf16.bf16.f32 {%0,%1,%2,%3}, {%4,%5,%6,%7}, {%8,%9}, {%0,%1,%2,%3};"
                 : "+f"(d[0]), "+f"(d[1]), "+f"(d[2]), "+f"(d[3])
                 : "r"(a[0]), "r"(a[1]), "r"(a[2]), "r"(a[3]), "r"(b0), "r"(b1));
}
__device__ __forceinline__ uint32_t clock32() {
    uint32_t c;
    asm volatile("mov.u32 %0, %%clock;" : "=r"(c)::"memory");
    return c;
}
#define WG_FENCE() asm volatile("wgmma.fence.sync.aligned;" ::: "memory")
#define WG_COMMIT() asm volatile("wgmma.commit_group.sync.aligned;" ::: "memory")
#define WG_WAIT0() asm volatile("wgmma.wait_group.sync.aligned 0;" ::: "memory")
#define WG_WAIT1() asm volatile("wgmma.wait_group.sync.aligned 1;" ::: "memory")
#define CP_COMMIT() asm volatile("cp.async.commit_group;" ::: "memory")
#define CP_WAIT(n) asm volatile("cp.async.wait_group %0;" ::"n"(n) : "memory")
#define SCHED_FENCE() asm volatile("pmevent 0;" ::: "memory")
#define PROXY_FENCE() asm volatile("fence.proxy.async.shared::cta;" ::: "memory")
template <int N>
__device__ __forceinline__ void pin(float (&d)[N]) {
#pragma unroll
    for (int i = 0; i < N; i++) asm volatile("" : "+f"(d[i])::"memory");
}
#define TS(k)
#define TS_DUMP(role)

__device__ __forceinline__ void wgmma_ss_n168_acc(float (&d)[84], uint64_t da, uint64_t db) {
    asm volatile(
        "wgmma.mma_async.sync.aligned.m64n168k16.f32.bf16.bf16 "
        "{%0,%1,%2,%3,%4,%5,%6,%7,%8,%9,%10,%11,%12,%13,%14,%15,"
        "%16,%17,%18,%19,%20,%21,%22,%23,%24,%25,%26,%27,%28,%29,%30,%31,"
        "%32,%33,%34,%35,%36,%37,%38,%39,%40,%41,%42,%43,%44,%45,%46,%47,"
        "%48,%49,%50,%51,%52,%53,%54,%55,%56,%57,%58,%59,%60,%61,%62,%63,"
        "%64,%65,%66,%67,%68,%69,%70,%71,%72,%73,%74,%75,%76,%77,%78,%79,"
        "%80,%81,%82,%83}, "
        "%84, %85, 1, 1, 1, 0, 1;"
        : "+f"(d[0]), "+f"(d[1]), "+f"(d[2]), "+f"(d[3]), "+f"(d[4]), "+f"(d[5]), "+f"(d[6]), "+f"(d[7]),
          "+f"(d[8]), "+f"(d[9]), "+f"(d[10]), "+f"(d[11]), "+f"(d[12]), "+f"(d[13]), "+f"(d[14]), "+f"(d[15]),
          "+f"(d[16]), "+f"(d[17]), "+f"(d[18]), "+f"(d[19]), "+f"(d[20]), "+f"(d[21]), "+f"(d[22]), "+f"(d[23]),
          "+f"(d[24]), "+f"(d[25]), "+f"(d[26]), "+f"(d[27]), "+f"(d[28]), "+f"(d[29]), "+f"(d[30]), "+f"(d[31]),
          "+f"(d[32]), "+f"(d[33]), "+f"(d[34]), "+f"(d[35]), "+f"(d[36]), "+f"(d[37]), "+f"(d[38]), "+f"(d[39]),
          "+f"(d[40]), "+f"(d[41]), "+f"(d[42]), "+f"(d[43]), "+f"(d[44]), "+f"(d[45]), "+f"(d[46]), "+f"(d[47]),
          "+f"(d[48]), "+f"(d[49]), "+f"(d[50]), "+f"(d[51]), "+f"(d[52]), "+f"(d[53]), "+f"(d[54]), "+f"(d[55]),
          "+f"(d[56]), "+f"(d[57]), "+f"(d[58]), "+f"(d[59]), "+f"(d[60]), "+f"(d[61]), "+f"(d[62]), "+f"(d[63]),
          "+f"(d[64]), "+f"(d[65]), "+f"(d[66]), "+f"(d[67]), "+f"(d[68]), "+f"(d[69]), "+f"(d[70]), "+f"(d[71]),
          "+f"(d[72]), "+f"(d[73]), "+f"(d[74]), "+f"(d[75]), "+f"(d[76]), "+f"(d[77]), "+f"(d[78]), "+f"(d[79]),
          "+f"(d[80]), "+f"(d[81]), "+f"(d[82]), "+f"(d[83])
        : "l"(da), "l"(db));
}

__device__ __forceinline__ void wgmma_rs_n32_set(float (&d)[16], const uint32_t (&a)[4], uint64_t db) {
    asm volatile(
        "wgmma.mma_async.sync.aligned.m64n32k16.f32.bf16.bf16 "
        "{%0,%1,%2,%3,%4,%5,%6,%7,%8,%9,%10,%11,%12,%13,%14,%15}, "
        "{%16,%17,%18,%19}, %20, 0, 1, 1, 0;"
        : "=f"(d[0]), "=f"(d[1]), "=f"(d[2]), "=f"(d[3]), "=f"(d[4]), "=f"(d[5]), "=f"(d[6]), "=f"(d[7]),
          "=f"(d[8]), "=f"(d[9]), "=f"(d[10]), "=f"(d[11]), "=f"(d[12]), "=f"(d[13]), "=f"(d[14]), "=f"(d[15])
        : "r"(a[0]), "r"(a[1]), "r"(a[2]), "r"(a[3]), "l"(db));
}

__device__ __forceinline__ void wgmma_rs_n32_acc(float (&d)[16], const uint32_t (&a)[4], uint64_t db) {
    asm volatile(
        "wgmma.mma_async.sync.aligned.m64n32k16.f32.bf16.bf16 "
        "{%0,%1,%2,%3,%4,%5,%6,%7,%8,%9,%10,%11,%12,%13,%14,%15}, "
        "{%16,%17,%18,%19}, %20, 1, 1, 1, 0;"
        : "+f"(d[0]), "+f"(d[1]), "+f"(d[2]), "+f"(d[3]), "+f"(d[4]), "+f"(d[5]), "+f"(d[6]), "+f"(d[7]),
          "+f"(d[8]), "+f"(d[9]), "+f"(d[10]), "+f"(d[11]), "+f"(d[12]), "+f"(d[13]), "+f"(d[14]), "+f"(d[15])
        : "r"(a[0]), "r"(a[1]), "r"(a[2]), "r"(a[3]), "l"(db));
}

__device__ __forceinline__ void wgmma_rs_n16_set(float (&d)[8], const uint32_t (&a)[4], uint64_t db) {
    asm volatile(
        "wgmma.mma_async.sync.aligned.m64n16k16.f32.bf16.bf16 "
        "{%0,%1,%2,%3,%4,%5,%6,%7}, "
        "{%8,%9,%10,%11}, %12, 0, 1, 1, 0;"
        : "=f"(d[0]), "=f"(d[1]), "=f"(d[2]), "=f"(d[3]), "=f"(d[4]), "=f"(d[5]), "=f"(d[6]), "=f"(d[7])
        : "r"(a[0]), "r"(a[1]), "r"(a[2]), "r"(a[3]), "l"(db));
}

__device__ __forceinline__ void wgmma_rs_n32_pred(float (&d)[16], const uint32_t (&a)[4], uint64_t db, uint32_t scale_d) {
    asm volatile(
        "{.reg .pred p; setp.ne.u32 p, %21, 0; wgmma.mma_async.sync.aligned.m64n32k16.f32.bf16.bf16 "
        "{%0,%1,%2,%3,%4,%5,%6,%7,%8,%9,%10,%11,%12,%13,%14,%15}, "
        "{%16,%17,%18,%19}, %20, p, 1, 1, 0;}"
        : "+f"(d[0]), "+f"(d[1]), "+f"(d[2]), "+f"(d[3]), "+f"(d[4]), "+f"(d[5]), "+f"(d[6]), "+f"(d[7]),
          "+f"(d[8]), "+f"(d[9]), "+f"(d[10]), "+f"(d[11]), "+f"(d[12]), "+f"(d[13]), "+f"(d[14]), "+f"(d[15])
        : "r"(a[0]), "r"(a[1]), "r"(a[2]), "r"(a[3]), "l"(db), "r"(scale_d));
}

__device__ __forceinline__ void prep_cta(uint32_t sb, int c, const __nv_bfloat16* __restrict__ wc,
                                         const __nv_bfloat16* __restrict__ se1, const __nv_bfloat16* __restrict__ se2,
                                         const __nv_bfloat16* __restrict__ w2, __nv_bfloat16* __restrict__ out) {
    const int tid = threadIdx.x, lane = tid & 31, warp = tid >> 5, s = c >> 1;
    constexpr int ZERO = 16 * NF * 128;
#pragma unroll
    for (int q = tid; q < 16 * NF * 8; q += 384) {
        const int i = q >> 7, nn = (q >> 3) & 15, j = fmap((16 * (c & 1) + nn) ^ s);
        cp16(sb + (q >> 3) * 128 + (((q & 7) ^ (i & 1) ^ ((i >> 3) << 1)) << 4), wc + ((s * NF + i) * NF + j) * ND + (q & 7) * 8);
    }
    if (tid < 8) sts128(sb + ZERO + tid * 16, 0, 0, 0, 0);
    if (tid >= 256) reinterpret_cast<uint4*>(out)[c * 128 + tid - 256] = make_uint4(0, 0, 0, 0);
    if (tid < 256) {
        const int n = ((tid >> 2) & 1) * 8 + (tid >> 5) + (s ? (c & 1) * 16 : 0);
        const int k = ((tid >> 1) & 1) * 8 + ((tid >> 3) & 3) * 2 + (tid & 1), mm = k >> 1, u = k & 1;
        const int f = s ? fmap(n) : mm < 6 ? 4 * mm + 2 * c + u : (mm == 6 && u == 0) ? 24 + c : -1;
        float v = 0.f;
        if (f >= 0 && (s ? k : n) < NR) v = __bfloat162float(s ? se2[k * NF + f] : se1[f * NR + n]);
        reinterpret_cast<__nv_bfloat16*>(g_se)[c * 256 + tid] = __float2bfloat16(s ? 0.5f * v : v);
    } else if (tid < 320) {
        const int q = tid - 256;
        reinterpret_cast<__nv_bfloat16*>(g_w2)[c * 64 + q] =
            __float2bfloat16(0.5f * __bfloat162float(w2[c * 64 + (q & 32) + 4 * (q & 6) + ((q >> 2) & 6) + (q & 1)]));
    }
    asm volatile("cp.async.wait_all;" ::: "memory");
    __syncthreads();
    const int k = 4 * (lane & 6) + 2 * (lane >> 3) + (lane & 1), i = fmap(k);
    const int g = lane >> 2, t = lane & 3;
#pragma unroll 4
    for (int task = warp; task < 128; task += 12) {
        const int nn = task & 15, eg = task >> 4, n = 16 * (c & 1) + nn;
        const uint32_t a = sb + (k < 28 ? (i * 16 + nn) * 128 : ZERO) + ((eg ^ (i & 1) ^ ((i >> 3) << 1)) << 4);
        uint4 v;
        asm volatile("ldmatrix.sync.aligned.m8n8.x4.trans.shared.b16 {%0,%1,%2,%3}, [%4];"
                     : "=r"(v.x), "=r"(v.y), "=r"(v.z), "=r"(v.w)
                     : "r"(a));
        if (t == 3) {
            const uint32_t mask = (eg & 1) ? 0xffff0000u : 0xffffu;
            v.x &= mask;
            v.y &= mask;
        }
        const int ch = (t < 2 ? t ^ ((g >> 1) & 1) : t) ^ ((n >> 1) & 3);
        const int step = (g & 1) + 2 * (eg & 1) + 2 * (g & 6);
        g_wc[(eg >> 2) * 8192 + step * 512 + ((eg >> 1) & 1) * 256 + s * 128 + n * 4 + ch] = v;
    }
    __threadfence();
    __syncthreads();
    if (tid == 0) atomicAdd(&g_ready, 1u);
}

#define PFB 1
#define PACE1 2250
#define PACE2 2850
#define START_MIN 3400
#define WDELAY 2000
#define WSTEP 400
#define WPF_AT 2600
#define WPF_STEP 800
#define POLL_AT 6500
#define T_SHIFT 300
constexpr int DB0 = 6;

__global__ void __launch_bounds__(384, 1)
fibinet_kernel(const int* __restrict__ idx, const uint4* __restrict__ table,
               const __nv_bfloat16* __restrict__ se1, const __nv_bfloat16* __restrict__ se2,
               const __nv_bfloat16* __restrict__ wc,
               const unsigned char* __restrict__ w1, const __nv_bfloat16* __restrict__ w2, __nv_bfloat16* __restrict__ out,
               const __grid_constant__ CUtensorMap tm_w1, const __grid_constant__ CUtensorMap tm_bi) {
    extern __shared__ __align__(1024) unsigned char smem[];
    const int tid = threadIdx.x;
    const int cta = blockIdx.x - NPREP, grp = cta >> 1, rank = cta & 1, lane = tid & 31;
    uint32_t ids[13][4], cid[3][2];
    const uint32_t idle = (tid >> 8) | (cta < 0);
    const uint32_t row = ((tid >> 5) & 3) * 16 + (lane >> 3);
    const unsigned char* ib = reinterpret_cast<const unsigned char*>(idx) + (int64_t)grp * (64 * NF * 4);
    {
        const unsigned char* ip = ib + (row * (NF * 4) + ((tid >> 4) & 8));
#pragma unroll
        for (int u = 0; u < 4; u++) {
            ids[0][u] = ids[1][u] = 0;
            asm volatile("{.reg .pred p; setp.eq.u32 p, %3, 0; @p ld.global.nc.L2::128B.v2.u32 {%0,%1}, [%2];}"
                         : "+r"(ids[0][u]), "+r"(ids[1][u])
                         : "l"(ip + 16 * NF * u), "r"(idle));
        }
    }
    const uint32_t t_0 = clock32();
    {
        const uint32_t co = ((tid & 127) >> 1) * (NF * 4) + ((tid >> 4) & 8) + 16 + 16 * (tid & 1);
#pragma unroll
        for (int k = 0; k < 3; k++) {
            cid[k][0] = cid[k][1] = 0;
            asm volatile("{.reg .pred p; setp.eq.u32 p, %3, 0; @p ld.global.nc.v2.u32 {%0,%1}, [%2];}"
                         : "+r"(cid[k][0]), "+r"(cid[k][1])
                         : "l"(ib + (co + 32 * k - (k == 2 ? 8 * ((tid >> 7) & tid & 1) : 0))), "r"(idle));
        }
    }
    const uint32_t t_start = (t_0 ^ (clock32() & blockIdx.y)) - T_SHIFT;
    const uint32_t sb = (uint32_t)__cvta_generic_to_shared(smem);
    uint32_t gd0 = sb + (tid >> 7) * XDELTA + row * 128 + (((lane & 7) ^ (lane >> 3) ^ ((tid >> 5) & 4)) << 4);
    const uint4* tp = table + (lane & 7);
    auto gather = [&](int i) {
#pragma unroll
        for (int u = 0; u < 4; u++)
            asm volatile(
                "{.reg .u64 a; .reg .pred p; setp.eq.u32 p, %3, 0; mad.wide.u32 a, %2, 128, %1; @p cp.async.cg.shared.global [%0], [a], 16;}" ::"r"(
                    (gd0 ^ ((u & 1) * 64)) + xpair(i) + u * 512),
                "l"(tp), "r"(ids[i][u]), "r"(i == 0 ? idle : 0u)
                : "memory");
        CP_COMMIT();
    };
    gather(0);
    if (cta < 0) {
        prep_cta(sb, blockIdx.x, wc, se1, se2, w2, out);
        return;
    }
    if (PFB && tid == 320) asm volatile("prefetch.tensormap [%0];" ::"l"(&tm_w1));
    const int warp = __reduce_max_sync(0xffffffffu, tid >> 5);
    const int w = warp >> 2;
    if (w == 2 && warp != 10 && elect()) {
        const uint32_t f = warp & 1, bar = warp == 11 ? sb + BAR_Z : sb + BAR_FULL + f * 8;
        mbar_init(bar, 1);
        if (warp == 11) {
            mbar_expect(bar, 8192);
            tma2d(sb + ZOFF, &tm_bi, bar, 32 * rank, 0);
        } else {
            const uint32_t L = (f ? wl(1) : wl(0)) * SLOT;
            mbar_expect(bar, 16384);
            tma2d(sb + ZOFF - 2 * L, &tm_w1, bar, 128 * rank + 64 * f, f * fieldof(1) * 64);
            tma2d(sb + ZOFF - L, &tm_w1, bar, 128 * rank + 64 - 64 * f, f * fieldof(1) * 64);
        }
    }
    __syncwarp();
    TS(1);

    if (w == 2) {
        asm volatile("setmaxnreg.dec.sync.aligned.u32 40;");
        auto load_wc = [&](int gi) {
            if (elect()) {
                const unsigned char* src = reinterpret_cast<const unsigned char*>(g_wc) + rank * 131072;
                mbar_expect(sb + BAR_WC + gi * 8, (wcfirst(gi + 1) - wcfirst(gi)) * 8192);
#pragma unroll
                for (int c = wcfirst(gi); c < wcfirst(gi + 1); c++) bulk(sb + wcslot(c), src + c * 8192, 8192, sb + BAR_WC + gi * 8);
            }
            __syncwarp();
        };
        if (warp == 8) {
#pragma unroll
            for (int f = 2; f < 26; f++) {
                if (f == 2) {
                    if (elect()) {
#pragma unroll
                        for (int k = 2; k < 8; k++) mbar_init(sb + BAR_FULL + k * 8, 1);
                        asm volatile("fence.mbarrier_init.release.cluster;" ::: "memory");
                    }
                    __syncwarp();
                    asm volatile("bar.arrive 0, 384;" ::: "memory");
                    TS(31);
                }
                if (f == 5) asm volatile("bar.sync 7, 64;" ::: "memory");
                if (f >= 5) mbar_wait(sb + bdone(f - 5), bpar(f - 5));
                if (f >= 2 && f < 5)
                    while (clock32() - t_start < WDELAY + (f - 2) * WSTEP) {
                    }
                if (elect()) {
                    mbar_expect(sb + bfull(f), 16384);
                    tma2d(sb + slot(2 * wl(f)), &tm_w1, sb + bfull(f), 128 * rank + 64 * (f & 1), fieldof(f) * 64);
                    tma2d(sb + slot(wl(f)), &tm_w1, sb + bfull(f), 128 * rank + 64 - 64 * (f & 1), fieldof(f) * 64);
                }
                TS(f);
            }
            asm volatile("bar.arrive 8, 128;" ::: "memory");
            TS_DUMP(2);
        } else if (warp == 9) {
            if (elect()) {
#pragma unroll
                for (int k = 0; k < 8; k++) mbar_init(sb + BAR_WC + k * 8, k < 7 ? 1 : 8);
                asm volatile("fence.mbarrier_init.release.cluster;" ::: "memory");
            }
            __syncwarp();
            asm volatile("bar.sync 0, 384;" ::: "memory");
            while (clock32() - t_start < POLL_AT) __nanosleep(100);
            if (elect()) {
                unsigned v, it = 0;
                do {
                    asm volatile("ld.acquire.gpu.global.u32 %0, [%1];" : "=r"(v) : "l"(&g_ready) : "memory");
                } while (v < NPREP && ++it < 4000000u);
                asm volatile("fence.proxy.async.global;" ::: "memory");
                mbar_expect(sb + BAR_SE, 2048 + 256);
                bulk(sb + SEOFF, g_se, 2048, sb + BAR_SE);
                bulk(sb + W2OFF, g_w2 + rank * 16, 256, sb + BAR_SE);
            }
            __syncwarp();
            TS(0);
            asm volatile("bar.sync 8, 128;" ::: "memory");
#pragma unroll
            for (int gi = 0; gi < 3; gi++) {
                mbar_wait(sb + bdone(21 + gi), bpar(21 + gi));
                load_wc(gi);
                TS(1 + gi);
            }
        } else if (warp == 10) {
            if (elect()) {
#pragma unroll
                for (int k = 0; k < 8; k++) mbar_init(sb + BAR_DONE + k * 8, 4);
                asm volatile("fence.mbarrier_init.release.cluster;" ::: "memory");
            }
            __syncwarp();
            asm volatile("bar.arrive 7, 64;" ::: "memory");
            asm volatile("bar.sync 0, 384;" ::: "memory");
#pragma unroll 1
            for (int k = 0; k < 7; k++) {
                while (clock32() - t_start < (uint32_t)(WPF_AT + k * WPF_STEP)) __nanosleep(150);
                if (lane < 6)
                    asm volatile("prefetch.global.L2 [%0];" ::"l"(w1 + (5 + k * 3 + (lane >> 1)) * 32768 + cta * 256 + (lane & 1) * 128));
            }
            asm volatile("bar.sync 8, 128;" ::: "memory");
        } else {
            mbar_wait(sb + BAR_Z);
#pragma unroll
            for (int k = 0; k < 2; k++)
                sts128(sb + ZOFF + (k * 32 + lane) * 128 + ((4 ^ (lane & 7)) << 4), 0x3c803c80u, 0x3c803c80u, 0x3c803c80u, 0x3c803c80u);
            PROXY_FENCE();
            TS(16);
            if (lane == 15 || lane == 16) TS_DUMP(3);
            asm volatile("bar.arrive 0, 384;" ::: "memory");
            asm volatile("bar.sync 8, 128;" ::: "memory");
        }
        {
            uint32_t bw[2][4], z0[4], z1[4];
            mbar_wait(sb + BAR_SE);
            lds128(bw[0], sb + SEOFF + lane * 16);
            lds128(bw[1], sb + SEOFF + 512 + lane * 16);
            asm volatile("bar.sync 2, 384;" ::: "memory");
            lds128(z0, sb + ZQOFF + (tid & 127) * 16);
            lds128(z1, sb + ZQOFF + 2048 + (tid & 127) * 16);
            TS(8);
            float s[2][4] = {};
#pragma unroll
            for (int n = 0; n < 2; n++) {
                mma16816(s[n], z0, bw[0][2 * n], bw[0][2 * n + 1]);
                mma16816(s[n], z1, bw[1][2 * n], bw[1][2 * n + 1]);
            }
            lds128(bw[0], sb + SEOFF + 1024 + lane * 16);
            lds128(bw[1], sb + SEOFF + 1536 + lane * 16);
            float th[8];
#pragma unroll
            for (int k = 0; k < 8; k++) th[k] = gelu_tanh(s[k >> 2][k & 3]);
            SCHED_FENCE();
            TS(9);
            uint32_t gq[4];
#pragma unroll
            for (int k = 0; k < 4; k++)
                gq[k] = pack(s[k >> 1][2 * (k & 1)] * ffma(th[2 * k], 0.5f, 0.5f), s[k >> 1][2 * (k & 1) + 1] * ffma(th[2 * k + 1], 0.5f, 0.5f));
            float a[4][4] = {};
#pragma unroll
            for (int n = 0; n < 4; n++) mma16816(a[n], gq, bw[n >> 1][2 * (n & 1)], bw[n >> 1][2 * (n & 1) + 1]);
#pragma unroll
            for (int k = 0; k < 16; k++)
                if (k < 13 || k == 14) a[k >> 2][k & 3] = tanh_fast(a[k >> 2][k & 3]);
            SCHED_FENCE();
            TS(10);
            uint32_t ap[8];
#pragma unroll
            for (int k = 0; k < 8; k++)
                ap[k] = pack(ffma(a[k >> 1][2 * (k & 1)], 0.5f, 0.5f), ffma(a[k >> 1][2 * (k & 1) + (k < 6)], 0.5f, 0.5f));
            sts128(sb + GOFF + (tid & 127) * 16, ap[0], ap[1], ap[2], ap[3]);
            sts128(sb + GOFF + 2048 + (tid & 127) * 16, ap[4], ap[5], ap[6], ap[7]);
            if (warp != 9) mbar_wait(sb + BAR_WC + (warp == 8 ? 0 : warp - 9) * 8);
            asm volatile("bar.arrive 3, 384;" ::: "memory");
            TS(11);
        }
        if (warp == 9) {
            load_wc(3);
            load_wc(4);
            mbar_wait(sb + BAR_TD);
            load_wc(5);
            if (lane == 0 && atomicAdd(&g_seen, 1u) == NMAIN - 1) {
                g_seen = 0;
                g_ready = 0;
            }
            if (lane < 16) TS_DUMP(3);
        } else if (warp == 10) {
            uint32_t* dst = reinterpret_cast<uint32_t*>(out) + grp * 32 + lane;
            asm volatile("" : "+l"(dst));
            SCHED_FENCE();
            asm volatile("bar.sync 4, 288;" ::: "memory");
            uint32_t p[4];
            lds64(p[0], p[1], sb + PARTOFF + lane * 8);
            lds64(p[2], p[3], sb + PARTOFF + 256 + lane * 8);
            asm volatile("red.relaxed.gpu.global.add.noftz.bf16x2 [%0], %1;" ::"l"(dst),
                         "r"(pack(__uint_as_float(p[0]) + __uint_as_float(p[2]), __uint_as_float(p[1]) + __uint_as_float(p[3])))
                         : "memory");
        }
    } else {
        asm volatile("setmaxnreg.inc.sync.aligned.u32 232;");
        const uint32_t sb = __reduce_max_sync(0xffffffffu, (uint32_t)__cvta_generic_to_shared(smem) | (tid >> 10));
        const int t128 = opaque(tid & 127), lane = t128 & 31;
        const int g = lane >> 2, t = lane & 3, wq = warp & 3;
        gd0 = opaque(gd0);
        TS(28);
        float acc[84];
#pragma unroll
        for (int k = 0; k < 84; k++) asm volatile("mov.b32 %0, 0;" : "=f"(acc[k]));
        uint32_t e0[9], e1[9], e2[9];
        uint32_t X[13][2][4];
        uint32_t zq[4] = {0, 0, 0, 0};
        const uint64_t dA = mkdesc(sb + w * XDELTA, 16, 1024, 1);
        uint32_t dBlo = (uint32_t)mkdesc(sb + ZOFF, 0, 0, 0);
        const uint32_t xl0 = opaque(sb + (t & 1) * XDELTA + (16 * wq + g) * 128 + (((4 * rank + 2 * w) ^ (4 * (t & 1)) ^ g) << 4));
        const uint32_t hi_half = t >> 1;
        const uint32_t sa0 = opaque(sb + AOFF + t * 4096 + (t >> 1) * 16 + (wq * 32 + g * 4 + w) * 16);
        const uint32_t sa1 = opaque(((g & 2) << 4) | ((t & 1) << 3));
        const uint32_t zero = __reduce_max_sync(0xffffffffu, blockIdx.y | (tid >> 10));
        auto expand = [&](int k0, int k1) {
#pragma unroll
            for (int k = k0; k < k1; k++)
#pragma unroll
                for (int u = 0; u < 4; u++)
                    asm volatile("shfl.sync.idx.b32 %0, %1, %2, 31, 0xffffffff;"
                                 : "=r"(ids[k][u])
                                 : "r"(k < 12 ? cid[(k - 2) >> 2][k & 1] : w ? cid[2][1] : cid[2][0]),
                                   "r"(2 * (lane >> 3) + 8 * u + (((k - 2) >> 1) & 1)));
        };
        auto twarm = [&]() {
            float s1[8];
            WG_FENCE();
            wgmma_rs_n16_set(s1, zq, mkdesc(sb + AOFF, 16, 512, 2));
            WG_COMMIT();
            WG_WAIT0();
            pin(s1);
            asm volatile("{.reg .pred p; setp.ne.u32 p, %1, 0; @p st.shared.f32 [%1], %0;}" ::"f"(s1[0]), "r"(zero));
        };
        expand(2, 8);
        twarm();
        TS(26);
        while (clock32() - t_start < PACE1) {
        }
        gather(1);
        expand(8, 13);
        twarm();
        TS(30);
        while (clock32() - t_start < PACE2) {
        }
        gather(2);
        twarm();
        asm volatile("bar.sync 0, 384;" ::: "memory");
        auto lift = [&](int i) {
            const int m = 2 * (i >> 2) + (i & 1);
#pragma unroll
            for (int r = 0; r < 2; r++)
#pragma unroll
                for (int cc = 0; cc < 2; cc++) {
                    const uint32_t a = (xl0 ^ (cc * 16)) + xpair(i) + r * 1024;
                    if (i == 12 ? r : (i & 2)) lds128_if(X[i == 12 ? 12 : 2 * m + r][cc], a, hi_half);
                    else lds128(X[2 * m + r][cc], a);
                }
        };
        auto store_pair = [&](int m, int half, const uint32_t (&ea)[9]) {
            uint32_t a;
            if (m < 4) a = sa0 + (sa1 ^ (((m & 1) << 5) | ((m >> 1) << 3)));
            else a = sb + BOFF + t * 2048 + (wq * 32 + g * 4 + ((2 * (m & 1) + w) ^ t)) * 8;
#pragma unroll
            for (int n = half; n < 4; n += 2)
#pragma unroll
                for (int u = 0; u < 2; u++)
                    sts64(a + (m < 4 ? (8 * n + u) * 2048 + n * 32 : (8 * n + u) * 1024),
                          __byte_perm(ea[2 * n], e1[2 * n], u ? 0x7632 : 0x5410),
                          __byte_perm(ea[2 * n + 1], e1[2 * n + 1], u ? 0x7632 : 0x5410));
        };
        auto z_pair = [&](int m, uint32_t a, uint32_t b) {
            asm volatile("{.reg .pred p; setp.eq.u32 p, %4, %5; @p prmt.b32 %0, %2, %3, 0x5410; @p prmt.b32 %1, %2, %3, 0x7632;}"
                         : "+r"(zq[2 * (m >> 2)]), "+r"(zq[2 * (m >> 2) + 1])
                         : "r"(a), "r"(b), "r"(t), "r"(m & 3));
        };

        TS(29);
        mbar_wait(sb + BAR_FULL + w * 8);
        CP_WAIT(2);
        while (clock32() - t_start < START_MIN) {
        }
        if (w == 1) {
            asm volatile("bar.arrive 6, 256;" ::: "memory");
            asm volatile("bar.sync 5, 256;" ::: "memory");
        }
#pragma unroll
        for (int i = 0; i < 13; i++) {
            const uint64_t da = dA + (xpair(i) >> 4) + ((uint64_t)i << 16);
            dBlo += (uint32_t)(w ? wl(2 * i + 1) - (i ? wl(2 * i - 1) : 0) : wl(2 * i) - (i ? wl(2 * i - 2) : 0)) *
                    (uint32_t)((SLOT << 12) - (SLOT >> 3));
            const uint64_t db = mkdesc(0, 0, 1024, 1) | dBlo;
            TS(i);
            WG_FENCE();
            wgmma_ss_n168_acc(acc, da, db + w * 256);
            wgmma_ss_n168_acc(acc, da + 2, db + w * 256 + 128);
            wgmma_ss_n168_acc(acc, da + 4, db + (w ^ 1) * 256);
            wgmma_ss_n168_acc(acc, da + 6, db + (w ^ 1) * 256 + 128);
            WG_COMMIT();
            if (i == 0) {
                if (w == 0) {
                    asm volatile("bar.arrive 5, 256;" ::: "memory");
                    asm volatile("bar.sync 6, 256;" ::: "memory");
                }
            } else {
                mbar_wait(sb + bdone(2 * i - 2) + (w ^ 1) * 8, bpar(2 * i - 2));
            }
            if (i < 10) gather(i + 3);
            if (i == 12) mbar_wait(sb + BAR_SE);
            lift(i);
            if (i == 10 || i == 11) mbar_wait(sb + bdone(2 * i - 2) + w * 8, bpar(2 * i - 2));
            if (i >= 2 && !(i & 1)) {
                z_pair((i - 2) >> 1, e0[8], e1[8]);
                store_pair((i - 2) >> 1, 0, e0);
#pragma unroll
                for (int k = 0; k < 8; k++) e2[k] = e0[k];
            } else if (i >= 3) {
                store_pair((i - 3) >> 1, 1, e2);
            }
            const uint32_t rdy = i < 12 ? mbar_test(sb + bfull(2 * i + 2) + w * 8, bpar(2 * i + 2)) : 0;
            WG_WAIT0();
            pin(acc);
            if (i == 12) TS(13);
            if (i == 0) TS(27);
            if (i < 10) CP_WAIT(2);
            else if (i == 10) CP_WAIT(1);
            else if (i == 11) CP_WAIT(0);
            if (i < 12 && lane == 0) mbar_arrive(sb + bdone(2 * i) + w * 8);
#pragma unroll
            for (int k = 0; k < 9; k++) {
                const int k0 = 64 + 2 * (k & 5) + ((k >> 1) & 1);
                const uint32_t v = k == 8 ? pack(acc[80], acc[82]) : i < 12 ? pack(acc[64 + 2 * k], acc[65 + 2 * k]) : pack(acc[k0], acc[k0 + 4]);
                if (i & 1) e1[k] = v;
                else e0[k] = v;
            }
            if (i < 12) {
#pragma unroll
                for (int k = 64; k < 83; k++)
                    if (k != 81) asm volatile("mov.b32 %0, %1;" : "+f"(acc[k]) : "r"(zero));
                mbar_wait_unless(rdy, sb + bfull(2 * i + 2) + w * 8, bpar(2 * i + 2));
            } else {
                z_pair(6, e0[8], 0);
                sts128(sb + ZQOFF + w * 2048 + t128 * 16, zq[0], zq[1], zq[2], zq[3]);
                asm volatile("bar.arrive 2, 384;" ::: "memory");
            }
        }
        TS(14);

        uint32_t ai[8];
        float rd[4] = {0.f, 0.f, 0.f, 0.f};
        float th[32];
        uint32_t hw[2][4];
        auto deep_issue = [&](int k2) {
            if (!(k2 & 1)) lds128(hw[k2 >> 1], sb + W2OFF + w * 128 + t * 16 + k2 * 32);
#pragma unroll
            for (int k = 8 * k2; k < 8 * k2 + 8; k++) th[k] = gelu_tanh(acc[k]);
        };
        uint32_t h[4];
        auto deep_use = [&](int k2) {
#pragma unroll
            for (int c = 0; c < 4; c++) {
                const int k = 8 * k2 + 2 * c;
                h[c] = pack(ffma(acc[k], th[k], acc[k]), ffma(acc[k + 1], th[k + 1], acc[k + 1]));
            }
            if (k2 < 3) mma16816(rd, h, hw[k2 >> 1][2 * (k2 & 1)], hw[k2 >> 1][2 * (k2 & 1) + 1]);
        };
        auto deep_send = [&](int k0, int k1) {
#pragma unroll
            for (int k = k0; k < k1; k++)
                sts128(sb + EXOFF + w * SLOT + t128 * 16 + k * 2048, pack(acc[32 + 8 * k], acc[33 + 8 * k]),
                       pack(acc[34 + 8 * k], acc[35 + 8 * k]), pack(acc[36 + 8 * k], acc[37 + 8 * k]), pack(acc[38 + 8 * k], acc[39 + 8 * k]));
        };
        uint32_t o[4][4];
        auto deep_recv = [&](int k0, int k1) {
#pragma unroll
            for (int k = k0; k < k1; k++) lds128(o[k], sb + EXOFF + (w ^ 1) * SLOT + t128 * 16 + k * 2048);
        };
        auto deep_add = [&](int k0, int k1) {
            const uint32_t eye = (g >> 1) == t ? ((g & 1) ? 0x3f800000u : 0x3f80u) : 0u;
#pragma unroll
            for (int k = 2 * k0; k < 2 * k1; k++)
                asm volatile("mma.sync.aligned.m16n8k8.row.col.f32.bf16.bf16.f32 {%0,%1,%2,%3}, {%4,%5}, {%6}, {%0,%1,%2,%3};"
                             : "+f"(acc[4 * k]), "+f"(acc[4 * k + 1]), "+f"(acc[4 * k + 2]), "+f"(acc[4 * k + 3])
                             : "r"(o[k >> 1][2 * (k & 1)]), "r"(o[k >> 1][2 * (k & 1) + 1]), "r"(eye));
        };
        auto store_last = [&]() {
#pragma unroll
            for (int n = 0; n < 4; n++) sts64(sb + COFF + w * 4096 + n * 1024 + (t128 ^ w) * 8, e0[2 * n], e0[2 * n + 1]);
            store_pair(5, 1, e2);
        };
        const uint32_t la = (sb + AOFF + w * (16 * 2048 + 64) + (wq * 32 + g * 4 + (t ^ (g & 2))) * 16);
        const uint32_t lb = (sb + BOFF + w * (16 * 1024) + t128 * 8);
        const uint32_t lc0 = (sb + COFF + (t & 1) * (4096 + 8) + w * 2048 + (wq * 8 + g) * 32), lc1 = lc0 ^ 8;
        uint32_t Ap[2][2][4];
        auto load_a = [&](int s) {
            const int e = estep(s);
            lds128(Ap[s & 1][0], la + e * 2048 + (e >> 2) * 16);
            lds64(Ap[s & 1][1][0], Ap[s & 1][1][1], (lb ^ ((e & 6) * 4)) + e * 1024);
            if (!(s & 2)) lds64(Ap[s & 1][1][2], Ap[s & 1][1][3], ((e & 2) ? lc1 : lc0) + (e & 1) * 1024 + (e & 4) * 4);
        };
        {
            uint32_t v[2][4];
            deep_send(0, 2);
            asm volatile("bar.sync 1, 256;" ::: "memory");
            deep_recv(0, 2);
            deep_send(2, 4);
            TS(15);
            deep_add(0, 2);
            deep_issue(0);
            asm volatile("bar.sync 1, 256;" ::: "memory");
            deep_recv(2, 4);
            SCHED_FENCE();
            deep_add(2, 4);
            TS(16);
            deep_issue(1);
            deep_use(0);
            store_last();
            SCHED_FENCE();
            TS(17);
            asm volatile("bar.sync 1, 256;" ::: "memory");
            load_a(0);
            deep_issue(2);
            deep_use(1);
            SCHED_FENCE();
            deep_use(2);
            TS(18);
            asm volatile("bar.sync 3, 384;" ::: "memory");
            lds128(v[0], sb + GOFF + t128 * 16);
            lds128(v[1], sb + GOFF + 2048 + t128 * 16);
            load_a(1);
            deep_issue(3);
#pragma unroll
            for (int k = 0; k < 8; k++) ai[k] = v[k >> 2][k & 3];
        }
        TS(19);

        uint32_t fin_a, tid2;
        float sum0, sum1;
        const uint32_t hi2 = lb & 16;
        {
            uint64_t dW[4];
#pragma unroll
            for (int k = 0; k < 4; k++) dW[k] = mkdesc(sb + w * 4096, 16, 512, 2) + ((uint64_t)zero << 32) + (wcslot(0) >> 4) + (k >> 1) * 128 + (k & 1) * 2;
            uint32_t Aq[2][2][4], pq[13], gate[13];
            float S[2][2][16];
            auto scale_a = [&](int s) {
#pragma unroll
                for (int k = 0; k < ((s & 2) ? 6 : 8); k++)
                    Aq[s & 1][k >> 2][k & 3] = hmul2(Ap[s & 1][k >> 2][k & 3], ai[k < 4 ? k ^ (estep(s) & 2) : k]);
            };
            auto sbuf = [](int s) { return s <= DB0 ? 0 : (s - DB0) & 1; };
            auto issue = [&](int s) {
                const bool first = s == 0 || s == DB0 + 1;
                WG_FENCE();
                if (first) wgmma_rs_n32_set(S[sbuf(s)][0], Ap[s & 1][0], dW[0]);
                else wgmma_rs_n32_pred(S[sbuf(s)][0], Ap[s & 1][0], dW[0], zero);
                wgmma_rs_n32_acc(S[sbuf(s)][0], Ap[s & 1][1], dW[1]);
                if (first) wgmma_rs_n32_set(S[sbuf(s)][1], Aq[s & 1][0], dW[2]);
                else wgmma_rs_n32_pred(S[sbuf(s)][1], Aq[s & 1][0], dW[2], zero);
                wgmma_rs_n32_acc(S[sbuf(s)][1], Aq[s & 1][1], dW[3]);
                WG_COMMIT();
                if (s <= DB0 || s >= 14) SCHED_FENCE();
                if (s < 15) {
#pragma unroll
                    for (int k = 0; k < 4; k++)
                        asm volatile("add.s64 %0, %0, %1;" : "+l"(dW[k]) : "l"((int64_t)((wcslot(s + 1) - wcslot(s)) / 16)));
                }
            };
            scale_a(0);
            issue(0);
            deep_use(3);
            scale_a(1);
            SCHED_FENCE();
#pragma unroll
            for (int e = 0; e < 16; e++) {
                if (e >= DB0 && e < 15) {
                    issue(e + 1);
                    WG_WAIT1();
                } else {
                    WG_WAIT0();
                }
                pin(S[sbuf(e)][0]);
                pin(S[sbuf(e)][1]);
                if (e == 0 && (lb & 0xf8) == 0) mbar_arrive(sb + BAR_TD);
                if (e == 0) TS(20);
                if (e + 2 < 16) load_a(e + 2);
#pragma unroll
                for (int qq = 0; qq < 13; qq++) {
                    const int q = (qq + 12) % 13;
                    const int ix = 4 * (q >> 2) + 2 * (q & 1) + ((q >> 1) & 1);
                    uint32_t v = pack(S[sbuf(e)][0][ix], S[sbuf(e)][1][ix ^ 1]);
                    if (q == 12)
                        asm volatile("{.reg .pred p; setp.ne.u32 p, %3, 0; @p cvt.rn.bf16x2.f32 %0, %2, %1;}"
                                     : "+r"(v)
                                     : "f"(S[sbuf(e)][0][14]), "f"(S[sbuf(e)][1][15]), "r"(hi2));
                    const uint32_t x = X[q][(e >> 1) & 1][e >> 2];
                    pq[q] = (e & 1) ? hfma2_bcast<1>(v, x, pq[q]) : hfma2_bcast<0>(v, x, e ? pq[q] : 0u);
                }
                if (e < DB0) issue(e + 1);
                if (e == 14) {
                    asm volatile("mov.u32 %0, %%tid.x;" : "=r"(tid2));
                    fin_a = sb + PARTOFF + (tid2 >> 5) * 64 + (tid2 & 28) + ((tid2 ^ (tid2 >> 3)) & 3) * 512;
                }
                if (e == 14) {
#pragma unroll
                    for (int q = 0; q < 13; q++)
                        asm volatile("prmt.b32 %0, %1, 0x3f80, %2;"
                                     : "=r"(gate[q])
                                     : "r"(q < 12 ? ai[2 * (q >> 2) + (q & 1)] : hi2 ? ai[7] : ai[6]), "r"((q & 2) ? 0x3254 : 0x1054));
                }
                if (e + 2 < 16) scale_a(e + 2);
                if (e == 3 || e == 6 || e == 9) mbar_wait(sb + BAR_WC + (e / 3 + 2) * 8);
                else if (e < 15) SCHED_FENCE();
                if (e == 7) TS(21);
            }
            float r0[4] = {0.f, 0.f, 0.f, 0.f}, r1[4] = {0.f, 0.f, 0.f, 0.f}, r2[4] = {rd[0], rd[0], rd[2], rd[2]};
            mma16816(r2, h, hw[1][2], hw[1][3]);
#pragma unroll
            for (int c = 0; c < 3; c++) {
                const uint32_t a[4] = {pq[4 * c], pq[4 * c + 1], pq[4 * c + 2], pq[4 * c + 3]};
                mma16816(r0, a, gate[4 * c], gate[4 * c + 2]);
                mma16816(r1, a, gate[4 * c + 1], gate[4 * c + 3]);
            }
            asm volatile("mma.sync.aligned.m16n8k8.row.col.f32.bf16.bf16.f32 {%0,%1,%2,%3}, {%4,%5}, {%6}, {%0,%1,%2,%3};"
                         : "+f"(r2[0]), "+f"(r2[1]), "+f"(r2[2]), "+f"(r2[3])
                         : "r"(hi2 ? 0u : pq[12]), "r"(hi2 ? pq[12] : 0u), "r"(gate[12]));
            sum0 = (tid2 & 4) ? r0[1] + r2[1] : r0[0] + r2[0];
            sum1 = (tid2 & 4) ? r1[3] + r2[3] : r1[2] + r2[2];
        }
        TS(22);
        {
            asm volatile("st.shared.f32 [%0], %1; st.shared.f32 [%0 + 32], %2;" ::"r"(fin_a), "f"(sum0), "f"(sum1) : "memory");
            asm volatile("bar.arrive 4, 288;" ::: "memory");
            if (wq == 0) TS_DUMP(w);
        }
    }
}

typedef CUresult (*EncodeFn)(CUtensorMap*, CUtensorMapDataType, cuuint32_t, void*, const cuuint64_t*, const cuuint64_t*,
                             const cuuint32_t*, const cuuint32_t*, CUtensorMapInterleave, CUtensorMapSwizzle,
                             CUtensorMapL2promotion, CUtensorMapFloatOOBfill);

}

extern "C" void kernel_launch(void* const* d_in, const int* in_sizes, int n_in, void* d_out, int out_size) {
    static EncodeFn encode = nullptr;
    if (!encode) {
        void* fn = nullptr;
        cudaDriverEntryPointQueryResult qr;
        cudaGetDriverEntryPoint("cuTensorMapEncodeTiled", &fn, cudaEnableDefault, &qr);
        encode = (EncodeFn)fn;
        cudaFuncSetAttribute(fibinet_kernel, cudaFuncAttributeMaxDynamicSharedMemorySize, SMEM_BYTES);
    }
    CUtensorMap tm;
    const cuuint64_t gd[2] = {NH, NF * ND};
    const cuuint64_t gs[1] = {NH * 2};
    const cuuint32_t bd[2] = {64, 64}, es[2] = {1, 1};
    encode(&tm, CU_TENSOR_MAP_DATA_TYPE_BFLOAT16, 2, d_in[6], gd, gs, bd, es, CU_TENSOR_MAP_INTERLEAVE_NONE,
           CU_TENSOR_MAP_SWIZZLE_128B, CU_TENSOR_MAP_L2_PROMOTION_L2_256B, CU_TENSOR_MAP_FLOAT_OOB_FILL_NONE);
    CUtensorMap tb;
    const cuuint64_t gd2[2] = {ND, ND};
    const cuuint64_t gs2[1] = {ND * 2};
    encode(&tb, CU_TENSOR_MAP_DATA_TYPE_BFLOAT16, 2, d_in[4], gd2, gs2, bd, es, CU_TENSOR_MAP_INTERLEAVE_NONE,
           CU_TENSOR_MAP_SWIZZLE_128B, CU_TENSOR_MAP_L2_PROMOTION_L2_256B, CU_TENSOR_MAP_FLOAT_OOB_FILL_NONE);
    fibinet_kernel<<<NPREP + NMAIN, 384, SMEM_BYTES>>>(
        (const int*)d_in[0], (const uint4*)d_in[1], (const __nv_bfloat16*)d_in[2], (const __nv_bfloat16*)d_in[3],
        (const __nv_bfloat16*)d_in[5], (const unsigned char*)d_in[6], (const __nv_bfloat16*)d_in[7], (__nv_bfloat16*)d_out, tm, tb);
}
```
